```python
import torch

def _softmax(x, axis=-1):
    return torch.softmax(x, dim=axis)

def _gelu(x):
    return torch.nn.functional.gelu(x, approximate='tanh')

def _silu(x):
    return torch.nn.functional.silu(x)

def _sigmoid(x):
    return torch.sigmoid(x)

def _layernorm(x, axis=-1, eps=1e-05):
    m = x.mean(dim=axis, keepdim=True)
    v = x.var(dim=axis, keepdim=True, unbiased=False)
    return (x - m) / torch.sqrt(v + eps)

def _scatter_add(tgt, idx, src, axis=0):
    return tgt.clone().index_add_(axis, idx, src)

def _segment_sum(src, seg, n):
    out = torch.zeros((n,) + src.shape[1:], dtype=src.dtype)
    return out.index_add_(0, seg, src)

def _pad(x, pw):
    flat = tuple((v for pair in reversed(pw) for v in pair))
    return torch.nn.functional.pad(x, flat)
kernel_name = 'parallel_sum__memory_aug_recurrent_mem_tr__mixer_token_mlp__prompt'

def setup_inputs():

    _w = lambda a: (lambda t: t.to(torch.bfloat16) if t.is_floating_point() else t)(torch.as_tensor(a))

    def _A_setup():
        B, S, Dm = (1, 2048, 576)
        H, Dh = (32, 128)
        M, seg = (8, 32)
        seg = min(seg, S)
        S = S // seg * seg
        return {'x': _w((lambda *s: torch.randn(*s, dtype=torch.bfloat16) * 0.05)(B, S, Dm)), 'mem0': _w((lambda *s: torch.randn(*s, dtype=torch.bfloat16) * 0.2)(B, M, Dm)), 'Wq': _w((lambda *s: torch.randn(*s, dtype=torch.bfloat16) * 1.6)(Dm, H, Dh) * Dm ** (-0.5)), 'Wk': _w((lambda *s: torch.randn(*s, dtype=torch.bfloat16) * 1.6)(Dm, H, Dh) * Dm ** (-0.5)), 'Wv': _w((lambda *s: torch.randn(*s, dtype=torch.bfloat16) * 0.2)(Dm, H, Dh) * Dm ** (-0.5)), 'Wo': _w((lambda *s: torch.randn(*s, dtype=torch.bfloat16) * 0.2)(H, Dh, Dm) * (H * Dh) ** (-0.5)), 'seg_len': seg}
    _A_in = _A_setup()

    def _B_setup():
        B, S, D, F = (1, 2048, 576, 4608)
        return {'x': _w((lambda *s: torch.randn(*s, dtype=torch.bfloat16) * 0.05)(B, S, D)), 'w1': _w((lambda *s: torch.randn(*s, dtype=torch.bfloat16) * 0.4)(S, F) * S ** (-0.5)), 'b1': _w((lambda *s: torch.randn(*s, dtype=torch.bfloat16) * 3.2)(F) * 0.02), 'w2': _w((lambda *s: torch.randn(*s, dtype=torch.bfloat16) * 0.2)(F, S) * F ** (-0.5)), 'b2': _w((lambda *s: torch.randn(*s, dtype=torch.bfloat16) * 0.4)(S) * 0.02)}
    _B_in = _B_setup()
    return {'A_x': _A_in['x'], 'A_mem0': _A_in['mem0'], 'A_Wq': _A_in['Wq'], 'A_Wk': _A_in['Wk'], 'A_Wv': _A_in['Wv'], 'A_Wo': _A_in['Wo'], 'A_seg_len': _A_in['seg_len'], 'B_x': _B_in['x'], 'B_w1': _B_in['w1'], 'B_b1': _B_in['b1'], 'B_w2': _B_in['w2'], 'B_b2': _B_in['b2']}

def reference(A_x, A_mem0, A_Wq, A_Wk, A_Wv, A_Wo, A_seg_len, B_x, B_w1, B_b1, B_w2, B_b2):

    def _A_ref(x, mem0, Wq, Wk, Wv, Wo, seg_len):
        B, S, Dm = x.shape
        H, Dh = (Wq.shape[1], Wq.shape[2])
        M = mem0.shape[1]
        scale = Dh ** (-0.5)
        n_seg = S // seg_len
        L = M + seg_len
        idx = torch.arange(L)
        mask = (idx[:, None] < M) | (idx[:, None] >= idx[None, :])
        mem = mem0
        outs = []
        for s in range(n_seg):
            xs = x[:, s * seg_len:(s + 1) * seg_len, :].clone()
            h = torch.concatenate([mem, xs], axis=1)
            q = torch.einsum('btd,dhe->bhte', h, Wq)
            k = torch.einsum('btd,dhe->bhte', h, Wk)
            v = torch.einsum('btd,dhe->bhte', h, Wv)
            scores = torch.einsum('bhqe,bhke->bhqk', q, k) * scale
            scores = torch.where(mask[None, None], scores, -1000000000.0)
            p = _softmax(scores, axis=-1)
            o = torch.einsum('bhqk,bhke->bhqe', p, v)
            o = torch.einsum('bhte,hed->btd', o, Wo)
            mem = o[:, :M, :].clone()
            outs.append(o[:, M:, :])
        return torch.concatenate(outs, axis=1)

    def _B_ref(x, w1, b1, w2, b2):
        B, S, D = x.shape
        h = _layernorm(x, axis=-1)
        u = torch.einsum('bsd,sf->bdf', h, w1) + b1
        u = _gelu(u)
        y = torch.einsum('bdf,fs->bds', u, w2) + b2
        return (lambda x, *d: x.permute(*d))(y, 0, 2, 1)
    x = A_x
    xn = _layernorm(x, axis=-1)
    return x + _A_ref(xn, A_mem0, A_Wq, A_Wk, A_Wv, A_Wo, A_seg_len) + _B_ref(xn, B_w1, B_b1, B_w2, B_b2)
```

```cpp
#include <cuda_runtime.h>
#include <cuda_bf16.h>
#include <cuda.h>
#include <stdint.h>

typedef __nv_bfloat16 bf16;
constexpr int S_ = 2048, D_ = 576, HD_ = 4096, F_ = 4608, NSEG = 64;

__device__ bf16 g_xn[S_ * D_];
__device__ bf16 g_h2[S_ * D_];
__device__ bf16 g_q[S_ * HD_];
__device__ bf16 g_k[S_ * HD_];
__device__ bf16 g_v[S_ * HD_];
__device__ bf16 g_o[S_ * HD_];
__device__ bf16 g_km[NSEG * 8 * HD_];
__device__ bf16 g_vm[NSEG * 8 * HD_];
__device__ bf16 g_ut[F_ * D_];
__device__ float g_yb[S_ * D_];
__device__ float g_part[2 * 8 * 8 * 5 * 32 * 4];
__device__ unsigned int g_cnt[64];

__device__ __forceinline__ uint32_t smem_u32(const void* p) { return (uint32_t)__cvta_generic_to_shared(p); }
__device__ __forceinline__ void mbar_init(uint32_t b, uint32_t c) { asm volatile("mbarrier.init.shared::cta.b64 [%0], %1;" ::"r"(b), "r"(c)); }
__device__ __forceinline__ void mbar_expect(uint32_t b, uint32_t bytes) { asm volatile("mbarrier.arrive.expect_tx.shared::cta.b64 _, [%0], %1;" ::"r"(b), "r"(bytes) : "memory"); }
__device__ __forceinline__ void mbar_wait(uint32_t b, uint32_t parity) {
  uint32_t ok;
  do { asm volatile("{\n.reg .pred p;\nmbarrier.try_wait.parity.shared::cta.b64 p, [%1], %2;\nselp.u32 %0, 1, 0, p;\n}" : "=r"(ok) : "r"(b), "r"(parity) : "memory"); } while (!ok);
}
__device__ __forceinline__ void mbar_wait_cl(uint32_t b, uint32_t parity) {
  uint32_t ok;
  do { asm volatile("{\n.reg .pred p;\nmbarrier.try_wait.parity.acquire.cluster.shared::cta.b64 p, [%1], %2;\nselp.u32 %0, 1, 0, p;\n}" : "=r"(ok) : "r"(b), "r"(parity) : "memory"); } while (!ok);
}
__device__ __forceinline__ uint32_t mapa(uint32_t a, uint32_t r) { uint32_t o; asm("mapa.shared::cluster.u32 %0, %1, %2;" : "=r"(o) : "r"(a), "r"(r)); return o; }
__device__ __forceinline__ void mbar_arrive_remote(uint32_t remote_b) { asm volatile("mbarrier.arrive.release.cluster.shared::cluster.b64 _, [%0];" ::"r"(remote_b) : "memory"); }
__device__ __forceinline__ uint32_t cluster_rank() { uint32_t r; asm("mov.u32 %0, %%cluster_ctarank;" : "=r"(r)); return r; }
__device__ __forceinline__ void cluster_sync() { asm volatile("barrier.cluster.arrive.release.aligned;\nbarrier.cluster.wait.acquire.aligned;" ::: "memory"); }
__device__ __forceinline__ void tma2d(uint32_t dst, const CUtensorMap* m, int c0, int c1, uint32_t bar) {
  asm volatile("cp.async.bulk.tensor.2d.shared::cluster.global.mbarrier::complete_tx::bytes [%0], [%1, {%3, %4}], [%2];"
               ::"r"(dst), "l"(m), "r"(bar), "r"(c0), "r"(c1) : "memory");
}
__device__ __forceinline__ void tma2d_mc(uint32_t dst, const CUtensorMap* m, int c0, int c1, uint32_t bar, uint16_t mask) {
  asm volatile("cp.async.bulk.tensor.2d.shared::cluster.global.mbarrier::complete_tx::bytes.multicast::cluster [%0], [%1, {%3, %4}], [%2], %5;"
               ::"r"(dst), "l"(m), "r"(bar), "r"(c0), "r"(c1), "h"(mask) : "memory");
}
__device__ __forceinline__ uint32_t pack_bf16(float a, float b) { __nv_bfloat162 t = __floats2bfloat162_rn(a, b); return *(uint32_t*)&t; }
__device__ __forceinline__ float2 unpack_bf16(uint32_t u) { return __bfloat1622float2(*(__nv_bfloat162*)&u); }
__device__ __forceinline__ void mma16816(float (&c)[4], const uint32_t (&a)[4], uint32_t b0, uint32_t b1) {
  asm volatile("mma.sync.aligned.m16n8k16.row.col.f32.bf16.bf16.f32 {%0,%1,%2,%3},{%4,%5,%6,%7},{%8,%9},{%0,%1,%2,%3};"
               : "+f"(c[0]), "+f"(c[1]), "+f"(c[2]), "+f"(c[3]) : "r"(a[0]), "r"(a[1]), "r"(a[2]), "r"(a[3]), "r"(b0), "r"(b1));
}
__device__ __forceinline__ void ldsm4(uint32_t (&r)[4], uint32_t a) { asm volatile("ldmatrix.sync.aligned.m8n8.x4.shared.b16 {%0,%1,%2,%3},[%4];" : "=r"(r[0]), "=r"(r[1]), "=r"(r[2]), "=r"(r[3]) : "r"(a) : "memory"); }
__device__ __forceinline__ void ldsm4t(uint32_t (&r)[4], uint32_t a) { asm volatile("ldmatrix.sync.aligned.m8n8.x4.trans.shared.b16 {%0,%1,%2,%3},[%4];" : "=r"(r[0]), "=r"(r[1]), "=r"(r[2]), "=r"(r[3]) : "r"(a) : "memory"); }
__device__ __forceinline__ uint32_t movm(uint32_t a) { uint32_t o; asm volatile("movmatrix.sync.aligned.m8n8.trans.b16 %0, %1;" : "=r"(o) : "r"(a)); return o; }
__device__ __forceinline__ void cp16(uint32_t dst, const void* src) { asm volatile("cp.async.cg.shared.global [%0], [%1], 16;" ::"r"(dst), "l"(src) : "memory"); }
__device__ __forceinline__ void pdl_wait() { asm volatile("griddepcontrol.wait;" ::: "memory"); }
__device__ __forceinline__ void pdl_launch() { asm volatile("griddepcontrol.launch_dependents;" ::: "memory"); }

__global__ void __launch_bounds__(256) ln_kernel(const bf16* __restrict__ x) {
  int row = blockIdx.x * 8 + (threadIdx.x >> 5), lane = threadIdx.x & 31;
  if (threadIdx.x == 0 && blockIdx.x == 0) g_cnt[0] = 0;
  for (int i = blockIdx.x * 256 + threadIdx.x; i < 2 * 64 * 640; i += 256 * 256) g_part[i] = 0.f;
  const uint32_t* xr = (const uint32_t*)(x + (size_t)row * D_);
  float v[18]; float s = 0.f;
#pragma unroll
  for (int i = 0; i < 9; i++) { float2 f = unpack_bf16(xr[lane + 32 * i]); v[2 * i] = f.x; v[2 * i + 1] = f.y; s += f.x + f.y; }
#pragma unroll
  for (int pass = 0; pass < 2; pass++) {
#pragma unroll
    for (int o = 16; o; o >>= 1) s += __shfl_xor_sync(~0u, s, o);
    float m = s * (1.f / D_), q = 0.f;
#pragma unroll
    for (int i = 0; i < 18; i++) { v[i] -= m; q += v[i] * v[i]; }
#pragma unroll
    for (int o = 16; o; o >>= 1) q += __shfl_xor_sync(~0u, q, o);
    float r = 1.f / sqrtf(q * (1.f / D_) + 1e-5f);
    uint32_t* dst = (uint32_t*)((pass == 0 ? g_xn : g_h2) + (size_t)row * D_);
    s = 0.f;
#pragma unroll
    for (int i = 0; i < 9; i++) {
      uint32_t p = pack_bf16(v[2 * i] * r, v[2 * i + 1] * r);
      dst[lane + 32 * i] = p;
      float2 f = unpack_bf16(p); v[2 * i] = f.x; v[2 * i + 1] = f.y; s += f.x + f.y;
    }
  }
}

template<int TA> __device__ __forceinline__ void wgmma_n256(float (&d)[128], uint64_t da, uint64_t db, int sc) {
  asm volatile("{\n.reg .pred p;\nsetp.ne.b32 p, %130, 0;\n"
    "wgmma.mma_async.sync.aligned.m64n256k16.f32.bf16.bf16 {%0, %1, %2, %3, %4, %5, %6, %7, %8, %9, %10, %11, %12, %13, %14, %15, %16, %17, %18, %19, %20, %21, %22, %23, %24, %25, %26, %27, %28, %29, %30, %31, %32, %33, %34, %35, %36, %37, %38, %39, %40, %41, %42, %43, %44, %45, %46, %47, %48, %49, %50, %51, %52, %53, %54, %55, %56, %57, %58, %59, %60, %61, %62, %63, %64, %65, %66, %67, %68, %69, %70, %71, %72, %73, %74, %75, %76, %77, %78, %79, %80, %81, %82, %83, %84, %85, %86, %87, %88, %89, %90, %91, %92, %93, %94, %95, %96, %97, %98, %99, %100, %101, %102, %103, %104, %105, %106, %107, %108, %109, %110, %111, %112, %113, %114, %115, %116, %117, %118, %119, %120, %121, %122, %123, %124, %125, %126, %127}, %128, %129, p, 1, 1, %131, 1;\n}\n"
    : "+f"(d[0]), "+f"(d[1]), "+f"(d[2]), "+f"(d[3]), "+f"(d[4]), "+f"(d[5]), "+f"(d[6]), "+f"(d[7]), "+f"(d[8]), "+f"(d[9]), "+f"(d[10]), "+f"(d[11]), "+f"(d[12]), "+f"(d[13]), "+f"(d[14]), "+f"(d[15]), "+f"(d[16]), "+f"(d[17]), "+f"(d[18]), "+f"(d[19]), "+f"(d[20]), "+f"(d[21]), "+f"(d[22]), "+f"(d[23]), "+f"(d[24]), "+f"(d[25]), "+f"(d[26]), "+f"(d[27]), "+f"(d[28]), "+f"(d[29]), "+f"(d[30]), "+f"(d[31]), "+f"(d[32]), "+f"(d[33]), "+f"(d[34]), "+f"(d[35]), "+f"(d[36]), "+f"(d[37]), "+f"(d[38]), "+f"(d[39]), "+f"(d[40]), "+f"(d[41]), "+f"(d[42]), "+f"(d[43]), "+f"(d[44]), "+f"(d[45]), "+f"(d[46]), "+f"(d[47]), "+f"(d[48]), "+f"(d[49]), "+f"(d[50]), "+f"(d[51]), "+f"(d[52]), "+f"(d[53]), "+f"(d[54]), "+f"(d[55]), "+f"(d[56]), "+f"(d[57]), "+f"(d[58]), "+f"(d[59]), "+f"(d[60]), "+f"(d[61]), "+f"(d[62]), "+f"(d[63]), "+f"(d[64]), "+f"(d[65]), "+f"(d[66]), "+f"(d[67]), "+f"(d[68]), "+f"(d[69]), "+f"(d[70]), "+f"(d[71]), "+f"(d[72]), "+f"(d[73]), "+f"(d[74]), "+f"(d[75]), "+f"(d[76]), "+f"(d[77]), "+f"(d[78]), "+f"(d[79]), "+f"(d[80]), "+f"(d[81]), "+f"(d[82]), "+f"(d[83]), "+f"(d[84]), "+f"(d[85]), "+f"(d[86]), "+f"(d[87]), "+f"(d[88]), "+f"(d[89]), "+f"(d[90]), "+f"(d[91]), "+f"(d[92]), "+f"(d[93]), "+f"(d[94]), "+f"(d[95]), "+f"(d[96]), "+f"(d[97]), "+f"(d[98]), "+f"(d[99]), "+f"(d[100]), "+f"(d[101]), "+f"(d[102]), "+f"(d[103]), "+f"(d[104]), "+f"(d[105]), "+f"(d[106]), "+f"(d[107]), "+f"(d[108]), "+f"(d[109]), "+f"(d[110]), "+f"(d[111]), "+f"(d[112]), "+f"(d[113]), "+f"(d[114]), "+f"(d[115]), "+f"(d[116]), "+f"(d[117]), "+f"(d[118]), "+f"(d[119]), "+f"(d[120]), "+f"(d[121]), "+f"(d[122]), "+f"(d[123]), "+f"(d[124]), "+f"(d[125]), "+f"(d[126]), "+f"(d[127])
    : "l"(da), "l"(db), "r"(sc), "n"(TA));
}

template<int TA> __device__ __forceinline__ void wgmma_n192(float (&d)[128], uint64_t da, uint64_t db, int sc) {
  asm volatile("{\n.reg .pred p;\nsetp.ne.b32 p, %98, 0;\n"
    "wgmma.mma_async.sync.aligned.m64n192k16.f32.bf16.bf16 {%0, %1, %2, %3, %4, %5, %6, %7, %8, %9, %10, %11, %12, %13, %14, %15, %16, %17, %18, %19, %20, %21, %22, %23, %24, %25, %26, %27, %28, %29, %30, %31, %32, %33, %34, %35, %36, %37, %38, %39, %40, %41, %42, %43, %44, %45, %46, %47, %48, %49, %50, %51, %52, %53, %54, %55, %56, %57, %58, %59, %60, %61, %62, %63, %64, %65, %66, %67, %68, %69, %70, %71, %72, %73, %74, %75, %76, %77, %78, %79, %80, %81, %82, %83, %84, %85, %86, %87, %88, %89, %90, %91, %92, %93, %94, %95}, %96, %97, p, 1, 1, %99, 1;\n}\n"
    : "+f"(d[0]), "+f"(d[1]), "+f"(d[2]), "+f"(d[3]), "+f"(d[4]), "+f"(d[5]), "+f"(d[6]), "+f"(d[7]), "+f"(d[8]), "+f"(d[9]), "+f"(d[10]), "+f"(d[11]), "+f"(d[12]), "+f"(d[13]), "+f"(d[14]), "+f"(d[15]), "+f"(d[16]), "+f"(d[17]), "+f"(d[18]), "+f"(d[19]), "+f"(d[20]), "+f"(d[21]), "+f"(d[22]), "+f"(d[23]), "+f"(d[24]), "+f"(d[25]), "+f"(d[26]), "+f"(d[27]), "+f"(d[28]), "+f"(d[29]), "+f"(d[30]), "+f"(d[31]), "+f"(d[32]), "+f"(d[33]), "+f"(d[34]), "+f"(d[35]), "+f"(d[36]), "+f"(d[37]), "+f"(d[38]), "+f"(d[39]), "+f"(d[40]), "+f"(d[41]), "+f"(d[42]), "+f"(d[43]), "+f"(d[44]), "+f"(d[45]), "+f"(d[46]), "+f"(d[47]), "+f"(d[48]), "+f"(d[49]), "+f"(d[50]), "+f"(d[51]), "+f"(d[52]), "+f"(d[53]), "+f"(d[54]), "+f"(d[55]), "+f"(d[56]), "+f"(d[57]), "+f"(d[58]), "+f"(d[59]), "+f"(d[60]), "+f"(d[61]), "+f"(d[62]), "+f"(d[63]), "+f"(d[64]), "+f"(d[65]), "+f"(d[66]), "+f"(d[67]), "+f"(d[68]), "+f"(d[69]), "+f"(d[70]), "+f"(d[71]), "+f"(d[72]), "+f"(d[73]), "+f"(d[74]), "+f"(d[75]), "+f"(d[76]), "+f"(d[77]), "+f"(d[78]), "+f"(d[79]), "+f"(d[80]), "+f"(d[81]), "+f"(d[82]), "+f"(d[83]), "+f"(d[84]), "+f"(d[85]), "+f"(d[86]), "+f"(d[87]), "+f"(d[88]), "+f"(d[89]), "+f"(d[90]), "+f"(d[91]), "+f"(d[92]), "+f"(d[93]), "+f"(d[94]), "+f"(d[95])
    : "l"(da), "l"(db), "r"(sc), "n"(TA));
}

struct GemmParams {
  CUtensorMap mA[4];
  CUtensorMap mB[6];
  const bf16* x; const bf16* b1; const bf16* b2; bf16* out;
  int stride;
  int wait_at_end;
  uint16_t job[960];
};
constexpr int NSTAGE = 4, STAGE_BYTES = 49152;
constexpr int GEMM_SMEM = NSTAGE * STAGE_BYTES + 8 * 2048 + 256 + 1024;

__device__ __forceinline__ uint64_t mkdesc(uint32_t addr, uint32_t lbo, uint32_t sbo) {
  return (uint64_t)((addr & 0x3FFFF) >> 4) | ((uint64_t)(lbo >> 4) << 16) | ((uint64_t)(sbo >> 4) << 32) | (1ull << 62);
}
__device__ __forceinline__ float gelu_tanh(float u) {
  float z = 0.7978845608028654f * (u + 0.044715f * u * u * u);
  float e = __expf(2.f * z);
  float th = 1.f - __fdividef(2.f, e + 1.f);
  return 0.5f * u * (1.f + th);
}
template <int BN, int TA>
__device__ __forceinline__ void gemm_mainloop(float (&d)[128], int kiters, uint32_t sbase, uint32_t fullb, uint32_t emptyb_l, uint32_t emptyb_r,
                                              int wg, int& stage, uint32_t& phase, bool elect) {
  int prev = -1;
  for (int k = 0; k < kiters; k++) {
    mbar_wait(fullb + stage * 8, phase);
    uint32_t a = sbase + stage * STAGE_BYTES + wg * 8192, b = sbase + stage * STAGE_BYTES + 16384;
    asm volatile("wgmma.fence.sync.aligned;" ::: "memory");
#pragma unroll
    for (int kk = 0; kk < 4; kk++) {
      uint64_t da = TA ? mkdesc(a + kk * 2048, 8192, 1024) : mkdesc(a + kk * 32, 16, 1024);
      uint64_t db = mkdesc(b + kk * 2048, 8192, 1024);
      if constexpr (BN == 256) wgmma_n256<TA>(d, da, db, (k | kk) != 0); else wgmma_n192<TA>(d, da, db, (k | kk) != 0);
    }
    asm volatile("wgmma.commit_group.sync.aligned;" ::: "memory");
    asm volatile("wgmma.wait_group.sync.aligned 1;" ::: "memory");
    if (prev >= 0 && elect) { mbar_arrive_remote(emptyb_l + prev * 8); mbar_arrive_remote(emptyb_r + prev * 8); }
    prev = stage;
    if (++stage == NSTAGE) { stage = 0; phase ^= 1; }
  }
  asm volatile("wgmma.wait_group.sync.aligned 0;" ::: "memory");
  if (elect) { mbar_arrive_remote(emptyb_l + prev * 8); mbar_arrive_remote(emptyb_r + prev * 8); }
}
template <int BN, class F>
__device__ __forceinline__ void store_tile(const float (&d)[128], uint32_t stg, bf16* dst, int ld, int lane, F f) {
#pragma unroll
  for (int c = 0; c < BN / 64; c++) {
#pragma unroll
    for (int i = 0; i < 8; i += 2) {
      const int o = c * 32 + i * 4;
      uint32_t r0 = f(d[o], d[o + 1], 0, c * 64 + i * 8), r1 = f(d[o + 2], d[o + 3], 1, c * 64 + i * 8);
      uint32_t r2 = f(d[o + 4], d[o + 5], 0, c * 64 + i * 8 + 8), r3 = f(d[o + 6], d[o + 7], 1, c * 64 + i * 8 + 8);
      int m = lane >> 3, row = (m & 1) * 8 + (lane & 7), ch = (i + (m >> 1)) ^ (row & 7);
      asm volatile("stmatrix.sync.aligned.m8n8.x4.shared.b16 [%0], {%1,%2,%3,%4};" ::"r"(stg + row * 128 + ch * 16), "r"(r0), "r"(r1), "r"(r2), "r"(r3) : "memory");
    }
    __syncwarp();
#pragma unroll
    for (int j = 0; j < 4; j++) {
      int idx = lane + 32 * j, row = idx >> 3, ch = idx & 7;
      uint4 v;
      asm volatile("ld.shared.v4.u32 {%0,%1,%2,%3}, [%4];" : "=r"(v.x), "=r"(v.y), "=r"(v.z), "=r"(v.w) : "r"(stg + row * 128 + ((ch ^ (row & 7)) * 16)));
      *(uint4*)(dst + (size_t)row * ld + c * 64 + ch * 8) = v;
    }
    __syncwarp();
  }
}

__global__ void __launch_bounds__(384, 1) gemm_kernel(const __grid_constant__ GemmParams p) {
  extern __shared__ uint8_t smem_raw[];
  const uint32_t sbase = (smem_u32(smem_raw) + 1023) & ~1023u;
  const uint32_t stg0 = sbase + NSTAGE * STAGE_BYTES, fullb = stg0 + 8 * 2048, emptyb = fullb + 64;
  const uint32_t rank = cluster_rank();
  const int wg = __shfl_sync(~0u, (int)(threadIdx.x >> 7), 0), lane = threadIdx.x & 31;
  const int cl = blockIdx.x >> 1;
  if (threadIdx.x == 0) {
    for (int i = 0; i < NSTAGE; i++) { mbar_init(fullb + i * 8, 1); mbar_init(emptyb + i * 8, 4); }
    asm volatile("fence.mbarrier_init.release.cluster;" ::: "memory");
  }
  cluster_sync();
  const uint16_t* jobs = p.job + cl * p.stride;
  if (wg == 0) {
    asm volatile("setmaxnreg.dec.sync.aligned.u32 40;");
    if (threadIdx.x == 0) {
      int stage = 0; uint32_t phase = 1;
      for (int j = 0; j < p.stride; j++) {
        uint32_t job = jobs[j];
        if (job == 0xFFFF) break;
        int type = job >> 12, m = (job >> 6) & 63, n = job & 63;
        int row0 = m * 256 + rank * 128;
        int bn = type < 3 ? 256 : 192;
        int kit = type < 3 ? 9 : (type == 3 ? 32 : (type == 4 ? 72 : 64));
        const CUtensorMap* ma = &p.mA[type < 3 ? 0 : type - 2];
        const CUtensorMap* mb = &p.mB[type];
        bool ta = (type == 3 || type == 4);
        if (type == 4) {
          uint32_t v;
          do { asm volatile("ld.acquire.gpu.global.u32 %0, [%1];" : "=r"(v) : "l"(&g_cnt[0]) : "memory"); if (v < 108) __nanosleep(100); } while (v < 108);
          asm volatile("fence.proxy.async;" ::: "memory");
        }
        for (int k = 0; k < kit; k++) {
          mbar_wait_cl(emptyb + stage * 8, phase);
          uint32_t fb = fullb + stage * 8, a = sbase + stage * STAGE_BYTES, b = a + 16384;
          mbar_expect(fb, 16384 + bn * 128);
          if (ta) { tma2d(a, ma, row0, k * 64, fb); tma2d(a + 8192, ma, row0 + 64, k * 64, fb); }
          else tma2d(a, ma, k * 64, row0, fb);
          for (int i = 0; i < bn / 64; i++) tma2d_mc(b + i * 8192 + rank * 4096, mb, n * bn + i * 64, k * 64 + rank * 32, fb, (uint16_t)3);
          if (++stage == NSTAGE) { stage = 0; phase ^= 1; }
        }
      }
    }
    __syncwarp();
    if (p.wait_at_end) pdl_wait();
    cluster_sync();
  } else {
    asm volatile("setmaxnreg.inc.sync.aligned.u32 232;");
    const int cw = wg - 1, warp = __shfl_sync(~0u, (int)(threadIdx.x >> 5) & 3, 0);
    const uint32_t eb_l = mapa(emptyb, rank), eb_r = mapa(emptyb, rank ^ 1);
    const uint32_t stg = stg0 + (cw * 4 + warp) * 2048;
    const bool elect = (threadIdx.x & 127) == 0;
    const int g = lane >> 2, t = lane & 3;
    int stage = 0; uint32_t phase = 0;
    float d[128];
    for (int j = 0; j < p.stride; j++) {
      uint32_t job = jobs[j];
      if (job == 0xFFFF) break;
      int type = job >> 12, m = (job >> 6) & 63, n = job & 63;
      int row0 = m * 256 + rank * 128 + cw * 64 + warp * 16;
      if (type < 3) {
        gemm_mainloop<256, 0>(d, 9, sbase, fullb, eb_l, eb_r, cw, stage, phase, elect);
        bf16* dst = (type == 0 ? g_q : (type == 1 ? g_k : g_v)) + (size_t)row0 * HD_ + n * 256;
        store_tile<256>(d, stg, dst, HD_, lane, [](float a, float b, int, int) { return pack_bf16(a, b); });
      } else if (type == 3) {
        gemm_mainloop<192, 1>(d, 32, sbase, fullb, eb_l, eb_r, cw, stage, phase, elect);
        float bb[2] = {__bfloat162float(p.b1[row0 + g]), __bfloat162float(p.b1[row0 + g + 8])};
        store_tile<192>(d, stg, g_ut + (size_t)row0 * D_ + n * 192, D_, lane,
                        [&](float a, float b, int h, int) { return pack_bf16(gelu_tanh(a + bb[h]), gelu_tanh(b + bb[h])); });
        __threadfence();
        asm volatile("fence.proxy.async;" ::: "memory");
        asm volatile("bar.sync %0, 256;" ::"r"(1) : "memory");
        if (threadIdx.x == 128) atomicAdd(&g_cnt[0], 1);
      } else if (type == 4) {
        gemm_mainloop<192, 1>(d, 72, sbase, fullb, eb_l, eb_r, cw, stage, phase, elect);
        float bb[2] = {__bfloat162float(p.b2[row0 + g]), __bfloat162float(p.b2[row0 + g + 8])};
#pragma unroll
        for (int i = 0; i < 24; i++)
#pragma unroll
          for (int h = 0; h < 2; h++) {
            size_t off = (size_t)(row0 + g + h * 8) * D_ + n * 192 + i * 8 + t * 2;
            float2 xv = unpack_bf16(*(const uint32_t*)(p.x + off));
            *(float2*)(g_yb + off) = make_float2(d[i * 4 + h * 2] + bb[h] + xv.x, d[i * 4 + h * 2 + 1] + bb[h] + xv.y);
          }
      } else {
        gemm_mainloop<192, 0>(d, 64, sbase, fullb, eb_l, eb_r, cw, stage, phase, elect);
        const float* yb = g_yb + (size_t)(row0 + g) * D_ + n * 192 + t * 2;
        store_tile<192>(d, stg, p.out + (size_t)row0 * D_ + n * 192, D_, lane,
                        [&](float a, float b, int h, int c) { float2 y = *(const float2*)(yb + h * 8 * D_ + c); return pack_bf16(a + y.x, b + y.y); });
      }
    }
    if (p.wait_at_end) pdl_wait();
    cluster_sync();
  }
}

__global__ void __launch_bounds__(128) attn_kernel() {
  __shared__ __align__(128) uint8_t sm[4][48 * 256];
  const int warp = threadIdx.x >> 5, lane = threadIdx.x & 31, g = lane >> 2, t = lane & 3;
  const int id = blockIdx.x * 4 + warp, seg = id >> 5, h = id & 31;
  const uint32_t sv = smem_u32(sm[warp]);
  const size_t tok0 = (size_t)seg * 32;
  for (int i = lane; i < 40 * 16; i += 32) {
    int r = i >> 4, c = i & 15;
    const bf16* src = (r < 8 ? g_vm + ((size_t)seg * 8 + r) * HD_ : g_v + (tok0 + r - 8) * HD_) + h * 128 + c * 8;
    cp16(sv + r * 256 + ((c ^ (r & 7)) * 16), src);
  }
  for (int i = lane; i < 8 * 16; i += 32) *(uint4*)(sm[warp] + 40 * 256 + i * 16) = make_uint4(0, 0, 0, 0);
  asm volatile("cp.async.commit_group;" ::: "memory");
  float s[2][5][4];
#pragma unroll
  for (int m = 0; m < 2; m++)
#pragma unroll
    for (int n = 0; n < 5; n++) { s[m][n][0] = s[m][n][1] = s[m][n][2] = s[m][n][3] = 0.f; }
#pragma unroll
  for (int j = 0; j < 4; j++) {
    uint4 qa[2][2], kb[5];
#pragma unroll
    for (int m = 0; m < 2; m++)
#pragma unroll
      for (int hh = 0; hh < 2; hh++) qa[m][hh] = *(const uint4*)(g_q + (tok0 + m * 16 + hh * 8 + g) * HD_ + h * 128 + j * 32 + t * 8);
#pragma unroll
    for (int n = 0; n < 5; n++)
      kb[n] = *(const uint4*)((n == 0 ? g_km + ((size_t)seg * 8 + g) * HD_ : g_k + (tok0 + (n - 1) * 8 + g) * HD_) + h * 128 + j * 32 + t * 8);
#pragma unroll
    for (int m = 0; m < 2; m++) {
      uint32_t a0[4] = {qa[m][0].x, qa[m][1].x, qa[m][0].y, qa[m][1].y}, a1[4] = {qa[m][0].z, qa[m][1].z, qa[m][0].w, qa[m][1].w};
#pragma unroll
      for (int n = 0; n < 5; n++) { mma16816(s[m][n], a0, kb[n].x, kb[n].y); mma16816(s[m][n], a1, kb[n].z, kb[n].w); }
    }
  }
  const float sc = 0.08838834764831845f * 1.4426950408889634f;
  uint32_t pa[2][3][4];
#pragma unroll
  for (int m = 0; m < 2; m++) {
    float inv[2];
#pragma unroll
    for (int hh = 0; hh < 2; hh++) {
      int qi = 8 + m * 16 + hh * 8 + g;
      float mx = -INFINITY;
#pragma unroll
      for (int n = 0; n < 5; n++)
#pragma unroll
        for (int e = 0; e < 2; e++) { float& z = s[m][n][hh * 2 + e]; z = (n * 8 + t * 2 + e <= qi) ? z * sc : -INFINITY; mx = fmaxf(mx, z); }
      mx = fmaxf(mx, __shfl_xor_sync(~0u, mx, 1)); mx = fmaxf(mx, __shfl_xor_sync(~0u, mx, 2));
      float sum = 0.f;
#pragma unroll
      for (int n = 0; n < 5; n++)
#pragma unroll
        for (int e = 0; e < 2; e++) { float& z = s[m][n][hh * 2 + e]; z = exp2f(z - mx); sum += z; }
      sum += __shfl_xor_sync(~0u, sum, 1); sum += __shfl_xor_sync(~0u, sum, 2);
      inv[hh] = 1.f / sum;
    }
#pragma unroll
    for (int kk = 0; kk < 3; kk++) {
      pa[m][kk][0] = pack_bf16(s[m][2 * kk][0] * inv[0], s[m][2 * kk][1] * inv[0]);
      pa[m][kk][1] = pack_bf16(s[m][2 * kk][2] * inv[1], s[m][2 * kk][3] * inv[1]);
      if (kk < 2) {
        pa[m][kk][2] = pack_bf16(s[m][2 * kk + 1][0] * inv[0], s[m][2 * kk + 1][1] * inv[0]);
        pa[m][kk][3] = pack_bf16(s[m][2 * kk + 1][2] * inv[1], s[m][2 * kk + 1][3] * inv[1]);
      } else { pa[m][kk][2] = 0; pa[m][kk][3] = 0; }
    }
  }
  asm volatile("cp.async.wait_group 0;" ::: "memory");
  __syncwarp();
  uint32_t ov[2][16][2];
#pragma unroll
  for (int np = 0; np < 8; np++) {
    float o[2][2][4] = {};
#pragma unroll
    for (int kk = 0; kk < 3; kk++) {
      uint32_t b[4];
      int mi = lane >> 3, r = kk * 16 + (mi & 1) * 8 + (lane & 7), c = np * 2 + (mi >> 1);
      ldsm4t(b, sv + r * 256 + ((c ^ (r & 7)) * 16));
#pragma unroll
      for (int m = 0; m < 2; m++) { mma16816(o[m][0], pa[m][kk], b[0], b[1]); mma16816(o[m][1], pa[m][kk], b[2], b[3]); }
    }
#pragma unroll
    for (int m = 0; m < 2; m++)
#pragma unroll
      for (int q = 0; q < 2; q++) { ov[m][np * 2 + q][0] = pack_bf16(o[m][q][0], o[m][q][1]); ov[m][np * 2 + q][1] = pack_bf16(o[m][q][2], o[m][q][3]); }
  }
  __syncwarp();
#pragma unroll
  for (int m = 0; m < 2; m++)
#pragma unroll
    for (int n = 0; n < 16; n++)
#pragma unroll
      for (int hh = 0; hh < 2; hh++) {
        int r = m * 16 + hh * 8 + g;
        *(uint32_t*)(sm[warp] + r * 256 + ((n ^ (r & 7)) * 16) + t * 4) = ov[m][n][hh];
      }
  __syncwarp();
#pragma unroll
  for (int i = 0; i < 16; i++) {
    int idx = lane + 32 * i, r = idx >> 4, c = idx & 15;
    *(uint4*)(g_o + (tok0 + r) * HD_ + h * 128 + c * 8) = *(const uint4*)(sm[warp] + r * 256 + ((c ^ (r & 7)) * 16));
  }
}
constexpr int CH_WV = 0;
constexpr int CH_MEM = CH_WV + 73728;
constexpr int CH_KB = CH_MEM + 9216;
constexpr int CH_VB = CH_KB + 12288;
constexpr int CH_WO = CH_VB + 12288;
constexpr int CH_Q = CH_WO + 81920;
constexpr int CH_R1 = CH_Q + 1024;
constexpr int CH_SC = CH_R1 + 4096;
constexpr int CH_OF = CH_SC + 3584;
constexpr int CH_R2 = CH_OF + 8192;
constexpr int CH_BAR = CH_R2 + 12288;
constexpr int CHAIN_SMEM = CH_BAR + 64 + 1024;
#define NREGT 1
__device__ __forceinline__ void st_async1(uint32_t a, uint32_t v, uint32_t bar) { asm volatile("st.async.weak.shared::cluster.mbarrier::complete_tx::bytes.b32 [%0], %1, [%2];" ::"r"(a), "r"(v), "r"(bar) : "memory"); }
__device__ __forceinline__ void st_async2(uint32_t a, uint32_t v0, uint32_t v1, uint32_t bar) { asm volatile("st.async.weak.shared::cluster.mbarrier::complete_tx::bytes.v2.b32 [%0], {%1, %2}, [%3];" ::"r"(a), "r"(v0), "r"(v1), "r"(bar) : "memory"); }
__device__ __forceinline__ uint4 lds128(uint32_t a) { uint4 v; asm volatile("ld.shared.v4.u32 {%0,%1,%2,%3}, [%4];" : "=r"(v.x), "=r"(v.y), "=r"(v.z), "=r"(v.w) : "r"(a) : "memory"); return v; }
__device__ __forceinline__ void sts128f(uint32_t a, const float (&c)[4]) { asm volatile("st.shared.v4.f32 [%0], {%1,%2,%3,%4};" ::"r"(a), "f"(c[0]), "f"(c[1]), "f"(c[2]), "f"(c[3]) : "memory"); }
__device__ __forceinline__ void sts32(uint32_t a, uint32_t v) { asm volatile("st.shared.u32 [%0], %1;" ::"r"(a), "r"(v) : "memory"); }
__device__ __forceinline__ void mbar_wait_b(uint32_t b, uint32_t parity) {
  uint32_t ok; int n = 0;
  do { asm volatile("{\n.reg .pred p;\nmbarrier.try_wait.parity.acquire.cluster.shared::cta.b64 p, [%1], %2;\nselp.u32 %0, 1, 0, p;\n}" : "=r"(ok) : "r"(b), "r"(parity) : "memory"); } while (!ok && ++n < (1 << 20));
}
#define BAR_ALL() asm volatile("bar.sync 0, 256;" ::: "memory")

__global__ void __launch_bounds__(256, 1) chain_kernel(const bf16* __restrict__ mem0, const bf16* __restrict__ Wq, const bf16* __restrict__ Wk,
                                                       const bf16* __restrict__ Wv, const bf16* __restrict__ Wo) {
  extern __shared__ uint8_t smem_raw[];
  const uint32_t sb = (smem_u32(smem_raw) + 1023) & ~1023u;
  const int tid = threadIdx.x, warp = __shfl_sync(~0u, tid >> 5, 0), wgi = __shfl_sync(~0u, tid >> 7, 0), lane = tid & 31, g = lane >> 2, t = lane & 3;
  const uint32_t r = cluster_rank();
  const int c = blockIdx.x >> 3, h = 4 * c + (r >> 1), j0 = h * 128 + (r & 1) * 64;
  const int ntile = r < 4 ? 5 : 4, col0 = r < 4 ? 80 * r : 320 + 64 * (r - 4);
  const uint32_t bm = sb + CH_BAR, bs = bm + 8, bo = bm + 16;
  pdl_launch();
  if (tid == 0) { mbar_init(bm, 1); mbar_init(bs, 1); mbar_init(bo, 1); asm volatile("fence.mbarrier_init.release.cluster;" ::: "memory"); }
  const int mi = lane >> 3, l7 = lane & 7;
  for (int i = tid; i < 576 * 8; i += 256) {
    int row = i >> 3, ch = i & 7;
    cp16(sb + CH_WV + row * 128 + ((ch ^ (row & 7)) * 16), Wq + (size_t)row * HD_ + j0 + ch * 8);
    cp16(sb + CH_WO + row * 128 + ((ch ^ (row & 7)) * 16), Wk + (size_t)row * HD_ + j0 + ch * 8);
  }
  asm volatile("cp.async.commit_group;\ncp.async.wait_group 0;" ::: "memory");
  BAR_ALL();
  uint32_t wq[18][4], wk[18][4];
  const int kg1 = warp >> 2, mg1 = warp & 3;
#pragma unroll
  for (int i = 0; i < 18; i++) {
    int row = (kg1 * 18 + i) * 16 + (mi >> 1) * 8 + l7, ch = (mg1 * 2 + (mi & 1)) ^ (row & 7);
    ldsm4t(wq[i], sb + CH_WV + row * 128 + ch * 16);
    ldsm4t(wk[i], sb + CH_WO + row * 128 + ch * 16);
  }
  BAR_ALL();
  for (int i = tid; i < 512 * ntile * 2; i += 256) {
    int row = i / (ntile * 2), ch = i - row * (ntile * 2);
    cp16(sb + CH_WV + row * 176 + ch * 16, Wo + (size_t)(c * 512 + row) * D_ + col0 + ch * 8);
  }
  asm volatile("cp.async.commit_group;\ncp.async.wait_group 0;" ::: "memory");
  BAR_ALL();
  const int kg2 = warp >> 1, mg2 = warp & 1;
  uint32_t wo[NREGT > 0 ? NREGT : 1][8][4];
  for (int u = warp; u < ntile * 32; u += 8) {
    int tile = u >> 5, ks = u & 31;
    uint32_t a[4];
    ldsm4t(a, sb + CH_WV + (ks * 16 + (mi >> 1) * 8 + l7) * 176 + (tile * 2 + (mi & 1)) * 16);
    asm volatile("st.shared.v4.u32 [%0], {%1,%2,%3,%4};" ::"r"(sb + CH_WO + u * 512 + lane * 16), "r"(a[0]), "r"(a[1]), "r"(a[2]), "r"(a[3]) : "memory");
  }
  BAR_ALL();
#pragma unroll
  for (int tt = 0; tt < NREGT; tt++)
#pragma unroll
    for (int i = 0; i < 8; i++) { uint4 v = lds128(sb + CH_WO + ((mg2 * 2 + tt) * 32 + kg2 * 8 + i) * 512 + lane * 16); wo[tt][i][0] = v.x; wo[tt][i][1] = v.y; wo[tt][i][2] = v.z; wo[tt][i][3] = v.w; }
  for (int i = tid; i < 576 * 8; i += 256) {
    int row = i >> 3, ch = i & 7;
    cp16(sb + CH_WV + row * 128 + ((ch ^ (row & 7)) * 16), Wv + (size_t)row * HD_ + j0 + ch * 8);
  }
  for (int i = tid; i < 8 * 72; i += 256) {
    int row = i / 72, ch = i - row * 72;
    cp16(sb + CH_MEM + ch * 128 + row * 16, mem0 + row * D_ + ch * 8);
  }
  for (int i = tid; i < 4 * 64; i += 256) {
    int b = i >> 6, o = i & 63;
    asm volatile("st.shared.v4.u32 [%0], {%1,%1,%1,%1};" ::"r"(sb + CH_KB + b * 6144 + 40 * 128 + o * 16), "r"(0) : "memory");
  }
  pdl_wait();
  auto prefetch_kv = [&](int s) {
#pragma unroll
    for (int i = 0; i < 2; i++) {
      int u = tid + i * 256, which = u >> 8, row = (u & 255) >> 3, ch = u & 7;
      const bf16* src = (which ? g_v : g_k) + (size_t)(s * 32 + row) * HD_ + j0 + ch * 8;
      cp16(sb + (which ? CH_VB : CH_KB) + (s & 1) * 6144 + (row + 8) * 128 + ((ch ^ (row & 7)) * 16), src);
    }
    asm volatile("cp.async.commit_group;" ::: "memory");
  };
  prefetch_kv(0);
  asm volatile("cp.async.wait_group 0;" ::: "memory");
  asm volatile("fence.proxy.async.shared::cta;" ::: "memory");
  BAR_ALL();
  cluster_sync();
  const uint32_t peer = r ^ 1;
  const uint32_t sc_l = mapa(sb + CH_SC + (r & 1) * 1792, r), sc_r = mapa(sb + CH_SC + (r & 1) * 1792, peer), bs_l = mapa(bs, r), bs_r = mapa(bs, peer);
  const uint32_t cl0 = mapa(sb, 0), clstep = mapa(sb, 1) - cl0;

  for (int s = 0; s < NSEG; s++) {
    const uint32_t par = s & 1, kb = sb + CH_KB + par * 6144, vb = sb + CH_VB + par * 6144;
    if (s > 0) mbar_wait_b(bm, par ^ 1);
    if (tid == 0 && s < NSEG - 1) { mbar_expect(bs, 3072); mbar_expect(bo, 8192); mbar_expect(bm, 9216); }
    auto phase1 = [&]() {
    if (s + 1 < NSEG) prefetch_kv(s + 1);
    float qa[2][4] = {}, ka[2][4] = {};
#pragma unroll
    for (int i = 0; i < 18; i += 2) {
      uint32_t b[4];
      ldsm4(b, sb + CH_MEM + (kg1 * 18 + i) * 256 + mi * 128 + l7 * 16);
      mma16816(qa[0], wq[i], b[0], b[1]); mma16816(ka[0], wk[i], b[0], b[1]);
      mma16816(qa[1], wq[i + 1], b[2], b[3]); mma16816(ka[1], wk[i + 1], b[2], b[3]);
    }
#pragma unroll
    for (int e = 0; e < 4; e++) { qa[0][e] += qa[1][e]; ka[0][e] += ka[1][e]; }
    sts128f(sb + CH_R1 + (kg1 * 4 + mg1) * 512 + lane * 16, kg1 ? qa[0] : ka[0]);
    asm volatile("cp.async.wait_group 1;" ::: "memory");
    BAR_ALL();
    {
      uint4 o = lds128(sb + CH_R1 + ((kg1 ^ 1) * 4 + mg1) * 512 + lane * 16);
      float (&m)[4] = kg1 ? ka[0] : qa[0];
      uint32_t b0 = movm(pack_bf16(m[0] + __uint_as_float(o.x), m[1] + __uint_as_float(o.y)));
      uint32_t b1 = movm(pack_bf16(m[2] + __uint_as_float(o.z), m[3] + __uint_as_float(o.w)));
      uint32_t dst = (kg1 ? kb : sb + CH_Q) + g * 128 + t * 4;
      sts32(dst + (((mg1 * 2) ^ g) * 16), b0); sts32(dst + (((mg1 * 2 + 1) ^ g) * 16), b1);
      if (kg1) { uint32_t* gp = (uint32_t*)(g_km + ((size_t)s * 8 + g) * HD_ + j0 + mg1 * 16 + t * 2); gp[0] = b0; gp[4] = b1; }
    }
    BAR_ALL();
    };
    if (wgi == 0) {
      float va[4] = {0.f, 0.f, 0.f, 0.f};
      asm volatile("fence.proxy.async.shared::cta;" ::: "memory");
      asm volatile("wgmma.fence.sync.aligned;" ::: "memory");
#pragma unroll
      for (int ks = 0; ks < 36; ks++) {
        uint64_t da = mkdesc(sb + CH_WV + ks * 2048, 8192, 1024);
        uint64_t db = (uint64_t)(((sb + CH_MEM + ks * 256) & 0x3FFFF) >> 4) | ((uint64_t)(128 >> 4) << 16) | ((uint64_t)(256 >> 4) << 32);
        asm volatile("{\n.reg .pred p;\nsetp.ne.b32 p, %6, 0;\nwgmma.mma_async.sync.aligned.m64n8k16.f32.bf16.bf16 {%0,%1,%2,%3}, %4, %5, p, 1, 1, 1, 0;\n}"
                     : "+f"(va[0]), "+f"(va[1]), "+f"(va[2]), "+f"(va[3]) : "l"(da), "l"(db), "r"(ks));
      }
      asm volatile("wgmma.commit_group.sync.aligned;" ::: "memory");
      phase1();
      asm volatile("wgmma.wait_group.sync.aligned 0;" : "+f"(va[0]), "+f"(va[1]), "+f"(va[2]), "+f"(va[3]) :: "memory");
      uint32_t b0 = movm(pack_bf16(va[0], va[1])), b1 = movm(pack_bf16(va[2], va[3]));
      sts32(vb + g * 128 + t * 4 + (((warp * 2) ^ g) * 16), b0); sts32(vb + g * 128 + t * 4 + (((warp * 2 + 1) ^ g) * 16), b1);
      uint32_t* gp = (uint32_t*)(g_vm + ((size_t)s * 8 + g) * HD_ + j0 + warp * 16 + t * 2); gp[0] = b0; gp[4] = b1;
      if (s < NSEG - 1) {
        __syncwarp();
        uint32_t vt[3][4];
#pragma unroll
        for (int kk = 0; kk < 3; kk++) { int row = kk * 16 + (mi >> 1) * 8 + l7; ldsm4t(vt[kk], vb + row * 128 + (((warp * 2 + (mi & 1)) ^ l7) * 16)); }
        mbar_wait_b(bs, par);
        float z[12]; float mx = -INFINITY;
        const float scl = 0.08838834764831845f * 1.4426950408889634f;
#pragma unroll
        for (int i = 0; i < 5; i++) {
          float2 u0, u1; uint32_t a = sb + CH_SC + (g * 56 + i * 8 + 2 * t) * 4;
          asm volatile("ld.shared.v2.f32 {%0,%1}, [%2];" : "=f"(u0.x), "=f"(u0.y) : "r"(a) : "memory");
          asm volatile("ld.shared.v2.f32 {%0,%1}, [%2];" : "=f"(u1.x), "=f"(u1.y) : "r"(a + 1792) : "memory");
          z[2 * i] = (u0.x + u1.x) * scl; z[2 * i + 1] = (u0.y + u1.y) * scl; mx = fmaxf(mx, fmaxf(z[2 * i], z[2 * i + 1]));
        }
        mx = fmaxf(mx, __shfl_xor_sync(~0u, mx, 1)); mx = fmaxf(mx, __shfl_xor_sync(~0u, mx, 2));
        float sum = 0.f;
#pragma unroll
        for (int i = 0; i < 10; i++) { z[i] = exp2f(z[i] - mx); sum += z[i]; }
        sum += __shfl_xor_sync(~0u, sum, 1); sum += __shfl_xor_sync(~0u, sum, 2);
        float inv = 1.f / sum;
        float oa[4] = {};
        mma16816(oa, vt[0], pack_bf16(z[0] * inv, z[1] * inv), pack_bf16(z[2] * inv, z[3] * inv));
        mma16816(oa, vt[1], pack_bf16(z[4] * inv, z[5] * inv), pack_bf16(z[6] * inv, z[7] * inv));
        mma16816(oa, vt[2], pack_bf16(z[8] * inv, z[9] * inv), 0u);
        uint32_t o0 = movm(pack_bf16(oa[0], oa[1])), o1 = movm(pack_bf16(oa[2], oa[3]));
        const int ks = r * 4 + warp;
        const uint32_t off = CH_OF + (ks >> 1) * 512 + lane * 16 + (ks & 1) * 8;
#pragma unroll
        for (int d = 0; d < 8; d++) st_async2(cl0 + d * clstep + off, o0, o1, cl0 + d * clstep + CH_BAR + 16);
      }
    } else {
      phase1();
      if (warp < 7 && s < NSEG - 1) {
        const int mt = warp - 4;
        float sa[2][4] = {};
#pragma unroll
        for (int kp = 0; kp < 2; kp++) {
          uint32_t b[4], a0[4], a1[4];
          ldsm4(b, sb + CH_Q + l7 * 128 + (((kp * 4 + mi) ^ l7) * 16));
          int row = mt * 16 + (mi & 1) * 8 + l7;
          ldsm4(a0, kb + row * 128 + (((kp * 4 + (mi >> 1)) ^ l7) * 16));
          ldsm4(a1, kb + row * 128 + (((kp * 4 + 2 + (mi >> 1)) ^ l7) * 16));
          mma16816(sa[0], a0, b[0], b[1]); mma16816(sa[1], a1, b[2], b[3]);
        }
#pragma unroll
        for (int e = 0; e < 4; e++) {
          uint32_t off = ((2 * t + (e & 1)) * 56 + mt * 16 + (e >> 1) * 8 + g) * 4, v = __float_as_uint(sa[0][e] + sa[1][e]);
          st_async1(sc_r + off, v, bs_r); st_async1(sc_l + off, v, bs_l);
        }
      }
    }
    if (s == NSEG - 1) break;
    mbar_wait_b(bo, par);
    {
      float acc[3][4] = {};
#pragma unroll
      for (int i = 0; i < 8; i += 2) {
        uint4 b = lds128(sb + CH_OF + (kg2 * 4 + (i >> 1)) * 512 + lane * 16);
#pragma unroll
        for (int tt = 0; tt < 2; tt++)
#pragma unroll
          for (int e = 0; e < 2; e++) {
            if (tt < NREGT) mma16816(acc[tt], wo[tt < NREGT ? tt : 0][i + e], e ? b.z : b.x, e ? b.w : b.y);
            else { uint4 v = lds128(sb + CH_WO + ((mg2 * 2 + tt) * 32 + kg2 * 8 + i + e) * 512 + lane * 16); uint32_t a[4] = {v.x, v.y, v.z, v.w}; mma16816(acc[tt], a, e ? b.z : b.x, e ? b.w : b.y); }
          }
        if (ntile == 5 && (i >> 2) == mg2) {
#pragma unroll
          for (int e = 0; e < 2; e++) { uint4 v = lds128(sb + CH_WO + (4 * 32 + kg2 * 8 + i + e) * 512 + lane * 16); uint32_t a[4] = {v.x, v.y, v.z, v.w}; mma16816(acc[2], a, e ? b.z : b.x, e ? b.w : b.y); }
        }
      }
      sts128f(sb + CH_R2 + (kg2 * 4 + mg2 * 2) * 512 + lane * 16, acc[0]);
      sts128f(sb + CH_R2 + (kg2 * 4 + mg2 * 2 + 1) * 512 + lane * 16, acc[1]);
      sts128f(sb + CH_R2 + (16 + warp) * 512 + lane * 16, acc[2]);
    }
    BAR_ALL();
    if (warp < ntile) {
      const uint32_t tag = ((s >> 1) + 1) & 1;
      float a[4] = {};
      const int np = warp == 4 ? 8 : 4;
      for (int i = 0; i < np; i++) {
        uint4 v = lds128(sb + CH_R2 + (warp == 4 ? 16 + i : i * 4 + warp) * 512 + lane * 16);
        a[0] += __uint_as_float(v.x); a[1] += __uint_as_float(v.y); a[2] += __uint_as_float(v.z); a[3] += __uint_as_float(v.w);
      }
      float* pb = g_part + (size_t)(par * 64 + r) * 640 + warp * 128 + lane * 4;
      asm volatile("st.relaxed.gpu.global.v4.b32 [%0], {%1,%2,%3,%4};" ::"l"(pb + c * 8 * 640), "r"((__float_as_uint(a[0]) & ~1u) | tag), "r"((__float_as_uint(a[1]) & ~1u) | tag),
                   "r"((__float_as_uint(a[2]) & ~1u) | tag), "r"((__float_as_uint(a[3]) & ~1u) | tag) : "memory");
      uint4 v[8]; int n = 0; bool ok;
      do {
        ok = true;
#pragma unroll
        for (int i = 0; i < 8; i++) asm volatile("ld.relaxed.gpu.global.v4.b32 {%0,%1,%2,%3}, [%4];" : "=r"(v[i].x), "=r"(v[i].y), "=r"(v[i].z), "=r"(v[i].w) : "l"(pb + i * 8 * 640) : "memory");
#pragma unroll
        for (int i = 0; i < 8; i++) ok = ok && (((v[i].x & v[i].y & v[i].z & v[i].w & 1u) == tag) && (((v[i].x | v[i].y | v[i].z | v[i].w) & 1u) == tag));
      } while (!ok && ++n < (1 << 18));
      float m[4] = {};
#pragma unroll
      for (int i = 0; i < 8; i++) { m[0] += __uint_as_float(v[i].x); m[1] += __uint_as_float(v[i].y); m[2] += __uint_as_float(v[i].z); m[3] += __uint_as_float(v[i].w); }
      __syncwarp();
      uint32_t b0 = movm(pack_bf16(m[0], m[1])), b1 = movm(pack_bf16(m[2], m[3]));
      const uint32_t off = CH_MEM + (col0 / 16 + warp) * 256 + g * 16 + t * 4;
#pragma unroll
      for (int d = 0; d < 8; d++) { st_async1(cl0 + d * clstep + off, b0, cl0 + d * clstep + CH_BAR); st_async1(cl0 + d * clstep + off + 128, b1, cl0 + d * clstep + CH_BAR); }
    }
  }
  cluster_sync();
}
typedef CUresult (*EncodeFn)(CUtensorMap*, CUtensorMapDataType, cuuint32_t, void*, const cuuint64_t*, const cuuint64_t*, const cuuint32_t*, const cuuint32_t*,
                             CUtensorMapInterleave, CUtensorMapSwizzle, CUtensorMapL2promotion, CUtensorMapFloatOOBfill);
static EncodeFn g_enc;
static void mkmap(CUtensorMap* m, const void* ptr, int rows, int cols, int boxc, int boxr) {
  cuuint64_t dims[2] = {(cuuint64_t)cols, (cuuint64_t)rows}, strides[1] = {(cuuint64_t)cols * 2};
  cuuint32_t box[2] = {(cuuint32_t)boxc, (cuuint32_t)boxr}, es[2] = {1, 1};
  g_enc(m, CU_TENSOR_MAP_DATA_TYPE_BFLOAT16, 2, (void*)ptr, dims, strides, box, es, CU_TENSOR_MAP_INTERLEAVE_NONE, CU_TENSOR_MAP_SWIZZLE_128B,
        CU_TENSOR_MAP_L2_PROMOTION_L2_256B, CU_TENSOR_MAP_FLOAT_OOB_FILL_NONE);
}
static inline uint16_t mkjob(int type, int m, int n) { return (uint16_t)(type << 12 | m << 6 | n); }
static void schedule(GemmParams& p, const uint16_t* jobs, int nj, int ncl) {
  static const double cost[6] = {11.0, 11.0, 11.0, 26.5, 57.5, 51.5};
  double t[66] = {}; int cnt[66] = {};
  p.stride = 960 / ncl;
  for (int i = 0; i < 960; i++) p.job[i] = 0xFFFF;
  double g2_end = 0;
  for (int i = 0; i < nj; i++) {
    int b = 0;
    for (int c = 1; c < ncl; c++) if (t[c] < t[b] || (t[c] == t[b] && cnt[c] < cnt[b])) b = c;
    int ty = jobs[i] >> 12;
    if (ty == 4 && t[b] < g2_end) t[b] = g2_end;
    t[b] += cost[ty];
    if (ty == 3 && t[b] > g2_end) g2_end = t[b];
    p.job[b * p.stride + cnt[b]++] = jobs[i];
  }
}
template <class... A>
static void launch(void (*k)(A...), int grid, int block, int smem, int cluster, bool pdl, A... a) {
  cudaLaunchConfig_t c = {};
  c.gridDim = grid; c.blockDim = block; c.dynamicSmemBytes = smem; c.stream = cudaStreamPerThread;
  cudaLaunchAttribute at[2]; int n = 0;
  if (cluster > 1) { at[n].id = cudaLaunchAttributeClusterDimension; at[n].val.clusterDim.x = cluster; at[n].val.clusterDim.y = 1; at[n].val.clusterDim.z = 1; n++; }
  if (pdl) { at[n].id = cudaLaunchAttributeProgrammaticStreamSerialization; at[n].val.programmaticStreamSerializationAllowed = 1; n++; }
  c.attrs = at; c.numAttrs = n;
  cudaLaunchKernelEx(&c, k, a...);
}

extern "C" void kernel_launch(void* const* d_in, const int* in_sizes, int n_in, void* d_out, int out_size) {
  const bf16 *x = (const bf16*)d_in[0], *mem0 = (const bf16*)d_in[1], *Wq = (const bf16*)d_in[2], *Wk = (const bf16*)d_in[3], *Wv = (const bf16*)d_in[4],
             *Wo = (const bf16*)d_in[5], *w1 = (const bf16*)d_in[8], *b1 = (const bf16*)d_in[9], *w2 = (const bf16*)d_in[10], *b2 = (const bf16*)d_in[11];
  static bool init = false;
  static GemmParams pre, side, post;
  if (!init) {
    init = true;
    cudaDriverEntryPointQueryResult qr;
    cudaGetDriverEntryPoint("cuTensorMapEncodeTiled", (void**)&g_enc, cudaEnableDefault, &qr);
    void *xn, *h2, *o, *ut;
    cudaGetSymbolAddress(&xn, g_xn); cudaGetSymbolAddress(&h2, g_h2); cudaGetSymbolAddress(&o, g_o); cudaGetSymbolAddress(&ut, g_ut);
    GemmParams b = {};
    mkmap(&b.mA[0], xn, S_, D_, 64, 128); mkmap(&b.mA[1], w1, S_, F_, 64, 64); mkmap(&b.mA[2], w2, F_, S_, 64, 64); mkmap(&b.mA[3], o, S_, HD_, 64, 128);
    mkmap(&b.mB[0], Wq, D_, HD_, 64, 32); mkmap(&b.mB[1], Wk, D_, HD_, 64, 32); mkmap(&b.mB[2], Wv, D_, HD_, 64, 32);
    mkmap(&b.mB[3], h2, S_, D_, 64, 32); mkmap(&b.mB[4], ut, F_, D_, 64, 32); mkmap(&b.mB[5], Wo, HD_, D_, 64, 32);
    b.x = x; b.b1 = b1; b.b2 = b2; b.out = (bf16*)d_out;
    pre = b; side = b; post = b;
    static uint16_t jl[1024]; int n = 0;
    for (int m = 0; m < 8; m++) for (int j = 0; j < 16; j++) { jl[n++] = mkjob(1, m, j); jl[n++] = mkjob(2, m, j); }
    schedule(pre, jl, n, 66);
    n = 0;
    for (int m = 0; m < 18; m++) for (int j = 0; j < 3; j++) jl[n++] = mkjob(3, m, j);
    int qn = 0;
    for (; qn < 34; qn++) jl[n++] = mkjob(0, qn >> 4, qn & 15);
    for (int m = 0; m < 8; m++) for (int j = 0; j < 3; j++) jl[n++] = mkjob(4, m, j);
    for (; qn < 128; qn++) jl[n++] = mkjob(0, qn >> 4, qn & 15);
    schedule(side, jl, n, 34);
    side.wait_at_end = 1;
    n = 0;
    for (int m = 0; m < 8; m++) for (int j = 0; j < 3; j++) jl[n++] = mkjob(5, m, j);
    schedule(post, jl, n, 24);
    cudaFuncSetAttribute(gemm_kernel, cudaFuncAttributeMaxDynamicSharedMemorySize, GEMM_SMEM);
    cudaFuncSetAttribute(chain_kernel, cudaFuncAttributeMaxDynamicSharedMemorySize, CHAIN_SMEM);
  }
  launch(ln_kernel, 256, 256, 0, 1, false, x);
  launch(gemm_kernel, 132, 384, GEMM_SMEM, 2, false, pre);
  launch(chain_kernel, 64, 256, CHAIN_SMEM, 8, false, mem0, Wq, Wk, Wv, Wo);
  launch(gemm_kernel, 68, 384, GEMM_SMEM, 2, true, side);
  launch(attn_kernel, 512, 128, 0, 1, false);
  launch(gemm_kernel, 48, 384, GEMM_SMEM, 2, false, post);
}
```

```cpp
#include <cuda_runtime.h>
#include <cuda_bf16.h>
#include <cuda.h>
#include <stdint.h>

typedef __nv_bfloat16 bf16;
constexpr int S_ = 2048, D_ = 576, HD_ = 4096, F_ = 4608, NSEG = 64;

__device__ bf16 g_xn[S_ * D_];
__device__ bf16 g_h2[S_ * D_];
__device__ bf16 g_q[S_ * HD_];
__device__ bf16 g_k[S_ * HD_];
__device__ bf16 g_v[S_ * HD_];
__device__ bf16 g_o[S_ * HD_];
__device__ bf16 g_km[NSEG * 8 * HD_];
__device__ bf16 g_vm[NSEG * 8 * HD_];
__device__ bf16 g_ut[F_ * D_];
__device__ float g_yb[S_ * D_];
__device__ float g_part[2 * 8 * 8 * 5 * 32 * 4];
__device__ unsigned int g_cnt[64];

#define PT(i)
#define PC(i)
__device__ __forceinline__ uint32_t smem_u32(const void* p) { return (uint32_t)__cvta_generic_to_shared(p); }
__device__ __forceinline__ void mbar_init(uint32_t b, uint32_t c) { asm volatile("mbarrier.init.shared::cta.b64 [%0], %1;" ::"r"(b), "r"(c)); }
__device__ __forceinline__ void mbar_expect(uint32_t b, uint32_t bytes) { asm volatile("mbarrier.arrive.expect_tx.shared::cta.b64 _, [%0], %1;" ::"r"(b), "r"(bytes) : "memory"); }
__device__ __forceinline__ void mbar_wait(uint32_t b, uint32_t parity) {
  uint32_t ok;
  do { asm volatile("{\n.reg .pred p;\nmbarrier.try_wait.parity.shared::cta.b64 p, [%1], %2;\nselp.u32 %0, 1, 0, p;\n}" : "=r"(ok) : "r"(b), "r"(parity) : "memory"); } while (!ok);
}
__device__ __forceinline__ void mbar_wait_cl(uint32_t b, uint32_t parity) {
  uint32_t ok;
  do { asm volatile("{\n.reg .pred p;\nmbarrier.try_wait.parity.shared::cta.b64 p, [%1], %2;\nselp.u32 %0, 1, 0, p;\n}" : "=r"(ok) : "r"(b), "r"(parity) : "memory"); } while (!ok);
}
__device__ __forceinline__ uint32_t mapa(uint32_t a, uint32_t r) { uint32_t o; asm("mapa.shared::cluster.u32 %0, %1, %2;" : "=r"(o) : "r"(a), "r"(r)); return o; }
__device__ __forceinline__ void mbar_arrive_remote(uint32_t remote_b) { asm volatile("mbarrier.arrive.shared::cluster.b64 _, [%0];" ::"r"(remote_b) : "memory"); }
__device__ __forceinline__ uint32_t cluster_rank() { uint32_t r; asm("mov.u32 %0, %%cluster_ctarank;" : "=r"(r)); return r; }
__device__ __forceinline__ void cluster_sync() { asm volatile("barrier.cluster.arrive.release.aligned;\nbarrier.cluster.wait.acquire.aligned;" ::: "memory"); }
__device__ __forceinline__ void tma2d(uint32_t dst, const CUtensorMap* m, int c0, int c1, uint32_t bar) {
  asm volatile("cp.async.bulk.tensor.2d.shared::cluster.global.mbarrier::complete_tx::bytes [%0], [%1, {%3, %4}], [%2];"
               ::"r"(dst), "l"(m), "r"(bar), "r"(c0), "r"(c1) : "memory");
}
__device__ __forceinline__ void tma2d_mc(uint32_t dst, const CUtensorMap* m, int c0, int c1, uint32_t bar, uint16_t mask) {
  asm volatile("cp.async.bulk.tensor.2d.shared::cluster.global.mbarrier::complete_tx::bytes.multicast::cluster [%0], [%1, {%3, %4}], [%2], %5;"
               ::"r"(dst), "l"(m), "r"(bar), "r"(c0), "r"(c1), "h"(mask) : "memory");
}
__device__ __forceinline__ uint32_t pack_bf16(float a, float b) { __nv_bfloat162 t = __floats2bfloat162_rn(a, b); return *(uint32_t*)&t; }
__device__ __forceinline__ float2 unpack_bf16(uint32_t u) { return __bfloat1622float2(*(__nv_bfloat162*)&u); }
__device__ __forceinline__ void mma16816(float (&c)[4], const uint32_t (&a)[4], uint32_t b0, uint32_t b1) {
  asm volatile("mma.sync.aligned.m16n8k16.row.col.f32.bf16.bf16.f32 {%0,%1,%2,%3},{%4,%5,%6,%7},{%8,%9},{%0,%1,%2,%3};"
               : "+f"(c[0]), "+f"(c[1]), "+f"(c[2]), "+f"(c[3]) : "r"(a[0]), "r"(a[1]), "r"(a[2]), "r"(a[3]), "r"(b0), "r"(b1));
}
__device__ __forceinline__ void ldsm4(uint32_t (&r)[4], uint32_t a) { asm volatile("ldmatrix.sync.aligned.m8n8.x4.shared.b16 {%0,%1,%2,%3},[%4];" : "=r"(r[0]), "=r"(r[1]), "=r"(r[2]), "=r"(r[3]) : "r"(a) : "memory"); }
__device__ __forceinline__ void ldsm4t(uint32_t (&r)[4], uint32_t a) { asm volatile("ldmatrix.sync.aligned.m8n8.x4.trans.shared.b16 {%0,%1,%2,%3},[%4];" : "=r"(r[0]), "=r"(r[1]), "=r"(r[2]), "=r"(r[3]) : "r"(a) : "memory"); }
__device__ __forceinline__ uint32_t movm(uint32_t a) { uint32_t o; asm volatile("movmatrix.sync.aligned.m8n8.trans.b16 %0, %1;" : "=r"(o) : "r"(a)); return o; }
__device__ __forceinline__ void cp16(uint32_t dst, const void* src) { asm volatile("cp.async.cg.shared.global [%0], [%1], 16;" ::"r"(dst), "l"(src) : "memory"); }
__device__ __forceinline__ void pdl_wait() { asm volatile("griddepcontrol.wait;" ::: "memory"); }
__device__ __forceinline__ void pdl_launch() { asm volatile("griddepcontrol.launch_dependents;" ::: "memory"); }

__global__ void __launch_bounds__(256) ln_kernel(const bf16* __restrict__ x) {
  int row = blockIdx.x * 8 + (threadIdx.x >> 5), lane = threadIdx.x & 31;
  if (threadIdx.x == 0 && blockIdx.x == 0) { g_cnt[0] = 0; PT(0); }
  for (int i = blockIdx.x * 256 + threadIdx.x; i < 2 * 64 * 640; i += 256 * 256) g_part[i] = 0.f;
  const uint32_t* xr = (const uint32_t*)(x + (size_t)row * D_);
  float v[18]; float s = 0.f;
#pragma unroll
  for (int i = 0; i < 9; i++) { float2 f = unpack_bf16(xr[lane + 32 * i]); v[2 * i] = f.x; v[2 * i + 1] = f.y; s += f.x + f.y; }
#pragma unroll
  for (int pass = 0; pass < 2; pass++) {
#pragma unroll
    for (int o = 16; o; o >>= 1) s += __shfl_xor_sync(~0u, s, o);
    float m = s * (1.f / D_), q = 0.f;
#pragma unroll
    for (int i = 0; i < 18; i++) { v[i] -= m; q += v[i] * v[i]; }
#pragma unroll
    for (int o = 16; o; o >>= 1) q += __shfl_xor_sync(~0u, q, o);
    float r = 1.f / sqrtf(q * (1.f / D_) + 1e-5f);
    uint32_t* dst = (uint32_t*)((pass == 0 ? g_xn : g_h2) + (size_t)row * D_);
    s = 0.f;
#pragma unroll
    for (int i = 0; i < 9; i++) {
      uint32_t p = pack_bf16(v[2 * i] * r, v[2 * i + 1] * r);
      dst[lane + 32 * i] = p;
      float2 f = unpack_bf16(p); v[2 * i] = f.x; v[2 * i + 1] = f.y; s += f.x + f.y;
    }
  }
}

template<int TA> __device__ __forceinline__ void wgmma_n256(float (&d)[128], uint64_t da, uint64_t db, int sc) {
  asm volatile("{\n.reg .pred p;\nsetp.ne.b32 p, %130, 0;\n"
    "wgmma.mma_async.sync.aligned.m64n256k16.f32.bf16.bf16 {%0, %1, %2, %3, %4, %5, %6, %7, %8, %9, %10, %11, %12, %13, %14, %15, %16, %17, %18, %19, %20, %21, %22, %23, %24, %25, %26, %27, %28, %29, %30, %31, %32, %33, %34, %35, %36, %37, %38, %39, %40, %41, %42, %43, %44, %45, %46, %47, %48, %49, %50, %51, %52, %53, %54, %55, %56, %57, %58, %59, %60, %61, %62, %63, %64, %65, %66, %67, %68, %69, %70, %71, %72, %73, %74, %75, %76, %77, %78, %79, %80, %81, %82, %83, %84, %85, %86, %87, %88, %89, %90, %91, %92, %93, %94, %95, %96, %97, %98, %99, %100, %101, %102, %103, %104, %105, %106, %107, %108, %109, %110, %111, %112, %113, %114, %115, %116, %117, %118, %119, %120, %121, %122, %123, %124, %125, %126, %127}, %128, %129, p, 1, 1, %131, 1;\n}\n"
    : "+f"(d[0]), "+f"(d[1]), "+f"(d[2]), "+f"(d[3]), "+f"(d[4]), "+f"(d[5]), "+f"(d[6]), "+f"(d[7]), "+f"(d[8]), "+f"(d[9]), "+f"(d[10]), "+f"(d[11]), "+f"(d[12]), "+f"(d[13]), "+f"(d[14]), "+f"(d[15]), "+f"(d[16]), "+f"(d[17]), "+f"(d[18]), "+f"(d[19]), "+f"(d[20]), "+f"(d[21]), "+f"(d[22]), "+f"(d[23]), "+f"(d[24]), "+f"(d[25]), "+f"(d[26]), "+f"(d[27]), "+f"(d[28]), "+f"(d[29]), "+f"(d[30]), "+f"(d[31]), "+f"(d[32]), "+f"(d[33]), "+f"(d[34]), "+f"(d[35]), "+f"(d[36]), "+f"(d[37]), "+f"(d[38]), "+f"(d[39]), "+f"(d[40]), "+f"(d[41]), "+f"(d[42]), "+f"(d[43]), "+f"(d[44]), "+f"(d[45]), "+f"(d[46]), "+f"(d[47]), "+f"(d[48]), "+f"(d[49]), "+f"(d[50]), "+f"(d[51]), "+f"(d[52]), "+f"(d[53]), "+f"(d[54]), "+f"(d[55]), "+f"(d[56]), "+f"(d[57]), "+f"(d[58]), "+f"(d[59]), "+f"(d[60]), "+f"(d[61]), "+f"(d[62]), "+f"(d[63]), "+f"(d[64]), "+f"(d[65]), "+f"(d[66]), "+f"(d[67]), "+f"(d[68]), "+f"(d[69]), "+f"(d[70]), "+f"(d[71]), "+f"(d[72]), "+f"(d[73]), "+f"(d[74]), "+f"(d[75]), "+f"(d[76]), "+f"(d[77]), "+f"(d[78]), "+f"(d[79]), "+f"(d[80]), "+f"(d[81]), "+f"(d[82]), "+f"(d[83]), "+f"(d[84]), "+f"(d[85]), "+f"(d[86]), "+f"(d[87]), "+f"(d[88]), "+f"(d[89]), "+f"(d[90]), "+f"(d[91]), "+f"(d[92]), "+f"(d[93]), "+f"(d[94]), "+f"(d[95]), "+f"(d[96]), "+f"(d[97]), "+f"(d[98]), "+f"(d[99]), "+f"(d[100]), "+f"(d[101]), "+f"(d[102]), "+f"(d[103]), "+f"(d[104]), "+f"(d[105]), "+f"(d[106]), "+f"(d[107]), "+f"(d[108]), "+f"(d[109]), "+f"(d[110]), "+f"(d[111]), "+f"(d[112]), "+f"(d[113]), "+f"(d[114]), "+f"(d[115]), "+f"(d[116]), "+f"(d[117]), "+f"(d[118]), "+f"(d[119]), "+f"(d[120]), "+f"(d[121]), "+f"(d[122]), "+f"(d[123]), "+f"(d[124]), "+f"(d[125]), "+f"(d[126]), "+f"(d[127])
    : "l"(da), "l"(db), "r"(sc), "n"(TA));
}

template<int TA> __device__ __forceinline__ void wgmma_n192(float (&d)[128], uint64_t da, uint64_t db, int sc) {
  asm volatile("{\n.reg .pred p;\nsetp.ne.b32 p, %98, 0;\n"
    "wgmma.mma_async.sync.aligned.m64n192k16.f32.bf16.bf16 {%0, %1, %2, %3, %4, %5, %6, %7, %8, %9, %10, %11, %12, %13, %14, %15, %16, %17, %18, %19, %20, %21, %22, %23, %24, %25, %26, %27, %28, %29, %30, %31, %32, %33, %34, %35, %36, %37, %38, %39, %40, %41, %42, %43, %44, %45, %46, %47, %48, %49, %50, %51, %52, %53, %54, %55, %56, %57, %58, %59, %60, %61, %62, %63, %64, %65, %66, %67, %68, %69, %70, %71, %72, %73, %74, %75, %76, %77, %78, %79, %80, %81, %82, %83, %84, %85, %86, %87, %88, %89, %90, %91, %92, %93, %94, %95}, %96, %97, p, 1, 1, %99, 1;\n}\n"
    : "+f"(d[0]), "+f"(d[1]), "+f"(d[2]), "+f"(d[3]), "+f"(d[4]), "+f"(d[5]), "+f"(d[6]), "+f"(d[7]), "+f"(d[8]), "+f"(d[9]), "+f"(d[10]), "+f"(d[11]), "+f"(d[12]), "+f"(d[13]), "+f"(d[14]), "+f"(d[15]), "+f"(d[16]), "+f"(d[17]), "+f"(d[18]), "+f"(d[19]), "+f"(d[20]), "+f"(d[21]), "+f"(d[22]), "+f"(d[23]), "+f"(d[24]), "+f"(d[25]), "+f"(d[26]), "+f"(d[27]), "+f"(d[28]), "+f"(d[29]), "+f"(d[30]), "+f"(d[31]), "+f"(d[32]), "+f"(d[33]), "+f"(d[34]), "+f"(d[35]), "+f"(d[36]), "+f"(d[37]), "+f"(d[38]), "+f"(d[39]), "+f"(d[40]), "+f"(d[41]), "+f"(d[42]), "+f"(d[43]), "+f"(d[44]), "+f"(d[45]), "+f"(d[46]), "+f"(d[47]), "+f"(d[48]), "+f"(d[49]), "+f"(d[50]), "+f"(d[51]), "+f"(d[52]), "+f"(d[53]), "+f"(d[54]), "+f"(d[55]), "+f"(d[56]), "+f"(d[57]), "+f"(d[58]), "+f"(d[59]), "+f"(d[60]), "+f"(d[61]), "+f"(d[62]), "+f"(d[63]), "+f"(d[64]), "+f"(d[65]), "+f"(d[66]), "+f"(d[67]), "+f"(d[68]), "+f"(d[69]), "+f"(d[70]), "+f"(d[71]), "+f"(d[72]), "+f"(d[73]), "+f"(d[74]), "+f"(d[75]), "+f"(d[76]), "+f"(d[77]), "+f"(d[78]), "+f"(d[79]), "+f"(d[80]), "+f"(d[81]), "+f"(d[82]), "+f"(d[83]), "+f"(d[84]), "+f"(d[85]), "+f"(d[86]), "+f"(d[87]), "+f"(d[88]), "+f"(d[89]), "+f"(d[90]), "+f"(d[91]), "+f"(d[92]), "+f"(d[93]), "+f"(d[94]), "+f"(d[95])
    : "l"(da), "l"(db), "r"(sc), "n"(TA));
}

struct GemmParams {
  CUtensorMap mA[4];
  CUtensorMap mB[6];
  const bf16* x; const bf16* b1; const bf16* b2; bf16* out;
  int stride, kid;
  int wait_at_end;
  uint16_t job[960];
};
constexpr int NSTAGE = 4, STAGE_BYTES = 49152;
constexpr int GEMM_SMEM = NSTAGE * STAGE_BYTES + 8 * 2048 + 256 + 1024;

__device__ __forceinline__ uint64_t mkdesc(uint32_t addr, uint32_t lbo, uint32_t sbo) {
  return (uint64_t)((addr & 0x3FFFF) >> 4) | ((uint64_t)(lbo >> 4) << 16) | ((uint64_t)(sbo >> 4) << 32) | (1ull << 62);
}
__device__ __forceinline__ float gelu_tanh(float u) {
  float z = 0.7978845608028654f * (u + 0.044715f * u * u * u);
  float e = __expf(2.f * z);
  float th = 1.f - __fdividef(2.f, e + 1.f);
  return 0.5f * u * (1.f + th);
}
template <int BN, int TA>
__device__ __forceinline__ void gemm_mainloop(float (&d)[128], int kiters, uint32_t sbase, uint32_t fullb, uint32_t emptyb_l, uint32_t emptyb_r,
                                              int wg, int& stage, uint32_t& phase, bool elect) {
  int prev = -1;
  for (int k = 0; k < kiters; k++) {
    mbar_wait(fullb + stage * 8, phase);
    uint32_t a = sbase + stage * STAGE_BYTES + wg * 8192, b = sbase + stage * STAGE_BYTES + 16384;
    asm volatile("wgmma.fence.sync.aligned;" ::: "memory");
#pragma unroll
    for (int kk = 0; kk < 4; kk++) {
      uint64_t da = TA ? mkdesc(a + kk * 2048, 8192, 1024) : mkdesc(a + kk * 32, 16, 1024);
      uint64_t db = mkdesc(b + kk * 2048, 8192, 1024);
      if constexpr (BN == 256) wgmma_n256<TA>(d, da, db, (k | kk) != 0); else wgmma_n192<TA>(d, da, db, (k | kk) != 0);
    }
    asm volatile("wgmma.commit_group.sync.aligned;" ::: "memory");
    asm volatile("wgmma.wait_group.sync.aligned 1;" ::: "memory");
    if (prev >= 0 && elect) { mbar_arrive_remote(emptyb_l + prev * 8); mbar_arrive_remote(emptyb_r + prev * 8); }
    prev = stage;
    if (++stage == NSTAGE) { stage = 0; phase ^= 1; }
  }
  asm volatile("wgmma.wait_group.sync.aligned 0;" ::: "memory");
  if (elect) { mbar_arrive_remote(emptyb_l + prev * 8); mbar_arrive_remote(emptyb_r + prev * 8); }
}
template <int BN, class F>
__device__ __forceinline__ void store_tile(const float (&d)[128], uint32_t stg, bf16* dst, int ld, int lane, F f) {
#pragma unroll
  for (int c = 0; c < BN / 64; c++) {
#pragma unroll
    for (int i = 0; i < 8; i += 2) {
      const int o = c * 32 + i * 4;
      uint32_t r0 = f(d[o], d[o + 1], 0, c * 64 + i * 8), r1 = f(d[o + 2], d[o + 3], 1, c * 64 + i * 8);
      uint32_t r2 = f(d[o + 4], d[o + 5], 0, c * 64 + i * 8 + 8), r3 = f(d[o + 6], d[o + 7], 1, c * 64 + i * 8 + 8);
      int m = lane >> 3, row = (m & 1) * 8 + (lane & 7), ch = (i + (m >> 1)) ^ (row & 7);
      asm volatile("stmatrix.sync.aligned.m8n8.x4.shared.b16 [%0], {%1,%2,%3,%4};" ::"r"(stg + row * 128 + ch * 16), "r"(r0), "r"(r1), "r"(r2), "r"(r3) : "memory");
    }
    __syncwarp();
#pragma unroll
    for (int j = 0; j < 4; j++) {
      int idx = lane + 32 * j, row = idx >> 3, ch = idx & 7;
      uint4 v;
      asm volatile("ld.shared.v4.u32 {%0,%1,%2,%3}, [%4];" : "=r"(v.x), "=r"(v.y), "=r"(v.z), "=r"(v.w) : "r"(stg + row * 128 + ((ch ^ (row & 7)) * 16)));
      *(uint4*)(dst + (size_t)row * ld + c * 64 + ch * 8) = v;
    }
    __syncwarp();
  }
}

__global__ void __launch_bounds__(384, 1) gemm_kernel(const __grid_constant__ GemmParams p) {
  extern __shared__ uint8_t smem_raw[];
  const uint32_t sbase = (smem_u32(smem_raw) + 1023) & ~1023u;
  const uint32_t stg0 = sbase + NSTAGE * STAGE_BYTES, fullb = stg0 + 8 * 2048, emptyb = fullb + 64;
  const uint32_t rank = cluster_rank();
  const int wg = __shfl_sync(~0u, (int)(threadIdx.x >> 7), 0), lane = threadIdx.x & 31;
  const int cl = blockIdx.x >> 1;
  if (threadIdx.x == 0) {
    for (int i = 0; i < NSTAGE; i++) { mbar_init(fullb + i * 8, 1); mbar_init(emptyb + i * 8, 4); }
    asm volatile("fence.mbarrier_init.release.cluster;" ::: "memory");
  }
  cluster_sync();
  if (blockIdx.x == 0 && threadIdx.x == 0) PT(1 + p.kid * 2);
  const uint16_t* jobs = p.job + cl * p.stride;
  if (wg == 0) {
    asm volatile("setmaxnreg.dec.sync.aligned.u32 40;");
    if (threadIdx.x == 0) {
      int stage = 0; uint32_t phase = 1;
      for (int j = 0; j < p.stride; j++) {
        uint32_t job = jobs[j];
        if (job == 0xFFFF) break;
        int type = job >> 12, m = (job >> 6) & 63, n = job & 63;
        int row0 = m * 256 + rank * 128;
        int bn = type < 3 ? 256 : 192;
        int kit = type < 3 ? 9 : (type == 3 ? 32 : (type == 4 ? 72 : 64));
        const CUtensorMap* ma = &p.mA[type < 3 ? 0 : type - 2];
        const CUtensorMap* mb = &p.mB[type];
        bool ta = (type == 3 || type == 4);
        if (type == 4) {
          uint32_t v;
          do { asm volatile("ld.acquire.gpu.global.u32 %0, [%1];" : "=r"(v) : "l"(&g_cnt[0]) : "memory"); if (v < 108) __nanosleep(100); } while (v < 108);
          asm volatile("fence.proxy.async;" ::: "memory");
        }
        for (int k = 0; k < kit; k++) {
          mbar_wait_cl(emptyb + stage * 8, phase);
          uint32_t fb = fullb + stage * 8, a = sbase + stage * STAGE_BYTES, b = a + 16384;
          mbar_expect(fb, 16384 + bn * 128);
          if (ta) { tma2d(a, ma, row0, k * 64, fb); tma2d(a + 8192, ma, row0 + 64, k * 64, fb); }
          else tma2d(a, ma, k * 64, row0, fb);
          for (int i = 0; i < bn / 64; i++) tma2d_mc(b + i * 8192 + rank * 4096, mb, n * bn + i * 64, k * 64 + rank * 32, fb, (uint16_t)3);
          if (++stage == NSTAGE) { stage = 0; phase ^= 1; }
        }
      }
    }
    __syncwarp();
    if (p.wait_at_end) pdl_wait();
    cluster_sync();
  } else {
    asm volatile("setmaxnreg.inc.sync.aligned.u32 232;");
    const int cw = wg - 1, warp = __shfl_sync(~0u, (int)(threadIdx.x >> 5) & 3, 0);
    const uint32_t eb_l = mapa(emptyb, rank), eb_r = mapa(emptyb, rank ^ 1);
    const uint32_t stg = stg0 + (cw * 4 + warp) * 2048;
    const bool elect = (threadIdx.x & 127) == 0;
    const int g = lane >> 2, t = lane & 3;
    int stage = 0; uint32_t phase = 0;
    float d[128];
    for (int j = 0; j < p.stride; j++) {
      uint32_t job = jobs[j];
      if (job == 0xFFFF) break;
      int type = job >> 12, m = (job >> 6) & 63, n = job & 63;
      int row0 = m * 256 + rank * 128 + cw * 64 + warp * 16;
      if (type < 3) {
        gemm_mainloop<256, 0>(d, 9, sbase, fullb, eb_l, eb_r, cw, stage, phase, elect);
        bf16* dst = (type == 0 ? g_q : (type == 1 ? g_k : g_v)) + (size_t)row0 * HD_ + n * 256;
        store_tile<256>(d, stg, dst, HD_, lane, [](float a, float b, int, int) { return pack_bf16(a, b); });
      } else if (type == 3) {
        gemm_mainloop<192, 1>(d, 32, sbase, fullb, eb_l, eb_r, cw, stage, phase, elect);
        float bb[2] = {__bfloat162float(p.b1[row0 + g]), __bfloat162float(p.b1[row0 + g + 8])};
        store_tile<192>(d, stg, g_ut + (size_t)row0 * D_ + n * 192, D_, lane,
                        [&](float a, float b, int h, int) { return pack_bf16(gelu_tanh(a + bb[h]), gelu_tanh(b + bb[h])); });
        __threadfence();
        asm volatile("fence.proxy.async;" ::: "memory");
        asm volatile("bar.sync %0, 256;" ::"r"(1) : "memory");
        if (threadIdx.x == 128) atomicAdd(&g_cnt[0], 1);
      } else if (type == 4) {
        gemm_mainloop<192, 1>(d, 72, sbase, fullb, eb_l, eb_r, cw, stage, phase, elect);
        float bb[2] = {__bfloat162float(p.b2[row0 + g]), __bfloat162float(p.b2[row0 + g + 8])};
#pragma unroll
        for (int i = 0; i < 24; i++)
#pragma unroll
          for (int h = 0; h < 2; h++) {
            size_t off = (size_t)(row0 + g + h * 8) * D_ + n * 192 + i * 8 + t * 2;
            float2 xv = unpack_bf16(*(const uint32_t*)(p.x + off));
            *(float2*)(g_yb + off) = make_float2(d[i * 4 + h * 2] + bb[h] + xv.x, d[i * 4 + h * 2 + 1] + bb[h] + xv.y);
          }
      } else {
        gemm_mainloop<192, 0>(d, 64, sbase, fullb, eb_l, eb_r, cw, stage, phase, elect);
        const float* yb = g_yb + (size_t)(row0 + g) * D_ + n * 192 + t * 2;
        store_tile<192>(d, stg, p.out + (size_t)row0 * D_ + n * 192, D_, lane,
                        [&](float a, float b, int h, int c) { float2 y = *(const float2*)(yb + h * 8 * D_ + c); return pack_bf16(a + y.x, b + y.y); });
      }
      if (blockIdx.x == 0 && threadIdx.x == 128) PT(2048 + p.kid * 64 + j);
    }
    if (blockIdx.x == 0 && threadIdx.x == 128) PT(2 + p.kid * 2);
    if (p.wait_at_end) pdl_wait();
    cluster_sync();
  }
}

__global__ void __launch_bounds__(128) attn_kernel() {
  __shared__ __align__(128) uint8_t sm[4][48 * 256];
  const int warp = threadIdx.x >> 5, lane = threadIdx.x & 31, g = lane >> 2, t = lane & 3;
  const int id = blockIdx.x * 4 + warp, seg = id >> 5, h = id & 31;
  const uint32_t sv = smem_u32(sm[warp]);
  if (blockIdx.x == 0 && threadIdx.x == 0) PT(9);
  const size_t tok0 = (size_t)seg * 32;
  for (int i = lane; i < 40 * 16; i += 32) {
    int r = i >> 4, c = i & 15;
    const bf16* src = (r < 8 ? g_vm + ((size_t)seg * 8 + r) * HD_ : g_v + (tok0 + r - 8) * HD_) + h * 128 + c * 8;
    cp16(sv + r * 256 + ((c ^ (r & 7)) * 16), src);
  }
  for (int i = lane; i < 8 * 16; i += 32) *(uint4*)(sm[warp] + 40 * 256 + i * 16) = make_uint4(0, 0, 0, 0);
  asm volatile("cp.async.commit_group;" ::: "memory");
  float s[2][5][4];
#pragma unroll
  for (int m = 0; m < 2; m++)
#pragma unroll
    for (int n = 0; n < 5; n++) { s[m][n][0] = s[m][n][1] = s[m][n][2] = s[m][n][3] = 0.f; }
#pragma unroll
  for (int j = 0; j < 4; j++) {
    uint4 qa[2][2], kb[5];
#pragma unroll
    for (int m = 0; m < 2; m++)
#pragma unroll
      for (int hh = 0; hh < 2; hh++) qa[m][hh] = *(const uint4*)(g_q + (tok0 + m * 16 + hh * 8 + g) * HD_ + h * 128 + j * 32 + t * 8);
#pragma unroll
    for (int n = 0; n < 5; n++)
      kb[n] = *(const uint4*)((n == 0 ? g_km + ((size_t)seg * 8 + g) * HD_ : g_k + (tok0 + (n - 1) * 8 + g) * HD_) + h * 128 + j * 32 + t * 8);
#pragma unroll
    for (int m = 0; m < 2; m++) {
      uint32_t a0[4] = {qa[m][0].x, qa[m][1].x, qa[m][0].y, qa[m][1].y}, a1[4] = {qa[m][0].z, qa[m][1].z, qa[m][0].w, qa[m][1].w};
#pragma unroll
      for (int n = 0; n < 5; n++) { mma16816(s[m][n], a0, kb[n].x, kb[n].y); mma16816(s[m][n], a1, kb[n].z, kb[n].w); }
    }
  }
  const float sc = 0.08838834764831845f * 1.4426950408889634f;
  uint32_t pa[2][3][4];
#pragma unroll
  for (int m = 0; m < 2; m++) {
    float inv[2];
#pragma unroll
    for (int hh = 0; hh < 2; hh++) {
      int qi = 8 + m * 16 + hh * 8 + g;
      float mx = -INFINITY;
#pragma unroll
      for (int n = 0; n < 5; n++)
#pragma unroll
        for (int e = 0; e < 2; e++) { float& z = s[m][n][hh * 2 + e]; z = (n * 8 + t * 2 + e <= qi) ? z * sc : -INFINITY; mx = fmaxf(mx, z); }
      mx = fmaxf(mx, __shfl_xor_sync(~0u, mx, 1)); mx = fmaxf(mx, __shfl_xor_sync(~0u, mx, 2));
      float sum = 0.f;
#pragma unroll
      for (int n = 0; n < 5; n++)
#pragma unroll
        for (int e = 0; e < 2; e++) { float& z = s[m][n][hh * 2 + e]; z = exp2f(z - mx); sum += z; }
      sum += __shfl_xor_sync(~0u, sum, 1); sum += __shfl_xor_sync(~0u, sum, 2);
      inv[hh] = 1.f / sum;
    }
#pragma unroll
    for (int kk = 0; kk < 3; kk++) {
      pa[m][kk][0] = pack_bf16(s[m][2 * kk][0] * inv[0], s[m][2 * kk][1] * inv[0]);
      pa[m][kk][1] = pack_bf16(s[m][2 * kk][2] * inv[1], s[m][2 * kk][3] * inv[1]);
      if (kk < 2) {
        pa[m][kk][2] = pack_bf16(s[m][2 * kk + 1][0] * inv[0], s[m][2 * kk + 1][1] * inv[0]);
        pa[m][kk][3] = pack_bf16(s[m][2 * kk + 1][2] * inv[1], s[m][2 * kk + 1][3] * inv[1]);
      } else { pa[m][kk][2] = 0; pa[m][kk][3] = 0; }
    }
  }
  asm volatile("cp.async.wait_group 0;" ::: "memory");
  __syncwarp();
  uint32_t ov[2][16][2];
#pragma unroll
  for (int np = 0; np < 8; np++) {
    float o[2][2][4] = {};
#pragma unroll
    for (int kk = 0; kk < 3; kk++) {
      uint32_t b[4];
      int mi = lane >> 3, r = kk * 16 + (mi & 1) * 8 + (lane & 7), c = np * 2 + (mi >> 1);
      ldsm4t(b, sv + r * 256 + ((c ^ (r & 7)) * 16));
#pragma unroll
      for (int m = 0; m < 2; m++) { mma16816(o[m][0], pa[m][kk], b[0], b[1]); mma16816(o[m][1], pa[m][kk], b[2], b[3]); }
    }
#pragma unroll
    for (int m = 0; m < 2; m++)
#pragma unroll
      for (int q = 0; q < 2; q++) { ov[m][np * 2 + q][0] = pack_bf16(o[m][q][0], o[m][q][1]); ov[m][np * 2 + q][1] = pack_bf16(o[m][q][2], o[m][q][3]); }
  }
  __syncwarp();
#pragma unroll
  for (int m = 0; m < 2; m++)
#pragma unroll
    for (int n = 0; n < 16; n++)
#pragma unroll
      for (int hh = 0; hh < 2; hh++) {
        int r = m * 16 + hh * 8 + g;
        *(uint32_t*)(sm[warp] + r * 256 + ((n ^ (r & 7)) * 16) + t * 4) = ov[m][n][hh];
      }
  __syncwarp();
#pragma unroll
  for (int i = 0; i < 16; i++) {
    int idx = lane + 32 * i, r = idx >> 4, c = idx & 15;
    *(uint4*)(g_o + (tok0 + r) * HD_ + h * 128 + c * 8) = *(const uint4*)(sm[warp] + r * 256 + ((c ^ (r & 7)) * 16));
  }
}
constexpr int CH_WV = 0;
constexpr int CH_MEM = CH_WV + 73728;
constexpr int CH_KB = CH_MEM + 9216;
constexpr int CH_VB = CH_KB + 12288;
constexpr int CH_WO = CH_VB + 12288;
constexpr int CH_Q = CH_WO + 81920;
constexpr int CH_R1 = CH_Q + 1024;
constexpr int CH_SC = CH_R1 + 4096;
constexpr int CH_OF = CH_SC + 3584;
constexpr int CH_R2 = CH_OF + 8192;
constexpr int CH_BAR = CH_R2 + 12288;
constexpr int CHAIN_SMEM = CH_BAR + 64 + 1024;
#define NREGT 1
__device__ __forceinline__ void st_async1(uint32_t a, uint32_t v, uint32_t bar) { asm volatile("st.async.weak.shared::cluster.mbarrier::complete_tx::bytes.b32 [%0], %1, [%2];" ::"r"(a), "r"(v), "r"(bar) : "memory"); }
__device__ __forceinline__ void st_async2(uint32_t a, uint32_t v0, uint32_t v1, uint32_t bar) { asm volatile("st.async.weak.shared::cluster.mbarrier::complete_tx::bytes.v2.b32 [%0], {%1, %2}, [%3];" ::"r"(a), "r"(v0), "r"(v1), "r"(bar) : "memory"); }
__device__ __forceinline__ uint4 lds128(uint32_t a) { uint4 v; asm volatile("ld.shared.v4.u32 {%0,%1,%2,%3}, [%4];" : "=r"(v.x), "=r"(v.y), "=r"(v.z), "=r"(v.w) : "r"(a) : "memory"); return v; }
__device__ __forceinline__ void sts128f(uint32_t a, const float (&c)[4]) { asm volatile("st.shared.v4.f32 [%0], {%1,%2,%3,%4};" ::"r"(a), "f"(c[0]), "f"(c[1]), "f"(c[2]), "f"(c[3]) : "memory"); }
__device__ __forceinline__ void sts32(uint32_t a, uint32_t v) { asm volatile("st.shared.u32 [%0], %1;" ::"r"(a), "r"(v) : "memory"); }
__device__ __forceinline__ void mbar_wait_b(uint32_t b, uint32_t parity) {
  uint32_t ok; int n = 0;
  do { asm volatile("{\n.reg .pred p;\nmbarrier.try_wait.parity.shared::cta.b64 p, [%1], %2;\nselp.u32 %0, 1, 0, p;\n}" : "=r"(ok) : "r"(b), "r"(parity) : "memory"); } while (!ok && ++n < (1 << 20));
}
#define BAR_ALL() asm volatile("bar.sync 0, 256;" ::: "memory")

__global__ void __launch_bounds__(256, 1) chain_kernel(const bf16* __restrict__ mem0, const bf16* __restrict__ Wq, const bf16* __restrict__ Wk,
                                                       const bf16* __restrict__ Wv, const bf16* __restrict__ Wo) {
  extern __shared__ uint8_t smem_raw[];
  const uint32_t sb = (smem_u32(smem_raw) + 1023) & ~1023u;
  const int tid = threadIdx.x, warp = __shfl_sync(~0u, tid >> 5, 0), wgi = __shfl_sync(~0u, tid >> 7, 0), lane = tid & 31, g = lane >> 2, t = lane & 3;
  const uint32_t r = cluster_rank();
  const int c = blockIdx.x >> 3, h = 4 * c + (r >> 1), j0 = h * 128 + (r & 1) * 64;
  const uint32_t bm = sb + CH_BAR, bs = bm + 8, bo = bm + 16;
  pdl_launch();
  if (blockIdx.x == 0 && tid == 0) PT(7);
  if (tid == 0) { mbar_init(bm, 1); mbar_init(bs, 1); mbar_init(bo, 1); asm volatile("fence.mbarrier_init.release.cluster;" ::: "memory"); }
  const int mi = lane >> 3, l7 = lane & 7;
  for (int i = tid; i < 576 * 8; i += 256) {
    int row = i >> 3, ch = i & 7;
    cp16(sb + CH_WV + row * 128 + ((ch ^ (row & 7)) * 16), Wq + (size_t)row * HD_ + j0 + ch * 8);
    cp16(sb + CH_WO + row * 128 + ((ch ^ (row & 7)) * 16), Wk + (size_t)row * HD_ + j0 + ch * 8);
  }
  asm volatile("cp.async.commit_group;\ncp.async.wait_group 0;" ::: "memory");
  BAR_ALL();
  uint32_t w1[36][4];
#pragma unroll
  for (int i = 0; i < 36; i++) {
    int row = i * 16 + (mi >> 1) * 8 + l7, ch = ((warp & 3) * 2 + (mi & 1)) ^ (row & 7);
    ldsm4t(w1[i], sb + (wgi ? CH_WO : CH_WV) + row * 128 + ch * 16);
  }
  BAR_ALL();
  for (int i = tid; i < 512 * 10; i += 256) {
    int row = i / 10, ch = i - row * 10;
    cp16(sb + CH_WV + row * 176 + ch * 16, Wo + (size_t)(c * 512 + row) * D_ + (ch < 8 ? r * 64 + ch * 8 : 512 + (r >> 1) * 16 + (ch - 8) * 8));
  }
  asm volatile("cp.async.commit_group;\ncp.async.wait_group 0;" ::: "memory");
  BAR_ALL();
  uint32_t wo[16][4];
#pragma unroll
  for (int i = 0; i < 16; i++) ldsm4t(wo[i], sb + CH_WV + ((wgi * 16 + i) * 16 + (mi >> 1) * 8 + l7) * 176 + ((warp & 3) * 2 + (mi & 1)) * 16);
  for (int u = warp; u < 16; u += 8) {
    uint32_t a[4];
    ldsm4t(a, sb + CH_WV + (((r & 1) * 16 + u) * 16 + (mi >> 1) * 8 + l7) * 176 + (8 + (mi & 1)) * 16);
    asm volatile("st.shared.v4.u32 [%0], {%1,%2,%3,%4};" ::"r"(sb + CH_WO + u * 512 + lane * 16), "r"(a[0]), "r"(a[1]), "r"(a[2]), "r"(a[3]) : "memory");
  }
  BAR_ALL();
  for (int i = tid; i < 576 * 8; i += 256) {
    int row = i >> 3, ch = i & 7;
    cp16(sb + CH_WV + row * 128 + ((ch ^ (row & 7)) * 16), Wv + (size_t)row * HD_ + j0 + ch * 8);
  }
  for (int i = tid; i < 8 * 72; i += 256) {
    int row = i / 72, ch = i - row * 72;
    cp16(sb + CH_MEM + ch * 128 + row * 16, mem0 + row * D_ + ch * 8);
  }
  for (int i = tid; i < 4 * 64; i += 256) {
    int b = i >> 6, o = i & 63;
    asm volatile("st.shared.v4.u32 [%0], {%1,%1,%1,%1};" ::"r"(sb + CH_KB + b * 6144 + 40 * 128 + o * 16), "r"(0) : "memory");
  }
  pdl_wait();
  auto prefetch_kv = [&](int s) {
#pragma unroll
    for (int i = 0; i < 2; i++) {
      int u = tid + i * 256, which = u >> 8, row = (u & 255) >> 3, ch = u & 7;
      const bf16* src = (which ? g_v : g_k) + (size_t)(s * 32 + row) * HD_ + j0 + ch * 8;
      cp16(sb + (which ? CH_VB : CH_KB) + (s & 1) * 6144 + (row + 8) * 128 + ((ch ^ (row & 7)) * 16), src);
    }
    asm volatile("cp.async.commit_group;" ::: "memory");
  };
  prefetch_kv(0);
  asm volatile("cp.async.wait_group 0;" ::: "memory");
  asm volatile("fence.proxy.async.shared::cta;" ::: "memory");
  BAR_ALL();
  cluster_sync();
  const uint32_t peer = r ^ 1;
  const uint32_t sc_l = mapa(sb + CH_SC + (r & 1) * 1792, r), sc_r = mapa(sb + CH_SC + (r & 1) * 1792, peer), bs_l = mapa(bs, r), bs_r = mapa(bs, peer);
  const uint32_t cl0 = mapa(sb, 0), clstep = mapa(sb, 1) - cl0;

  if (blockIdx.x == 0 && tid == 0) PT(10);
#define CP(i) if (blockIdx.x == 0 && lane == 0 && warp == ((i) == 5 ? 4 : 0)) PC(64 + s * 16 + (i))
  for (int s = 0; s < NSEG; s++) {
    CP(0);
    const uint32_t par = s & 1, kb = sb + CH_KB + par * 6144, vb = sb + CH_VB + par * 6144;
    if (s > 0) mbar_wait_b(bm, par ^ 1);
    CP(1);
    if (tid == 0 && s < NSEG - 1) { mbar_expect(bs, 2560); mbar_expect(bo, 8192); mbar_expect(bm, 9216); }
    auto phase1 = [&]() {
      if (s + 1 < NSEG) prefetch_kv(s + 1);
      float pa[3][4] = {};
#pragma unroll
      for (int i = 0; i < 36; i += 2) {
        uint32_t b[4];
        ldsm4(b, sb + CH_MEM + i * 256 + mi * 128 + l7 * 16);
        mma16816(pa[i % 3], w1[i], b[0], b[1]); mma16816(pa[(i + 1) % 3], w1[i + 1], b[2], b[3]);
      }
      CP(2);
      uint32_t b0 = movm(pack_bf16(pa[0][0] + pa[1][0] + pa[2][0], pa[0][1] + pa[1][1] + pa[2][1]));
      uint32_t b1 = movm(pack_bf16(pa[0][2] + pa[1][2] + pa[2][2], pa[0][3] + pa[1][3] + pa[2][3]));
      uint32_t dst = (wgi ? kb : sb + CH_Q) + g * 128 + t * 4;
      sts32(dst + ((((warp & 3) * 2) ^ g) * 16), b0); sts32(dst + ((((warp & 3) * 2 + 1) ^ g) * 16), b1);
      if (wgi) { uint32_t* gp = (uint32_t*)(g_km + ((size_t)s * 8 + g) * HD_ + j0 + (warp & 3) * 16 + t * 2); gp[0] = b0; gp[4] = b1; }
      asm volatile("cp.async.wait_group 1;" ::: "memory");
    };
    if (wgi == 0) {
      phase1();
      float va[4][4] = {};
      asm volatile("wgmma.fence.sync.aligned;" ::: "memory");
#pragma unroll
      for (int ks = 0; ks < 36; ks++) {
        uint64_t da = mkdesc(sb + CH_WV + ks * 2048, 8192, 1024);
        uint64_t db = (uint64_t)(((sb + CH_MEM + ks * 256) & 0x3FFFF) >> 4) | ((uint64_t)(128 >> 4) << 16) | ((uint64_t)(256 >> 4) << 32);
        asm volatile("{\n.reg .pred p;\nsetp.ne.b32 p, %6, 0;\nwgmma.mma_async.sync.aligned.m64n8k16.f32.bf16.bf16 {%0,%1,%2,%3}, %4, %5, p, 1, 1, 1, 0;\n}"
                     : "+f"(va[ks & 3][0]), "+f"(va[ks & 3][1]), "+f"(va[ks & 3][2]), "+f"(va[ks & 3][3]) : "l"(da), "l"(db), "r"(ks >> 2));
      }
      asm volatile("wgmma.commit_group.sync.aligned;" ::: "memory");
      BAR_ALL();
      CP(4);
      asm volatile("wgmma.wait_group.sync.aligned 0;" ::: "memory");
#pragma unroll
      for (int i = 0; i < 4; i++) asm volatile("" : "+f"(va[i][0]), "+f"(va[i][1]), "+f"(va[i][2]), "+f"(va[i][3]) :: "memory");
      CP(6);
      uint32_t b0 = movm(pack_bf16(va[0][0] + va[1][0] + va[2][0] + va[3][0], va[0][1] + va[1][1] + va[2][1] + va[3][1]));
      uint32_t b1 = movm(pack_bf16(va[0][2] + va[1][2] + va[2][2] + va[3][2], va[0][3] + va[1][3] + va[2][3] + va[3][3]));
      sts32(vb + g * 128 + t * 4 + (((warp * 2) ^ g) * 16), b0); sts32(vb + g * 128 + t * 4 + (((warp * 2 + 1) ^ g) * 16), b1);
      uint32_t* gp = (uint32_t*)(g_vm + ((size_t)s * 8 + g) * HD_ + j0 + warp * 16 + t * 2); gp[0] = b0; gp[4] = b1;
      if (s < NSEG - 1) {
        __syncwarp();
        uint32_t vt[3][4];
#pragma unroll
        for (int kk = 0; kk < 3; kk++) { int row = kk * 16 + (mi >> 1) * 8 + l7; ldsm4t(vt[kk], vb + row * 128 + (((warp * 2 + (mi & 1)) ^ l7) * 16)); }
        mbar_wait_b(bs, par);
        CP(7);
        float z[10]; float mx = -INFINITY;
        const float scl = 0.08838834764831845f * 1.4426950408889634f;
#pragma unroll
        for (int i = 0; i < 5; i++) {
          float2 u0, u1; uint32_t a = sb + CH_SC + (g * 56 + i * 8 + 2 * t) * 4;
          asm volatile("ld.shared.v2.f32 {%0,%1}, [%2];" : "=f"(u0.x), "=f"(u0.y) : "r"(a) : "memory");
          asm volatile("ld.shared.v2.f32 {%0,%1}, [%2];" : "=f"(u1.x), "=f"(u1.y) : "r"(a + 1792) : "memory");
          z[2 * i] = (u0.x + u1.x) * scl; z[2 * i + 1] = (u0.y + u1.y) * scl;
        }
        mx = fmaxf(fmaxf(fmaxf(z[0], z[1]), fmaxf(z[2], z[3])), fmaxf(fmaxf(fmaxf(z[4], z[5]), fmaxf(z[6], z[7])), fmaxf(z[8], z[9])));
        mx = fmaxf(mx, __shfl_xor_sync(~0u, mx, 1)); mx = fmaxf(mx, __shfl_xor_sync(~0u, mx, 2));
        uint32_t pb[5];
#pragma unroll
        for (int i = 0; i < 5; i++) pb[i] = pack_bf16(exp2f(z[2 * i] - mx), exp2f(z[2 * i + 1] - mx));
        const uint32_t ones[4] = {0x3F803F80u, 0x3F803F80u, 0x3F803F80u, 0x3F803F80u};
        float o0[4] = {}, o1[4] = {}, o2[4] = {}, s0[4] = {}, s1[4] = {}, s2[4] = {};
        mma16816(o0, vt[0], pb[0], pb[1]); mma16816(s0, ones, pb[0], pb[1]);
        mma16816(o1, vt[1], pb[2], pb[3]); mma16816(s1, ones, pb[2], pb[3]);
        mma16816(o2, vt[2], pb[4], 0u); mma16816(s2, ones, pb[4], 0u);
        const float i0 = __fdividef(1.f, s0[0] + s1[0] + s2[0]), i1 = __fdividef(1.f, s0[1] + s1[1] + s2[1]);
        uint32_t f0 = movm(pack_bf16((o0[0] + o1[0] + o2[0]) * i0, (o0[1] + o1[1] + o2[1]) * i1));
        uint32_t f1 = movm(pack_bf16((o0[2] + o1[2] + o2[2]) * i0, (o0[3] + o1[3] + o2[3]) * i1));
        const int ks = r * 4 + warp;
        const uint32_t off = CH_OF + (ks >> 1) * 512 + lane * 16 + (ks & 1) * 8;
#pragma unroll
        for (int d = 0; d < 8; d++) st_async2(cl0 + d * clstep + off, f0, f1, cl0 + d * clstep + CH_BAR + 16);
      }
    } else {
      phase1();
      BAR_ALL();
      if (warp < 7 && s < NSEG - 1) {
        const int mt = warp - 4;
        float sa[4][4] = {};
#pragma unroll
        for (int kp = 0; kp < 2; kp++) {
          uint32_t b[4], a0[4], a1[4];
          ldsm4(b, sb + CH_Q + l7 * 128 + (((kp * 4 + mi) ^ l7) * 16));
          int row = mt * 16 + (mi & 1) * 8 + l7;
          ldsm4(a0, kb + row * 128 + (((kp * 4 + (mi >> 1)) ^ l7) * 16));
          ldsm4(a1, kb + row * 128 + (((kp * 4 + 2 + (mi >> 1)) ^ l7) * 16));
          mma16816(sa[2 * kp], a0, b[0], b[1]); mma16816(sa[2 * kp + 1], a1, b[2], b[3]);
        }
#pragma unroll
        for (int e = 0; e < 4; e++) {
          uint32_t off = ((2 * t + (e & 1)) * 56 + mt * 16 + (e >> 1) * 8 + g) * 4, v = __float_as_uint((sa[0][e] + sa[1][e]) + (sa[2][e] + sa[3][e]));
          if (mt < 2 || e < 2) { st_async1(sc_r + off, v, bs_r); st_async1(sc_l + off, v, bs_l); }
        }
        CP(5);
      }
    }
    if (s == NSEG - 1) break;
    CP(8);
    mbar_wait_b(bo, par);
    CP(9);
    const uint32_t tag = ((s >> 1) + 1) & 1;
    float* pbase = g_part + (size_t)par * 8 * 5120 + lane * 4;
    auto put = [&](int slot, const float (&a)[4]) {
      asm volatile("st.relaxed.gpu.global.v4.b32 [%0], {%1,%2,%3,%4};" ::"l"(pbase + c * 5120 + slot * 128), "r"((__float_as_uint(a[0]) & ~1u) | tag),
                   "r"((__float_as_uint(a[1]) & ~1u) | tag), "r"((__float_as_uint(a[2]) & ~1u) | tag), "r"((__float_as_uint(a[3]) & ~1u) | tag) : "memory");
    };
    {
      float acc[2][4] = {};
#pragma unroll
      for (int i = 0; i < 16; i += 2) {
        uint4 b = lds128(sb + CH_OF + (wgi * 8 + (i >> 1)) * 512 + lane * 16);
        mma16816(acc[0], wo[i], b.x, b.y); mma16816(acc[1], wo[i + 1], b.z, b.w);
      }
#pragma unroll
      for (int e = 0; e < 4; e++) acc[0][e] += acc[1][e];
      CP(10);
      const int w3 = warp & 3;
      if (wgi) {
        sts128f(sb + CH_R2 + w3 * 512 + lane * 16, acc[0]);
        asm volatile("bar.arrive %0, 64;" ::"r"(1 + w3) : "memory");
        if (w3 < 2) {
          float ex[2][4] = {};
#pragma unroll
          for (int i = 0; i < 8; i += 2) {
            uint4 b = lds128(sb + CH_OF + ((r & 1) * 8 + w3 * 4 + (i >> 1)) * 512 + lane * 16);
            uint4 v0 = lds128(sb + CH_WO + (w3 * 8 + i) * 512 + lane * 16), v1 = lds128(sb + CH_WO + (w3 * 8 + i + 1) * 512 + lane * 16);
            uint32_t a0[4] = {v0.x, v0.y, v0.z, v0.w}, a1[4] = {v1.x, v1.y, v1.z, v1.w};
            mma16816(ex[0], a0, b.x, b.y); mma16816(ex[1], a1, b.z, b.w);
          }
#pragma unroll
          for (int e = 0; e < 4; e++) ex[0][e] += ex[1][e];
          if (w3 == 1) { sts128f(sb + CH_R2 + 4 * 512 + lane * 16, ex[0]); asm volatile("bar.arrive 5, 64;" ::: "memory"); }
          else {
            asm volatile("bar.sync 5, 64;" ::: "memory");
            uint4 v = lds128(sb + CH_R2 + 4 * 512 + lane * 16);
            ex[0][0] += __uint_as_float(v.x); ex[0][1] += __uint_as_float(v.y); ex[0][2] += __uint_as_float(v.z); ex[0][3] += __uint_as_float(v.w);
            put(32 + r, ex[0]);
          }
        }
      } else {
        asm volatile("bar.sync %0, 64;" ::"r"(1 + w3) : "memory");
        uint4 v = lds128(sb + CH_R2 + w3 * 512 + lane * 16);
        acc[0][0] += __uint_as_float(v.x); acc[0][1] += __uint_as_float(v.y); acc[0][2] += __uint_as_float(v.z); acc[0][3] += __uint_as_float(v.w);
        put(r * 4 + w3, acc[0]);
      }
    }
    CP(11);
    if (warp < 4 || (warp == 6 && !(r & 1))) {
      const int tile = warp < 4 ? r * 4 + warp : 32 + (r >> 1), nrep = warp < 4 ? 1 : 2;
      float m[4] = {};
      for (int rep = 0; rep < nrep; rep++) {
        const float* pb = pbase + (warp < 4 ? tile : 32 + r + rep) * 128;
        uint4 v[8]; int n = 0; bool ok;
        do {
          ok = true;
#pragma unroll
          for (int i = 0; i < 8; i++) asm volatile("ld.relaxed.gpu.global.v4.b32 {%0,%1,%2,%3}, [%4];" : "=r"(v[i].x), "=r"(v[i].y), "=r"(v[i].z), "=r"(v[i].w) : "l"(pb + i * 5120) : "memory");
#pragma unroll
          for (int i = 0; i < 8; i++) ok = ok && (((v[i].x & v[i].y & v[i].z & v[i].w & 1u) == tag) && (((v[i].x | v[i].y | v[i].z | v[i].w) & 1u) == tag));
        } while (!ok && ++n < (1 << 18));
#pragma unroll
        for (int i = 0; i < 8; i++) { m[0] += __uint_as_float(v[i].x); m[1] += __uint_as_float(v[i].y); m[2] += __uint_as_float(v[i].z); m[3] += __uint_as_float(v[i].w); }
      }
      __syncwarp();
      CP(12);
      uint32_t b0 = movm(pack_bf16(m[0], m[1])), b1 = movm(pack_bf16(m[2], m[3]));
      const uint32_t off = CH_MEM + tile * 256 + g * 16 + t * 4;
#pragma unroll
      for (int d = 0; d < 8; d++) { st_async1(cl0 + d * clstep + off, b0, cl0 + d * clstep + CH_BAR); st_async1(cl0 + d * clstep + off + 128, b1, cl0 + d * clstep + CH_BAR); }
    }
  }
  if (blockIdx.x == 0 && tid == 0) PT(8);
  cluster_sync();
}
typedef CUresult (*EncodeFn)(CUtensorMap*, CUtensorMapDataType, cuuint32_t, void*, const cuuint64_t*, const cuuint64_t*, const cuuint32_t*, const cuuint32_t*,
                             CUtensorMapInterleave, CUtensorMapSwizzle, CUtensorMapL2promotion, CUtensorMapFloatOOBfill);
static EncodeFn g_enc;
static void mkmap(CUtensorMap* m, const void* ptr, int rows, int cols, int boxc, int boxr) {
  cuuint64_t dims[2] = {(cuuint64_t)cols, (cuuint64_t)rows}, strides[1] = {(cuuint64_t)cols * 2};
  cuuint32_t box[2] = {(cuuint32_t)boxc, (cuuint32_t)boxr}, es[2] = {1, 1};
  g_enc(m, CU_TENSOR_MAP_DATA_TYPE_BFLOAT16, 2, (void*)ptr, dims, strides, box, es, CU_TENSOR_MAP_INTERLEAVE_NONE, CU_TENSOR_MAP_SWIZZLE_128B,
        CU_TENSOR_MAP_L2_PROMOTION_L2_256B, CU_TENSOR_MAP_FLOAT_OOB_FILL_NONE);
}
static inline uint16_t mkjob(int type, int m, int n) { return (uint16_t)(type << 12 | m << 6 | n); }
static void schedule(GemmParams& p, const uint16_t* jobs, int nj, int ncl) {
  static const double cost[6] = {11.0, 11.0, 11.0, 26.5, 57.5, 51.5};
  double t[66] = {}; int cnt[66] = {};
  p.stride = 960 / ncl;
  for (int i = 0; i < 960; i++) p.job[i] = 0xFFFF;
  double g2_end = 0;
  for (int i = 0; i < nj; i++) {
    int b = 0;
    for (int c = 1; c < ncl; c++) if (t[c] < t[b] || (t[c] == t[b] && cnt[c] < cnt[b])) b = c;
    int ty = jobs[i] >> 12;
    if (ty == 4 && t[b] < g2_end) t[b] = g2_end;
    t[b] += cost[ty];
    if (ty == 3 && t[b] > g2_end) g2_end = t[b];
    p.job[b * p.stride + cnt[b]++] = jobs[i];
  }
}
template <class... A>
static void launch(void (*k)(A...), int grid, int block, int smem, int cluster, bool pdl, A... a) {
  cudaLaunchConfig_t c = {};
  c.gridDim = grid; c.blockDim = block; c.dynamicSmemBytes = smem; c.stream = cudaStreamPerThread;
  cudaLaunchAttribute at[2]; int n = 0;
  if (cluster > 1) { at[n].id = cudaLaunchAttributeClusterDimension; at[n].val.clusterDim.x = cluster; at[n].val.clusterDim.y = 1; at[n].val.clusterDim.z = 1; n++; }
  if (pdl) { at[n].id = cudaLaunchAttributeProgrammaticStreamSerialization; at[n].val.programmaticStreamSerializationAllowed = 1; n++; }
  c.attrs = at; c.numAttrs = n;
  cudaLaunchKernelEx(&c, k, a...);
}

extern "C" void kernel_launch(void* const* d_in, const int* in_sizes, int n_in, void* d_out, int out_size) {
  const bf16 *x = (const bf16*)d_in[0], *mem0 = (const bf16*)d_in[1], *Wq = (const bf16*)d_in[2], *Wk = (const bf16*)d_in[3], *Wv = (const bf16*)d_in[4],
             *Wo = (const bf16*)d_in[5], *w1 = (const bf16*)d_in[8], *b1 = (const bf16*)d_in[9], *w2 = (const bf16*)d_in[10], *b2 = (const bf16*)d_in[11];
  static bool init = false;
  static GemmParams pre, side, post;
  if (!init) {
    init = true;
    cudaDriverEntryPointQueryResult qr;
    cudaGetDriverEntryPoint("cuTensorMapEncodeTiled", (void**)&g_enc, cudaEnableDefault, &qr);
    void *xn, *h2, *o, *ut;
    cudaGetSymbolAddress(&xn, g_xn); cudaGetSymbolAddress(&h2, g_h2); cudaGetSymbolAddress(&o, g_o); cudaGetSymbolAddress(&ut, g_ut);
    GemmParams b = {};
    mkmap(&b.mA[0], xn, S_, D_, 64, 128); mkmap(&b.mA[1], w1, S_, F_, 64, 64); mkmap(&b.mA[2], w2, F_, S_, 64, 64); mkmap(&b.mA[3], o, S_, HD_, 64, 128);
    mkmap(&b.mB[0], Wq, D_, HD_, 64, 32); mkmap(&b.mB[1], Wk, D_, HD_, 64, 32); mkmap(&b.mB[2], Wv, D_, HD_, 64, 32);
    mkmap(&b.mB[3], h2, S_, D_, 64, 32); mkmap(&b.mB[4], ut, F_, D_, 64, 32); mkmap(&b.mB[5], Wo, HD_, D_, 64, 32);
    b.x = x; b.b1 = b1; b.b2 = b2; b.out = (bf16*)d_out;
    pre = b; side = b; post = b; side.kid = 1; post.kid = 2;
    static uint16_t jl[1024]; int n = 0;
    for (int m = 0; m < 8; m++) for (int j = 0; j < 16; j++) { jl[n++] = mkjob(1, m, j); jl[n++] = mkjob(2, m, j); }
    schedule(pre, jl, n, 66);
    n = 0;
    for (int m = 0; m < 18; m++) for (int j = 0; j < 3; j++) jl[n++] = mkjob(3, m, j);
    int qn = 0;
    for (; qn < 34; qn++) jl[n++] = mkjob(0, qn >> 4, qn & 15);
    for (int m = 0; m < 8; m++) for (int j = 0; j < 3; j++) jl[n++] = mkjob(4, m, j);
    for (; qn < 128; qn++) jl[n++] = mkjob(0, qn >> 4, qn & 15);
    schedule(side, jl, n, 34);
    side.wait_at_end = 1;
    n = 0;
    for (int m = 0; m < 8; m++) for (int j = 0; j < 3; j++) jl[n++] = mkjob(5, m, j);
    schedule(post, jl, n, 24);
    cudaFuncSetAttribute(gemm_kernel, cudaFuncAttributeMaxDynamicSharedMemorySize, GEMM_SMEM);
    cudaFuncSetAttribute(chain_kernel, cudaFuncAttributeMaxDynamicSharedMemorySize, CHAIN_SMEM);
  }
  launch(ln_kernel, 256, 256, 0, 1, false, x);
  launch(gemm_kernel, 132, 384, GEMM_SMEM, 2, false, pre);
  launch(chain_kernel, 64, 256, CHAIN_SMEM, 8, false, mem0, Wq, Wk, Wv, Wo);
  launch(gemm_kernel, 68, 384, GEMM_SMEM, 2, true, side);
  launch(attn_kernel, 512, 128, 0, 1, false);
  launch(gemm_kernel, 48, 384, GEMM_SMEM, 2, false, post);
}
```

```cpp
#include <cuda_runtime.h>
#include <cuda_bf16.h>
#include <cuda.h>
#include <stdint.h>

typedef __nv_bfloat16 bf16;
constexpr int S_ = 2048, D_ = 576, HD_ = 4096, F_ = 4608, NSEG = 64;

__device__ bf16 g_xn[S_ * D_];
__device__ bf16 g_h2[S_ * D_];
__device__ bf16 g_q[S_ * HD_];
__device__ bf16 g_k[S_ * HD_];
__device__ bf16 g_v[S_ * HD_];
__device__ bf16 g_o[S_ * HD_];
__device__ bf16 g_km[NSEG * 8 * HD_];
__device__ bf16 g_vm[NSEG * 8 * HD_];
__device__ bf16 g_ut[F_ * D_];
__device__ float g_yb[S_ * D_];
__device__ float g_part[2 * 8 * 8 * 5 * 32 * 4];
__device__ unsigned int g_cnt[64];

#define PT(i)
#define PC(i)
__device__ __forceinline__ uint32_t smem_u32(const void* p) { return (uint32_t)__cvta_generic_to_shared(p); }
__device__ __forceinline__ void mbar_init(uint32_t b, uint32_t c) { asm volatile("mbarrier.init.shared::cta.b64 [%0], %1;" ::"r"(b), "r"(c)); }
__device__ __forceinline__ void mbar_expect(uint32_t b, uint32_t bytes) { asm volatile("mbarrier.arrive.expect_tx.shared::cta.b64 _, [%0], %1;" ::"r"(b), "r"(bytes) : "memory"); }
__device__ __forceinline__ void mbar_wait(uint32_t b, uint32_t parity) {
  uint32_t ok;
  do { asm volatile("{\n.reg .pred p;\nmbarrier.try_wait.parity.shared::cta.b64 p, [%1], %2;\nselp.u32 %0, 1, 0, p;\n}" : "=r"(ok) : "r"(b), "r"(parity) : "memory"); } while (!ok);
}
__device__ __forceinline__ void mbar_wait_cl(uint32_t b, uint32_t parity) {
  uint32_t ok;
  do { asm volatile("{\n.reg .pred p;\nmbarrier.try_wait.parity.shared::cta.b64 p, [%1], %2;\nselp.u32 %0, 1, 0, p;\n}" : "=r"(ok) : "r"(b), "r"(parity) : "memory"); } while (!ok);
}
__device__ __forceinline__ uint32_t mapa(uint32_t a, uint32_t r) { uint32_t o; asm("mapa.shared::cluster.u32 %0, %1, %2;" : "=r"(o) : "r"(a), "r"(r)); return o; }
__device__ __forceinline__ void mbar_arrive_remote(uint32_t remote_b) { asm volatile("mbarrier.arrive.shared::cluster.b64 _, [%0];" ::"r"(remote_b) : "memory"); }
__device__ __forceinline__ uint32_t cluster_rank() { uint32_t r; asm("mov.u32 %0, %%cluster_ctarank;" : "=r"(r)); return r; }
__device__ __forceinline__ void cluster_sync() { asm volatile("barrier.cluster.arrive.release.aligned;\nbarrier.cluster.wait.acquire.aligned;" ::: "memory"); }
__device__ __forceinline__ void tma2d(uint32_t dst, const CUtensorMap* m, int c0, int c1, uint32_t bar) {
  asm volatile("cp.async.bulk.tensor.2d.shared::cluster.global.mbarrier::complete_tx::bytes [%0], [%1, {%3, %4}], [%2];"
               ::"r"(dst), "l"(m), "r"(bar), "r"(c0), "r"(c1) : "memory");
}
__device__ __forceinline__ void tma2d_mc(uint32_t dst, const CUtensorMap* m, int c0, int c1, uint32_t bar, uint16_t mask) {
  asm volatile("cp.async.bulk.tensor.2d.shared::cluster.global.mbarrier::complete_tx::bytes.multicast::cluster [%0], [%1, {%3, %4}], [%2], %5;"
               ::"r"(dst), "l"(m), "r"(bar), "r"(c0), "r"(c1), "h"(mask) : "memory");
}
__device__ __forceinline__ uint32_t pack_bf16(float a, float b) { __nv_bfloat162 t = __floats2bfloat162_rn(a, b); return *(uint32_t*)&t; }
__device__ __forceinline__ float2 unpack_bf16(uint32_t u) { return __bfloat1622float2(*(__nv_bfloat162*)&u); }
__device__ __forceinline__ void mma16816(float (&c)[4], const uint32_t (&a)[4], uint32_t b0, uint32_t b1) {
  asm volatile("mma.sync.aligned.m16n8k16.row.col.f32.bf16.bf16.f32 {%0,%1,%2,%3},{%4,%5,%6,%7},{%8,%9},{%0,%1,%2,%3};"
               : "+f"(c[0]), "+f"(c[1]), "+f"(c[2]), "+f"(c[3]) : "r"(a[0]), "r"(a[1]), "r"(a[2]), "r"(a[3]), "r"(b0), "r"(b1));
}
__device__ __forceinline__ void ldsm4(uint32_t (&r)[4], uint32_t a) { asm volatile("ldmatrix.sync.aligned.m8n8.x4.shared.b16 {%0,%1,%2,%3},[%4];" : "=r"(r[0]), "=r"(r[1]), "=r"(r[2]), "=r"(r[3]) : "r"(a) : "memory"); }
__device__ __forceinline__ void ldsm4t(uint32_t (&r)[4], uint32_t a) { asm volatile("ldmatrix.sync.aligned.m8n8.x4.trans.shared.b16 {%0,%1,%2,%3},[%4];" : "=r"(r[0]), "=r"(r[1]), "=r"(r[2]), "=r"(r[3]) : "r"(a) : "memory"); }
__device__ __forceinline__ uint32_t movm(uint32_t a) { uint32_t o; asm volatile("movmatrix.sync.aligned.m8n8.trans.b16 %0, %1;" : "=r"(o) : "r"(a)); return o; }
__device__ __forceinline__ void cp16(uint32_t dst, const void* src) { asm volatile("cp.async.cg.shared.global [%0], [%1], 16;" ::"r"(dst), "l"(src) : "memory"); }
__device__ __forceinline__ void pdl_wait() { asm volatile("griddepcontrol.wait;" ::: "memory"); }
__device__ __forceinline__ void pdl_launch() { asm volatile("griddepcontrol.launch_dependents;" ::: "memory"); }

__global__ void __launch_bounds__(256) ln_kernel(const bf16* __restrict__ x) {
  int row = blockIdx.x * 8 + (threadIdx.x >> 5), lane = threadIdx.x & 31;
  if (threadIdx.x == 0 && blockIdx.x == 0) { g_cnt[0] = 0; PT(0); }
  for (int i = blockIdx.x * 256 + threadIdx.x; i < 2 * 64 * 640; i += 256 * 256) g_part[i] = 0.f;
  const uint32_t* xr = (const uint32_t*)(x + (size_t)row * D_);
  float v[18]; float s = 0.f;
#pragma unroll
  for (int i = 0; i < 9; i++) { float2 f = unpack_bf16(xr[lane + 32 * i]); v[2 * i] = f.x; v[2 * i + 1] = f.y; s += f.x + f.y; }
#pragma unroll
  for (int pass = 0; pass < 2; pass++) {
#pragma unroll
    for (int o = 16; o; o >>= 1) s += __shfl_xor_sync(~0u, s, o);
    float m = s * (1.f / D_), q = 0.f;
#pragma unroll
    for (int i = 0; i < 18; i++) { v[i] -= m; q += v[i] * v[i]; }
#pragma unroll
    for (int o = 16; o; o >>= 1) q += __shfl_xor_sync(~0u, q, o);
    float r = 1.f / sqrtf(q * (1.f / D_) + 1e-5f);
    uint32_t* dst = (uint32_t*)((pass == 0 ? g_xn : g_h2) + (size_t)row * D_);
    s = 0.f;
#pragma unroll
    for (int i = 0; i < 9; i++) {
      uint32_t p = pack_bf16(v[2 * i] * r, v[2 * i + 1] * r);
      dst[lane + 32 * i] = p;
      float2 f = unpack_bf16(p); v[2 * i] = f.x; v[2 * i + 1] = f.y; s += f.x + f.y;
    }
  }
}

template<int TA> __device__ __forceinline__ void wgmma_n256(float (&d)[128], uint64_t da, uint64_t db, int sc) {
  asm volatile("{\n.reg .pred p;\nsetp.ne.b32 p, %130, 0;\n"
    "wgmma.mma_async.sync.aligned.m64n256k16.f32.bf16.bf16 {%0, %1, %2, %3, %4, %5, %6, %7, %8, %9, %10, %11, %12, %13, %14, %15, %16, %17, %18, %19, %20, %21, %22, %23, %24, %25, %26, %27, %28, %29, %30, %31, %32, %33, %34, %35, %36, %37, %38, %39, %40, %41, %42, %43, %44, %45, %46, %47, %48, %49, %50, %51, %52, %53, %54, %55, %56, %57, %58, %59, %60, %61, %62, %63, %64, %65, %66, %67, %68, %69, %70, %71, %72, %73, %74, %75, %76, %77, %78, %79, %80, %81, %82, %83, %84, %85, %86, %87, %88, %89, %90, %91, %92, %93, %94, %95, %96, %97, %98, %99, %100, %101, %102, %103, %104, %105, %106, %107, %108, %109, %110, %111, %112, %113, %114, %115, %116, %117, %118, %119, %120, %121, %122, %123, %124, %125, %126, %127}, %128, %129, p, 1, 1, %131, 1;\n}\n"
    : "+f"(d[0]), "+f"(d[1]), "+f"(d[2]), "+f"(d[3]), "+f"(d[4]), "+f"(d[5]), "+f"(d[6]), "+f"(d[7]), "+f"(d[8]), "+f"(d[9]), "+f"(d[10]), "+f"(d[11]), "+f"(d[12]), "+f"(d[13]), "+f"(d[14]), "+f"(d[15]), "+f"(d[16]), "+f"(d[17]), "+f"(d[18]), "+f"(d[19]), "+f"(d[20]), "+f"(d[21]), "+f"(d[22]), "+f"(d[23]), "+f"(d[24]), "+f"(d[25]), "+f"(d[26]), "+f"(d[27]), "+f"(d[28]), "+f"(d[29]), "+f"(d[30]), "+f"(d[31]), "+f"(d[32]), "+f"(d[33]), "+f"(d[34]), "+f"(d[35]), "+f"(d[36]), "+f"(d[37]), "+f"(d[38]), "+f"(d[39]), "+f"(d[40]), "+f"(d[41]), "+f"(d[42]), "+f"(d[43]), "+f"(d[44]), "+f"(d[45]), "+f"(d[46]), "+f"(d[47]), "+f"(d[48]), "+f"(d[49]), "+f"(d[50]), "+f"(d[51]), "+f"(d[52]), "+f"(d[53]), "+f"(d[54]), "+f"(d[55]), "+f"(d[56]), "+f"(d[57]), "+f"(d[58]), "+f"(d[59]), "+f"(d[60]), "+f"(d[61]), "+f"(d[62]), "+f"(d[63]), "+f"(d[64]), "+f"(d[65]), "+f"(d[66]), "+f"(d[67]), "+f"(d[68]), "+f"(d[69]), "+f"(d[70]), "+f"(d[71]), "+f"(d[72]), "+f"(d[73]), "+f"(d[74]), "+f"(d[75]), "+f"(d[76]), "+f"(d[77]), "+f"(d[78]), "+f"(d[79]), "+f"(d[80]), "+f"(d[81]), "+f"(d[82]), "+f"(d[83]), "+f"(d[84]), "+f"(d[85]), "+f"(d[86]), "+f"(d[87]), "+f"(d[88]), "+f"(d[89]), "+f"(d[90]), "+f"(d[91]), "+f"(d[92]), "+f"(d[93]), "+f"(d[94]), "+f"(d[95]), "+f"(d[96]), "+f"(d[97]), "+f"(d[98]), "+f"(d[99]), "+f"(d[100]), "+f"(d[101]), "+f"(d[102]), "+f"(d[103]), "+f"(d[104]), "+f"(d[105]), "+f"(d[106]), "+f"(d[107]), "+f"(d[108]), "+f"(d[109]), "+f"(d[110]), "+f"(d[111]), "+f"(d[112]), "+f"(d[113]), "+f"(d[114]), "+f"(d[115]), "+f"(d[116]), "+f"(d[117]), "+f"(d[118]), "+f"(d[119]), "+f"(d[120]), "+f"(d[121]), "+f"(d[122]), "+f"(d[123]), "+f"(d[124]), "+f"(d[125]), "+f"(d[126]), "+f"(d[127])
    : "l"(da), "l"(db), "r"(sc), "n"(TA));
}

template<int TA> __device__ __forceinline__ void wgmma_n192(float (&d)[128], uint64_t da, uint64_t db, int sc) {
  asm volatile("{\n.reg .pred p;\nsetp.ne.b32 p, %98, 0;\n"
    "wgmma.mma_async.sync.aligned.m64n192k16.f32.bf16.bf16 {%0, %1, %2, %3, %4, %5, %6, %7, %8, %9, %10, %11, %12, %13, %14, %15, %16, %17, %18, %19, %20, %21, %22, %23, %24, %25, %26, %27, %28, %29, %30, %31, %32, %33, %34, %35, %36, %37, %38, %39, %40, %41, %42, %43, %44, %45, %46, %47, %48, %49, %50, %51, %52, %53, %54, %55, %56, %57, %58, %59, %60, %61, %62, %63, %64, %65, %66, %67, %68, %69, %70, %71, %72, %73, %74, %75, %76, %77, %78, %79, %80, %81, %82, %83, %84, %85, %86, %87, %88, %89, %90, %91, %92, %93, %94, %95}, %96, %97, p, 1, 1, %99, 1;\n}\n"
    : "+f"(d[0]), "+f"(d[1]), "+f"(d[2]), "+f"(d[3]), "+f"(d[4]), "+f"(d[5]), "+f"(d[6]), "+f"(d[7]), "+f"(d[8]), "+f"(d[9]), "+f"(d[10]), "+f"(d[11]), "+f"(d[12]), "+f"(d[13]), "+f"(d[14]), "+f"(d[15]), "+f"(d[16]), "+f"(d[17]), "+f"(d[18]), "+f"(d[19]), "+f"(d[20]), "+f"(d[21]), "+f"(d[22]), "+f"(d[23]), "+f"(d[24]), "+f"(d[25]), "+f"(d[26]), "+f"(d[27]), "+f"(d[28]), "+f"(d[29]), "+f"(d[30]), "+f"(d[31]), "+f"(d[32]), "+f"(d[33]), "+f"(d[34]), "+f"(d[35]), "+f"(d[36]), "+f"(d[37]), "+f"(d[38]), "+f"(d[39]), "+f"(d[40]), "+f"(d[41]), "+f"(d[42]), "+f"(d[43]), "+f"(d[44]), "+f"(d[45]), "+f"(d[46]), "+f"(d[47]), "+f"(d[48]), "+f"(d[49]), "+f"(d[50]), "+f"(d[51]), "+f"(d[52]), "+f"(d[53]), "+f"(d[54]), "+f"(d[55]), "+f"(d[56]), "+f"(d[57]), "+f"(d[58]), "+f"(d[59]), "+f"(d[60]), "+f"(d[61]), "+f"(d[62]), "+f"(d[63]), "+f"(d[64]), "+f"(d[65]), "+f"(d[66]), "+f"(d[67]), "+f"(d[68]), "+f"(d[69]), "+f"(d[70]), "+f"(d[71]), "+f"(d[72]), "+f"(d[73]), "+f"(d[74]), "+f"(d[75]), "+f"(d[76]), "+f"(d[77]), "+f"(d[78]), "+f"(d[79]), "+f"(d[80]), "+f"(d[81]), "+f"(d[82]), "+f"(d[83]), "+f"(d[84]), "+f"(d[85]), "+f"(d[86]), "+f"(d[87]), "+f"(d[88]), "+f"(d[89]), "+f"(d[90]), "+f"(d[91]), "+f"(d[92]), "+f"(d[93]), "+f"(d[94]), "+f"(d[95])
    : "l"(da), "l"(db), "r"(sc), "n"(TA));
}

struct GemmParams {
  CUtensorMap mA[4];
  CUtensorMap mB[6];
  const bf16* x; const bf16* b1; const bf16* b2; bf16* out;
  int stride, kid;
  int wait_at_end;
  uint16_t job[960];
};
constexpr int NSTAGE = 4, STAGE_BYTES = 49152;
constexpr int GEMM_SMEM = NSTAGE * STAGE_BYTES + 8 * 2048 + 256 + 1024;

__device__ __forceinline__ uint64_t mkdesc(uint32_t addr, uint32_t lbo, uint32_t sbo) {
  return (uint64_t)((addr & 0x3FFFF) >> 4) | ((uint64_t)(lbo >> 4) << 16) | ((uint64_t)(sbo >> 4) << 32) | (1ull << 62);
}
__device__ __forceinline__ float gelu_tanh(float u) {
  float z = 0.7978845608028654f * (u + 0.044715f * u * u * u);
  float e = __expf(2.f * z);
  float th = 1.f - __fdividef(2.f, e + 1.f);
  return 0.5f * u * (1.f + th);
}
template <int BN, int TA>
__device__ __forceinline__ void gemm_mainloop(float (&d)[128], int kiters, uint32_t sbase, uint32_t fullb, uint32_t emptyb_l, uint32_t emptyb_r,
                                              int wg, int& stage, uint32_t& phase, bool elect) {
  int prev = -1;
  for (int k = 0; k < kiters; k++) {
    mbar_wait(fullb + stage * 8, phase);
    uint32_t a = sbase + stage * STAGE_BYTES + wg * 8192, b = sbase + stage * STAGE_BYTES + 16384;
    asm volatile("wgmma.fence.sync.aligned;" ::: "memory");
#pragma unroll
    for (int kk = 0; kk < 4; kk++) {
      uint64_t da = TA ? mkdesc(a + kk * 2048, 8192, 1024) : mkdesc(a + kk * 32, 16, 1024);
      uint64_t db = mkdesc(b + kk * 2048, 8192, 1024);
      if constexpr (BN == 256) wgmma_n256<TA>(d, da, db, (k | kk) != 0); else wgmma_n192<TA>(d, da, db, (k | kk) != 0);
    }
    asm volatile("wgmma.commit_group.sync.aligned;" ::: "memory");
    asm volatile("wgmma.wait_group.sync.aligned 1;" ::: "memory");
    if (prev >= 0 && elect) { mbar_arrive_remote(emptyb_l + prev * 8); mbar_arrive_remote(emptyb_r + prev * 8); }
    prev = stage;
    if (++stage == NSTAGE) { stage = 0; phase ^= 1; }
  }
  asm volatile("wgmma.wait_group.sync.aligned 0;" ::: "memory");
  if (elect) { mbar_arrive_remote(emptyb_l + prev * 8); mbar_arrive_remote(emptyb_r + prev * 8); }
}
template <int BN, class F>
__device__ __forceinline__ void store_tile(const float (&d)[128], uint32_t stg, bf16* dst, int ld, int lane, F f) {
#pragma unroll
  for (int c = 0; c < BN / 64; c++) {
#pragma unroll
    for (int i = 0; i < 8; i += 2) {
      const int o = c * 32 + i * 4;
      uint32_t r0 = f(d[o], d[o + 1], 0, c * 64 + i * 8), r1 = f(d[o + 2], d[o + 3], 1, c * 64 + i * 8);
      uint32_t r2 = f(d[o + 4], d[o + 5], 0, c * 64 + i * 8 + 8), r3 = f(d[o + 6], d[o + 7], 1, c * 64 + i * 8 + 8);
      int m = lane >> 3, row = (m & 1) * 8 + (lane & 7), ch = (i + (m >> 1)) ^ (row & 7);
      asm volatile("stmatrix.sync.aligned.m8n8.x4.shared.b16 [%0], {%1,%2,%3,%4};" ::"r"(stg + row * 128 + ch * 16), "r"(r0), "r"(r1), "r"(r2), "r"(r3) : "memory");
    }
    __syncwarp();
#pragma unroll
    for (int j = 0; j < 4; j++) {
      int idx = lane + 32 * j, row = idx >> 3, ch = idx & 7;
      uint4 v;
      asm volatile("ld.shared.v4.u32 {%0,%1,%2,%3}, [%4];" : "=r"(v.x), "=r"(v.y), "=r"(v.z), "=r"(v.w) : "r"(stg + row * 128 + ((ch ^ (row & 7)) * 16)));
      *(uint4*)(dst + (size_t)row * ld + c * 64 + ch * 8) = v;
    }
    __syncwarp();
  }
}

__global__ void __launch_bounds__(384, 1) gemm_kernel(const __grid_constant__ GemmParams p) {
  extern __shared__ uint8_t smem_raw[];
  const uint32_t sbase = (smem_u32(smem_raw) + 1023) & ~1023u;
  const uint32_t stg0 = sbase + NSTAGE * STAGE_BYTES, fullb = stg0 + 8 * 2048, emptyb = fullb + 64;
  const uint32_t rank = cluster_rank();
  const int wg = __shfl_sync(~0u, (int)(threadIdx.x >> 7), 0), lane = threadIdx.x & 31;
  const int cl = blockIdx.x >> 1;
  if (threadIdx.x == 0) {
    for (int i = 0; i < NSTAGE; i++) { mbar_init(fullb + i * 8, 1); mbar_init(emptyb + i * 8, 4); }
    asm volatile("fence.mbarrier_init.release.cluster;" ::: "memory");
  }
  cluster_sync();
  if (blockIdx.x == 0 && threadIdx.x == 0) PT(1 + p.kid * 2);
  const uint16_t* jobs = p.job + cl * p.stride;
  if (wg == 0) {
    asm volatile("setmaxnreg.dec.sync.aligned.u32 40;");
    if (threadIdx.x == 0) {
      int stage = 0; uint32_t phase = 1;
      for (int j = 0; j < p.stride; j++) {
        uint32_t job = jobs[j];
        if (job == 0xFFFF) break;
        int type = job >> 12, m = (job >> 6) & 63, n = job & 63;
        int row0 = m * 256 + rank * 128;
        int bn = type < 3 ? 256 : 192;
        int kit = type < 3 ? 9 : (type == 3 ? 32 : (type == 4 ? 72 : 64));
        const CUtensorMap* ma = &p.mA[type < 3 ? 0 : type - 2];
        const CUtensorMap* mb = &p.mB[type];
        bool ta = (type == 3 || type == 4);
        if (type == 4) {
          uint32_t v;
          do { asm volatile("ld.acquire.gpu.global.u32 %0, [%1];" : "=r"(v) : "l"(&g_cnt[0]) : "memory"); if (v < 108) __nanosleep(100); } while (v < 108);
          asm volatile("fence.proxy.async;" ::: "memory");
        }
        for (int k = 0; k < kit; k++) {
          mbar_wait_cl(emptyb + stage * 8, phase);
          uint32_t fb = fullb + stage * 8, a = sbase + stage * STAGE_BYTES, b = a + 16384;
          mbar_expect(fb, 16384 + bn * 128);
          if (ta) { tma2d(a, ma, row0, k * 64, fb); tma2d(a + 8192, ma, row0 + 64, k * 64, fb); }
          else tma2d(a, ma, k * 64, row0, fb);
          for (int i = 0; i < bn / 64; i++) tma2d_mc(b + i * 8192 + rank * 4096, mb, n * bn + i * 64, k * 64 + rank * 32, fb, (uint16_t)3);
          if (++stage == NSTAGE) { stage = 0; phase ^= 1; }
        }
      }
    }
    __syncwarp();
    if (p.wait_at_end) pdl_wait();
    cluster_sync();
  } else {
    asm volatile("setmaxnreg.inc.sync.aligned.u32 232;");
    const int cw = wg - 1, warp = __shfl_sync(~0u, (int)(threadIdx.x >> 5) & 3, 0);
    const uint32_t eb_l = mapa(emptyb, rank), eb_r = mapa(emptyb, rank ^ 1);
    const uint32_t stg = stg0 + (cw * 4 + warp) * 2048;
    const bool elect = (threadIdx.x & 127) == 0;
    const int g = lane >> 2, t = lane & 3;
    int stage = 0; uint32_t phase = 0;
    float d[128];
    for (int j = 0; j < p.stride; j++) {
      uint32_t job = jobs[j];
      if (job == 0xFFFF) break;
      int type = job >> 12, m = (job >> 6) & 63, n = job & 63;
      int row0 = m * 256 + rank * 128 + cw * 64 + warp * 16;
      if (type < 3) {
        gemm_mainloop<256, 0>(d, 9, sbase, fullb, eb_l, eb_r, cw, stage, phase, elect);
        bf16* dst = (type == 0 ? g_q : (type == 1 ? g_k : g_v)) + (size_t)row0 * HD_ + n * 256;
        store_tile<256>(d, stg, dst, HD_, lane, [](float a, float b, int, int) { return pack_bf16(a, b); });
      } else if (type == 3) {
        gemm_mainloop<192, 1>(d, 32, sbase, fullb, eb_l, eb_r, cw, stage, phase, elect);
        float bb[2] = {__bfloat162float(p.b1[row0 + g]), __bfloat162float(p.b1[row0 + g + 8])};
        store_tile<192>(d, stg, g_ut + (size_t)row0 * D_ + n * 192, D_, lane,
                        [&](float a, float b, int h, int) { return pack_bf16(gelu_tanh(a + bb[h]), gelu_tanh(b + bb[h])); });
        __threadfence();
        asm volatile("fence.proxy.async;" ::: "memory");
        asm volatile("bar.sync %0, 256;" ::"r"(1) : "memory");
        if (threadIdx.x == 128) atomicAdd(&g_cnt[0], 1);
      } else if (type == 4) {
        gemm_mainloop<192, 1>(d, 72, sbase, fullb, eb_l, eb_r, cw, stage, phase, elect);
        float bb[2] = {__bfloat162float(p.b2[row0 + g]), __bfloat162float(p.b2[row0 + g + 8])};
#pragma unroll
        for (int i = 0; i < 24; i++)
#pragma unroll
          for (int h = 0; h < 2; h++) {
            size_t off = (size_t)(row0 + g + h * 8) * D_ + n * 192 + i * 8 + t * 2;
            float2 xv = unpack_bf16(*(const uint32_t*)(p.x + off));
            *(float2*)(g_yb + off) = make_float2(d[i * 4 + h * 2] + bb[h] + xv.x, d[i * 4 + h * 2 + 1] + bb[h] + xv.y);
          }
      } else {
        gemm_mainloop<192, 0>(d, 64, sbase, fullb, eb_l, eb_r, cw, stage, phase, elect);
        const float* yb = g_yb + (size_t)(row0 + g) * D_ + n * 192 + t * 2;
        store_tile<192>(d, stg, p.out + (size_t)row0 * D_ + n * 192, D_, lane,
                        [&](float a, float b, int h, int c) { float2 y = *(const float2*)(yb + h * 8 * D_ + c); return pack_bf16(a + y.x, b + y.y); });
      }
      if (blockIdx.x == 0 && threadIdx.x == 128) PT(2048 + p.kid * 64 + j);
    }
    if (blockIdx.x == 0 && threadIdx.x == 128) PT(2 + p.kid * 2);
    if (p.wait_at_end) pdl_wait();
    cluster_sync();
  }
}

__global__ void __launch_bounds__(128) attn_kernel() {
  __shared__ __align__(128) uint8_t sm[4][48 * 256];
  const int warp = threadIdx.x >> 5, lane = threadIdx.x & 31, g = lane >> 2, t = lane & 3;
  const int id = blockIdx.x * 4 + warp, seg = id >> 5, h = id & 31;
  const uint32_t sv = smem_u32(sm[warp]);
  if (blockIdx.x == 0 && threadIdx.x == 0) PT(9);
  const size_t tok0 = (size_t)seg * 32;
  for (int i = lane; i < 40 * 16; i += 32) {
    int r = i >> 4, c = i & 15;
    const bf16* src = (r < 8 ? g_vm + ((size_t)seg * 8 + r) * HD_ : g_v + (tok0 + r - 8) * HD_) + h * 128 + c * 8;
    cp16(sv + r * 256 + ((c ^ (r & 7)) * 16), src);
  }
  for (int i = lane; i < 8 * 16; i += 32) *(uint4*)(sm[warp] + 40 * 256 + i * 16) = make_uint4(0, 0, 0, 0);
  asm volatile("cp.async.commit_group;" ::: "memory");
  float s[2][5][4];
#pragma unroll
  for (int m = 0; m < 2; m++)
#pragma unroll
    for (int n = 0; n < 5; n++) { s[m][n][0] = s[m][n][1] = s[m][n][2] = s[m][n][3] = 0.f; }
#pragma unroll
  for (int j = 0; j < 4; j++) {
    uint4 qa[2][2], kb[5];
#pragma unroll
    for (int m = 0; m < 2; m++)
#pragma unroll
      for (int hh = 0; hh < 2; hh++) qa[m][hh] = *(const uint4*)(g_q + (tok0 + m * 16 + hh * 8 + g) * HD_ + h * 128 + j * 32 + t * 8);
#pragma unroll
    for (int n = 0; n < 5; n++)
      kb[n] = *(const uint4*)((n == 0 ? g_km + ((size_t)seg * 8 + g) * HD_ : g_k + (tok0 + (n - 1) * 8 + g) * HD_) + h * 128 + j * 32 + t * 8);
#pragma unroll
    for (int m = 0; m < 2; m++) {
      uint32_t a0[4] = {qa[m][0].x, qa[m][1].x, qa[m][0].y, qa[m][1].y}, a1[4] = {qa[m][0].z, qa[m][1].z, qa[m][0].w, qa[m][1].w};
#pragma unroll
      for (int n = 0; n < 5; n++) { mma16816(s[m][n], a0, kb[n].x, kb[n].y); mma16816(s[m][n], a1, kb[n].z, kb[n].w); }
    }
  }
  const float sc = 0.08838834764831845f * 1.4426950408889634f;
  uint32_t pa[2][3][4];
#pragma unroll
  for (int m = 0; m < 2; m++) {
    float inv[2];
#pragma unroll
    for (int hh = 0; hh < 2; hh++) {
      int qi = 8 + m * 16 + hh * 8 + g;
      float mx = -INFINITY;
#pragma unroll
      for (int n = 0; n < 5; n++)
#pragma unroll
        for (int e = 0; e < 2; e++) { float& z = s[m][n][hh * 2 + e]; z = (n * 8 + t * 2 + e <= qi) ? z * sc : -INFINITY; mx = fmaxf(mx, z); }
      mx = fmaxf(mx, __shfl_xor_sync(~0u, mx, 1)); mx = fmaxf(mx, __shfl_xor_sync(~0u, mx, 2));
      float sum = 0.f;
#pragma unroll
      for (int n = 0; n < 5; n++)
#pragma unroll
        for (int e = 0; e < 2; e++) { float& z = s[m][n][hh * 2 + e]; z = exp2f(z - mx); sum += z; }
      sum += __shfl_xor_sync(~0u, sum, 1); sum += __shfl_xor_sync(~0u, sum, 2);
      inv[hh] = 1.f / sum;
    }
#pragma unroll
    for (int kk = 0; kk < 3; kk++) {
      pa[m][kk][0] = pack_bf16(s[m][2 * kk][0] * inv[0], s[m][2 * kk][1] * inv[0]);
      pa[m][kk][1] = pack_bf16(s[m][2 * kk][2] * inv[1], s[m][2 * kk][3] * inv[1]);
      if (kk < 2) {
        pa[m][kk][2] = pack_bf16(s[m][2 * kk + 1][0] * inv[0], s[m][2 * kk + 1][1] * inv[0]);
        pa[m][kk][3] = pack_bf16(s[m][2 * kk + 1][2] * inv[1], s[m][2 * kk + 1][3] * inv[1]);
      } else { pa[m][kk][2] = 0; pa[m][kk][3] = 0; }
    }
  }
  asm volatile("cp.async.wait_group 0;" ::: "memory");
  __syncwarp();
  uint32_t ov[2][16][2];
#pragma unroll
  for (int np = 0; np < 8; np++) {
    float o[2][2][4] = {};
#pragma unroll
    for (int kk = 0; kk < 3; kk++) {
      uint32_t b[4];
      int mi = lane >> 3, r = kk * 16 + (mi & 1) * 8 + (lane & 7), c = np * 2 + (mi >> 1);
      ldsm4t(b, sv + r * 256 + ((c ^ (r & 7)) * 16));
#pragma unroll
      for (int m = 0; m < 2; m++) { mma16816(o[m][0], pa[m][kk], b[0], b[1]); mma16816(o[m][1], pa[m][kk], b[2], b[3]); }
    }
#pragma unroll
    for (int m = 0; m < 2; m++)
#pragma unroll
      for (int q = 0; q < 2; q++) { ov[m][np * 2 + q][0] = pack_bf16(o[m][q][0], o[m][q][1]); ov[m][np * 2 + q][1] = pack_bf16(o[m][q][2], o[m][q][3]); }
  }
  __syncwarp();
#pragma unroll
  for (int m = 0; m < 2; m++)
#pragma unroll
    for (int n = 0; n < 16; n++)
#pragma unroll
      for (int hh = 0; hh < 2; hh++) {
        int r = m * 16 + hh * 8 + g;
        *(uint32_t*)(sm[warp] + r * 256 + ((n ^ (r & 7)) * 16) + t * 4) = ov[m][n][hh];
      }
  __syncwarp();
#pragma unroll
  for (int i = 0; i < 16; i++) {
    int idx = lane + 32 * i, r = idx >> 4, c = idx & 15;
    *(uint4*)(g_o + (tok0 + r) * HD_ + h * 128 + c * 8) = *(const uint4*)(sm[warp] + r * 256 + ((c ^ (r & 7)) * 16));
  }
}
constexpr int CH_WV = 0;
constexpr int CH_MEM = CH_WV + 73728;
constexpr int CH_KB = CH_MEM + 9216;
constexpr int CH_VB = CH_KB + 12288;
constexpr int CH_WO = CH_VB + 12288;
constexpr int CH_Q = CH_WO + 81920;
constexpr int CH_R1 = CH_Q + 1024;
constexpr int CH_SC = CH_R1 + 4096;
constexpr int CH_OF = CH_SC + 3584;
constexpr int CH_R2 = CH_OF + 8192;
constexpr int CH_BAR = CH_R2 + 12288;
constexpr int CHAIN_SMEM = CH_BAR + 64 + 1024;
#define NREGT 1
__device__ __forceinline__ void st_async1(uint32_t a, uint32_t v, uint32_t bar) { asm volatile("st.async.weak.shared::cluster.mbarrier::complete_tx::bytes.b32 [%0], %1, [%2];" ::"r"(a), "r"(v), "r"(bar) : "memory"); }
__device__ __forceinline__ void st_async2(uint32_t a, uint32_t v0, uint32_t v1, uint32_t bar) { asm volatile("st.async.weak.shared::cluster.mbarrier::complete_tx::bytes.v2.b32 [%0], {%1, %2}, [%3];" ::"r"(a), "r"(v0), "r"(v1), "r"(bar) : "memory"); }
__device__ __forceinline__ uint4 lds128(uint32_t a) { uint4 v; asm volatile("ld.shared.v4.u32 {%0,%1,%2,%3}, [%4];" : "=r"(v.x), "=r"(v.y), "=r"(v.z), "=r"(v.w) : "r"(a) : "memory"); return v; }
__device__ __forceinline__ void sts128f(uint32_t a, const float (&c)[4]) { asm volatile("st.shared.v4.f32 [%0], {%1,%2,%3,%4};" ::"r"(a), "f"(c[0]), "f"(c[1]), "f"(c[2]), "f"(c[3]) : "memory"); }
__device__ __forceinline__ void sts32(uint32_t a, uint32_t v) { asm volatile("st.shared.u32 [%0], %1;" ::"r"(a), "r"(v) : "memory"); }
__device__ __forceinline__ void mbar_wait_b(uint32_t b, uint32_t parity) {
  uint32_t ok; int n = 0;
  do { asm volatile("{\n.reg .pred p;\nmbarrier.try_wait.parity.shared::cta.b64 p, [%1], %2;\nselp.u32 %0, 1, 0, p;\n}" : "=r"(ok) : "r"(b), "r"(parity) : "memory"); } while (!ok && ++n < (1 << 20));
}
__device__ __forceinline__ uint32_t mapa_v(uint32_t a, uint32_t r) { uint32_t o; asm volatile("mapa.shared::cluster.u32 %0, %1, %2;" : "=r"(o) : "r"(a), "r"(r)); return o; }
__device__ __forceinline__ uint32_t tid_v() { uint32_t o; asm volatile("mov.u32 %0, %%tid.x;" : "=r"(o)); return o; }
template <int ACC>
__device__ __forceinline__ void wg_rs(float (&d)[4], const uint32_t (&a)[4], uint32_t dlo) {
  uint64_t db = ((uint64_t)16 << 32) | dlo;
  asm volatile("{\n.reg .pred p;\nsetp.ne.b32 p, %9, 0;\nwgmma.mma_async.sync.aligned.m64n8k16.f32.bf16.bf16 {%0,%1,%2,%3}, {%4,%5,%6,%7}, %8, p, 1, 1, 0;\n}"
               : "+f"(d[0]), "+f"(d[1]), "+f"(d[2]), "+f"(d[3]) : "r"(a[0]), "r"(a[1]), "r"(a[2]), "r"(a[3]), "l"(db), "n"(ACC));
}
template <int N>
__device__ __forceinline__ void wg_wait(float (&d)[N][4]) {
  asm volatile("wgmma.commit_group.sync.aligned;\nwgmma.wait_group.sync.aligned 0;" ::: "memory");
#pragma unroll
  for (int i = 0; i < N; i++) asm volatile("" : "+f"(d[i][0]), "+f"(d[i][1]), "+f"(d[i][2]), "+f"(d[i][3]) :: "memory");
}
#define BAR_ALL() asm volatile("bar.sync 0, 256;" ::: "memory")

__global__ void __launch_bounds__(256, 1) chain_kernel(const bf16* __restrict__ mem0, const bf16* __restrict__ Wq, const bf16* __restrict__ Wk,
                                                       const bf16* __restrict__ Wv, const bf16* __restrict__ Wo) {
  extern __shared__ uint8_t smem_raw[];
  const uint32_t sb = (smem_u32(smem_raw) + 1023) & ~1023u;
  const int tid = threadIdx.x, warp = __shfl_sync(~0u, tid >> 5, 0), wgi = __shfl_sync(~0u, tid >> 7, 0), lane = tid & 31, g = lane >> 2, t = lane & 3;
  const uint32_t r = cluster_rank();
  const int c = blockIdx.x >> 3, h = 4 * c + (r >> 1), j0 = h * 128 + (r & 1) * 64;
  const uint32_t bm = sb + CH_BAR, bs = bm + 8, bo = bm + 16;
  pdl_launch();
  if (blockIdx.x == 0 && tid == 0) PT(7);
  if (tid == 0) { mbar_init(bm, 1); mbar_init(bs, 1); mbar_init(bo, 1); asm volatile("fence.mbarrier_init.release.cluster;" ::: "memory"); }
  const int mi = lane >> 3, l7 = lane & 7;
  for (int i = tid; i < 576 * 8; i += 256) {
    int row = i >> 3, ch = i & 7;
    cp16(sb + CH_WV + row * 128 + ((ch ^ (row & 7)) * 16), Wq + (size_t)row * HD_ + j0 + ch * 8);
    cp16(sb + CH_WO + row * 128 + ((ch ^ (row & 7)) * 16), Wk + (size_t)row * HD_ + j0 + ch * 8);
  }
  asm volatile("cp.async.commit_group;\ncp.async.wait_group 0;" ::: "memory");
  BAR_ALL();
  uint32_t w1[36][4];
#pragma unroll
  for (int i = 0; i < 36; i++) {
    int row = i * 16 + (mi >> 1) * 8 + l7, ch = ((warp & 3) * 2 + (mi & 1)) ^ (row & 7);
    ldsm4t(w1[i], sb + (wgi ? CH_WO : CH_WV) + row * 128 + ch * 16);
  }
  BAR_ALL();
  for (int i = tid; i < 512 * 10; i += 256) {
    int row = i / 10, ch = i - row * 10;
    cp16(sb + CH_WV + row * 176 + ch * 16, Wo + (size_t)(c * 512 + row) * D_ + (ch < 8 ? r * 64 + ch * 8 : 512 + (r >> 1) * 16 + (ch - 8) * 8));
  }
  asm volatile("cp.async.commit_group;\ncp.async.wait_group 0;" ::: "memory");
  BAR_ALL();
  const int kperm = 2 * ((mi >> 1) * 2 + (l7 >> 2)) + (l7 & 1) + 8 * ((l7 >> 1) & 1);
  for (int i = 0; i < 16; i++) {
    uint32_t a[4];
    ldsm4t(a, sb + CH_WV + ((wgi * 16 + i) * 16 + kperm) * 176 + ((warp & 3) * 2 + (mi & 1)) * 16);
    asm volatile("st.shared.v4.u32 [%0], {%1,%2,%3,%4};" ::"r"(sb + CH_WO + 8192 + (warp * 16 + i) * 512 + lane * 16), "r"(a[0]), "r"(a[1]), "r"(a[2]), "r"(a[3]) : "memory");
  }
  for (int u = warp; u < 16; u += 8) {
    uint32_t a[4];
    ldsm4t(a, sb + CH_WV + (((r & 1) * 16 + u) * 16 + kperm) * 176 + (8 + (mi & 1)) * 16);
    asm volatile("st.shared.v4.u32 [%0], {%1,%2,%3,%4};" ::"r"(sb + CH_WO + u * 512 + lane * 16), "r"(a[0]), "r"(a[1]), "r"(a[2]), "r"(a[3]) : "memory");
  }
  BAR_ALL();
  for (int i = tid; i < 576 * 8; i += 256) {
    int row = i >> 3, ch = i & 7;
    cp16(sb + CH_WV + row * 128 + ((ch ^ (row & 7)) * 16), Wv + (size_t)row * HD_ + j0 + ch * 8);
  }
  for (int i = tid; i < 8 * 72; i += 256) {
    int row = i / 72, ch = i - row * 72;
    cp16(sb + CH_MEM + ch * 128 + row * 16, mem0 + row * D_ + ch * 8);
  }
  for (int i = tid; i < 4 * 64; i += 256) {
    int b = i >> 6, o = i & 63;
    asm volatile("st.shared.v4.u32 [%0], {%1,%1,%1,%1};" ::"r"(sb + CH_KB + b * 6144 + 40 * 128 + o * 16), "r"(0) : "memory");
  }
  pdl_wait();
  auto prefetch_kv = [&](int s, int tid) {
#pragma unroll
    for (int i = 0; i < 2; i++) {
      int u = tid + i * 256, which = u >> 8, row = (u & 255) >> 3, ch = u & 7;
      const bf16* src = (which ? g_v : g_k) + (size_t)(s * 32 + row) * HD_ + j0 + ch * 8;
      cp16(sb + (which ? CH_VB : CH_KB) + (s & 1) * 6144 + (row + 8) * 128 + ((ch ^ (row & 7)) * 16), src);
    }
    asm volatile("cp.async.commit_group;" ::: "memory");
  };
  prefetch_kv(0, tid);
  asm volatile("cp.async.wait_group 0;" ::: "memory");
  asm volatile("fence.proxy.async.shared::cta;" ::: "memory");
  BAR_ALL();
  cluster_sync();
  const uint32_t dsb = ((sb & 0x3FFFF) >> 4) | (8u << 16);
  if (blockIdx.x == 0 && tid == 0) PT(10);
#define CP(i) if (blockIdx.x == 0 && lane == 0 && warp == ((i) == 5 ? 4 : 0)) PC(64 + s * 16 + (i))
  for (int s = 0; s < NSEG; s++) {
    const int tid = tid_v(), lane = tid & 31, g = lane >> 2, t = lane & 3, mi = lane >> 3, l7 = lane & 7;
    CP(0);
    const uint32_t par = s & 1, kb = sb + CH_KB + par * 6144, vb = sb + CH_VB + par * 6144;
    if (s > 0) mbar_wait_b(bm, par ^ 1);
    CP(1);
    if (tid == 0 && s < NSEG - 1) { mbar_expect(bs, 2560); mbar_expect(bo, 8192); mbar_expect(bm, 9216); }
    auto phase1 = [&]() {
      float pa[6][4];
      asm volatile("wgmma.fence.sync.aligned;" ::: "memory");
#pragma unroll
      for (int i = 0; i < 36; i++) { if (i < 6) wg_rs<0>(pa[i % 6], w1[i], dsb + ((CH_MEM + i * 256) >> 4)); else wg_rs<1>(pa[i % 6], w1[i], dsb + ((CH_MEM + i * 256) >> 4)); }
      if (s + 1 < NSEG) prefetch_kv(s + 1, tid);
      wg_wait(pa);
      CP(2);
      uint32_t b0 = movm(pack_bf16(((pa[0][0] + pa[1][0]) + (pa[2][0] + pa[3][0])) + (pa[4][0] + pa[5][0]), ((pa[0][1] + pa[1][1]) + (pa[2][1] + pa[3][1])) + (pa[4][1] + pa[5][1])));
      uint32_t b1 = movm(pack_bf16(((pa[0][2] + pa[1][2]) + (pa[2][2] + pa[3][2])) + (pa[4][2] + pa[5][2]), ((pa[0][3] + pa[1][3]) + (pa[2][3] + pa[3][3])) + (pa[4][3] + pa[5][3])));
      uint32_t dst = (wgi ? kb : sb + CH_Q) + g * 128 + t * 4;
      sts32(dst + ((((warp & 3) * 2) ^ g) * 16), b0); sts32(dst + ((((warp & 3) * 2 + 1) ^ g) * 16), b1);
      if (wgi) { uint32_t* gp = (uint32_t*)(g_km + ((size_t)s * 8 + g) * HD_ + j0 + (warp & 3) * 16 + t * 2); gp[0] = b0; gp[4] = b1; }
      asm volatile("cp.async.wait_group 1;" ::: "memory");
    };
    if (wgi == 0) {
      phase1();
      BAR_ALL();
      CP(4);
      float va[4][4];
      asm volatile("wgmma.fence.sync.aligned;" ::: "memory");
      const uint32_t dwa = (((sb + CH_WV) & 0x3FFFF) >> 4) | ((8192u >> 4) << 16);
#pragma unroll
      for (int ks = 0; ks < 36; ks++) {
        uint64_t da = ((uint64_t)(0x40000000u | (1024 >> 4)) << 32) | (dwa + ks * 128), db = ((uint64_t)16 << 32) | (dsb + ((CH_MEM + ks * 256) >> 4));
        if (ks < 4)
          asm volatile("{\n.reg .pred p;\nsetp.ne.b32 p, 0, 0;\nwgmma.mma_async.sync.aligned.m64n8k16.f32.bf16.bf16 {%0,%1,%2,%3}, %4, %5, p, 1, 1, 1, 0;\n}"
                       : "=f"(va[ks & 3][0]), "=f"(va[ks & 3][1]), "=f"(va[ks & 3][2]), "=f"(va[ks & 3][3]) : "l"(da), "l"(db));
        else
          asm volatile("{\n.reg .pred p;\nsetp.ne.b32 p, 1, 0;\nwgmma.mma_async.sync.aligned.m64n8k16.f32.bf16.bf16 {%0,%1,%2,%3}, %4, %5, p, 1, 1, 1, 0;\n}"
                       : "+f"(va[ks & 3][0]), "+f"(va[ks & 3][1]), "+f"(va[ks & 3][2]), "+f"(va[ks & 3][3]) : "l"(da), "l"(db));
      }
      wg_wait(va);
      CP(6);
      uint32_t b0 = movm(pack_bf16(va[0][0] + va[1][0] + va[2][0] + va[3][0], va[0][1] + va[1][1] + va[2][1] + va[3][1]));
      uint32_t b1 = movm(pack_bf16(va[0][2] + va[1][2] + va[2][2] + va[3][2], va[0][3] + va[1][3] + va[2][3] + va[3][3]));
      sts32(vb + g * 128 + t * 4 + (((warp * 2) ^ g) * 16), b0); sts32(vb + g * 128 + t * 4 + (((warp * 2 + 1) ^ g) * 16), b1);
      uint32_t* gp = (uint32_t*)(g_vm + ((size_t)s * 8 + g) * HD_ + j0 + warp * 16 + t * 2); gp[0] = b0; gp[4] = b1;
      if (s < NSEG - 1) {
        __syncwarp();
        uint32_t vt[3][4];
#pragma unroll
        for (int kk = 0; kk < 3; kk++) { int row = kk * 16 + (mi >> 1) * 8 + l7; ldsm4t(vt[kk], vb + row * 128 + (((warp * 2 + (mi & 1)) ^ l7) * 16)); }
        mbar_wait_b(bs, par);
        CP(7);
        float z[10]; float mx = -INFINITY;
        const float scl = 0.08838834764831845f * 1.4426950408889634f;
#pragma unroll
        for (int i = 0; i < 5; i++) {
          float2 u0, u1; uint32_t a = sb + CH_SC + (g * 56 + i * 8 + 2 * t) * 4;
          asm volatile("ld.shared.v2.f32 {%0,%1}, [%2];" : "=f"(u0.x), "=f"(u0.y) : "r"(a) : "memory");
          asm volatile("ld.shared.v2.f32 {%0,%1}, [%2];" : "=f"(u1.x), "=f"(u1.y) : "r"(a + 1792) : "memory");
          z[2 * i] = (u0.x + u1.x) * scl; z[2 * i + 1] = (u0.y + u1.y) * scl;
        }
        mx = fmaxf(fmaxf(fmaxf(z[0], z[1]), fmaxf(z[2], z[3])), fmaxf(fmaxf(fmaxf(z[4], z[5]), fmaxf(z[6], z[7])), fmaxf(z[8], z[9])));
        mx = fmaxf(mx, __shfl_xor_sync(~0u, mx, 1)); mx = fmaxf(mx, __shfl_xor_sync(~0u, mx, 2));
        uint32_t pb[5];
#pragma unroll
        for (int i = 0; i < 5; i++) pb[i] = pack_bf16(exp2f(z[2 * i] - mx), exp2f(z[2 * i + 1] - mx));
        const uint32_t ones[4] = {0x3F803F80u, 0x3F803F80u, 0x3F803F80u, 0x3F803F80u};
        float o0[4] = {}, o1[4] = {}, o2[4] = {}, s0[4] = {}, s1[4] = {}, s2[4] = {};
        mma16816(o0, vt[0], pb[0], pb[1]); mma16816(s0, ones, pb[0], pb[1]);
        mma16816(o1, vt[1], pb[2], pb[3]); mma16816(s1, ones, pb[2], pb[3]);
        mma16816(o2, vt[2], pb[4], 0u); mma16816(s2, ones, pb[4], 0u);
        const float i0 = __fdividef(1.f, s0[0] + s1[0] + s2[0]), i1 = __fdividef(1.f, s0[1] + s1[1] + s2[1]);
        uint32_t f0 = movm(pack_bf16((o0[0] + o1[0] + o2[0]) * i0, (o0[1] + o1[1] + o2[1]) * i1));
        uint32_t f1 = movm(pack_bf16((o0[2] + o1[2] + o2[2]) * i0, (o0[3] + o1[3] + o2[3]) * i1));
        const int ks = r * 4 + warp;
        const uint32_t off = CH_OF + ks * 256 + (t >> 1) * 128 + g * 16 + (t & 1) * 8;
        const uint32_t cl0 = mapa_v(sb, 0), clstep = mapa_v(sb, 1) - cl0;
#pragma unroll
        for (int d = 0; d < 8; d++) st_async2(cl0 + d * clstep + off, f0, f1, cl0 + d * clstep + CH_BAR + 16);
      }
    } else {
      phase1();
      BAR_ALL();
      if (warp < 7 && s < NSEG - 1) {
        const int mt = warp - 4;
        const uint32_t sc_l = mapa_v(sb + CH_SC + (r & 1) * 1792, r), sc_r = mapa_v(sb + CH_SC + (r & 1) * 1792, r ^ 1), bs_l = mapa_v(bs, r), bs_r = mapa_v(bs, r ^ 1);
        float sa[4][4] = {};
#pragma unroll
        for (int kp = 0; kp < 2; kp++) {
          uint32_t b[4], a0[4], a1[4];
          ldsm4(b, sb + CH_Q + l7 * 128 + (((kp * 4 + mi) ^ l7) * 16));
          int row = mt * 16 + (mi & 1) * 8 + l7;
          ldsm4(a0, kb + row * 128 + (((kp * 4 + (mi >> 1)) ^ l7) * 16));
          ldsm4(a1, kb + row * 128 + (((kp * 4 + 2 + (mi >> 1)) ^ l7) * 16));
          mma16816(sa[2 * kp], a0, b[0], b[1]); mma16816(sa[2 * kp + 1], a1, b[2], b[3]);
        }
#pragma unroll
        for (int e = 0; e < 4; e++) {
          uint32_t off = ((2 * t + (e & 1)) * 56 + mt * 16 + (e >> 1) * 8 + g) * 4, v = __float_as_uint((sa[0][e] + sa[1][e]) + (sa[2][e] + sa[3][e]));
          if (mt < 2 || e < 2) { st_async1(sc_r + off, v, bs_r); st_async1(sc_l + off, v, bs_l); }
        }
        CP(5);
      }
    }
    if (s == NSEG - 1) break;
    CP(8);
    uint32_t wo[16][4];
#pragma unroll
    for (int i = 0; i < 16; i++) { uint4 v = lds128(sb + CH_WO + 8192 + (warp * 16 + i) * 512 + lane * 16); wo[i][0] = v.x; wo[i][1] = v.y; wo[i][2] = v.z; wo[i][3] = v.w; }
    mbar_wait_b(bo, par);
    CP(9);
    const uint32_t tag = ((s >> 1) + 1) & 1;
    float* pbase = g_part + (size_t)par * 8 * 5120 + lane * 4;
    auto put = [&](int slot, const float (&a)[4]) {
      asm volatile("st.relaxed.gpu.global.v4.b32 [%0], {%1,%2,%3,%4};" ::"l"(pbase + c * 5120 + slot * 128), "r"((__float_as_uint(a[0]) & ~1u) | tag),
                   "r"((__float_as_uint(a[1]) & ~1u) | tag), "r"((__float_as_uint(a[2]) & ~1u) | tag), "r"((__float_as_uint(a[3]) & ~1u) | tag) : "memory");
    };
    {
      float acc[4][4];
      asm volatile("wgmma.fence.sync.aligned;" ::: "memory");
      const uint32_t dof = dsb + ((CH_OF >> 4) + wgi * 256);
#pragma unroll
      for (int i = 0; i < 16; i++) { if (i < 4) wg_rs<0>(acc[i & 3], wo[i], dof + i * 16); else wg_rs<1>(acc[i & 3], wo[i], dof + i * 16); }
      wg_wait(acc);
#pragma unroll
      for (int e = 0; e < 4; e++) acc[0][e] = (acc[0][e] + acc[1][e]) + (acc[2][e] + acc[3][e]);
      CP(10);
      const int w3 = warp & 3;
      if (wgi) {
        sts128f(sb + CH_R2 + w3 * 512 + lane * 16, acc[0]);
        asm volatile("bar.arrive %0, 64;" ::"r"(1 + w3) : "memory");
        if (w3 < 2) {
          float ex[2][4] = {};
#pragma unroll
          for (int i = 0; i < 8; i += 2) {
            uint32_t b[4]; ldsm4(b, sb + CH_OF + ((r & 1) * 16 + w3 * 8 + i) * 256 + mi * 128 + l7 * 16);
            uint4 v0 = lds128(sb + CH_WO + (w3 * 8 + i) * 512 + lane * 16), v1 = lds128(sb + CH_WO + (w3 * 8 + i + 1) * 512 + lane * 16);
            uint32_t a0[4] = {v0.x, v0.y, v0.z, v0.w}, a1[4] = {v1.x, v1.y, v1.z, v1.w};
            mma16816(ex[0], a0, b[0], b[1]); mma16816(ex[1], a1, b[2], b[3]);
          }
#pragma unroll
          for (int e = 0; e < 4; e++) ex[0][e] += ex[1][e];
          if (w3 == 1) { sts128f(sb + CH_R2 + 4 * 512 + lane * 16, ex[0]); asm volatile("bar.arrive 5, 64;" ::: "memory"); }
          else {
            asm volatile("bar.sync 5, 64;" ::: "memory");
            uint4 v = lds128(sb + CH_R2 + 4 * 512 + lane * 16);
            ex[0][0] += __uint_as_float(v.x); ex[0][1] += __uint_as_float(v.y); ex[0][2] += __uint_as_float(v.z); ex[0][3] += __uint_as_float(v.w);
            put(32 + r, ex[0]);
          }
        }
      } else {
        asm volatile("bar.sync %0, 64;" ::"r"(1 + w3) : "memory");
        uint4 v = lds128(sb + CH_R2 + w3 * 512 + lane * 16);
        acc[0][0] += __uint_as_float(v.x); acc[0][1] += __uint_as_float(v.y); acc[0][2] += __uint_as_float(v.z); acc[0][3] += __uint_as_float(v.w);
        put(r * 4 + w3, acc[0]);
      }
    }
    CP(11);
    if (warp < 4) {
      const float* pb = pbase + (r * 4 + warp) * 128;
      uint4 v[8]; int n = 0; bool ok;
      do {
        ok = true;
#pragma unroll
        for (int i = 0; i < 8; i++) asm volatile("ld.relaxed.gpu.global.v4.b32 {%0,%1,%2,%3}, [%4];" : "=r"(v[i].x), "=r"(v[i].y), "=r"(v[i].z), "=r"(v[i].w) : "l"(pb + i * 5120) : "memory");
#pragma unroll
        for (int i = 0; i < 8; i++) ok = ok && (((v[i].x & v[i].y & v[i].z & v[i].w & 1u) == tag) && (((v[i].x | v[i].y | v[i].z | v[i].w) & 1u) == tag));
      } while (!ok && ++n < (1 << 18));
      float m[4] = {};
#pragma unroll
      for (int i = 0; i < 8; i++) { m[0] += __uint_as_float(v[i].x); m[1] += __uint_as_float(v[i].y); m[2] += __uint_as_float(v[i].z); m[3] += __uint_as_float(v[i].w); }
      __syncwarp();
      CP(12);
      uint32_t b0 = movm(pack_bf16(m[0], m[1])), b1 = movm(pack_bf16(m[2], m[3]));
      const uint32_t off = CH_MEM + (r * 4 + warp) * 256 + g * 16 + t * 4;
      const uint32_t cl0 = mapa_v(sb, 0), clstep = mapa_v(sb, 1) - cl0;
#pragma unroll
      for (int d = 0; d < 8; d++) { st_async1(cl0 + d * clstep + off, b0, cl0 + d * clstep + CH_BAR); st_async1(cl0 + d * clstep + off + 128, b1, cl0 + d * clstep + CH_BAR); }
    } else if (warp == 6) {
      const float* pb = pbase - lane * 4 + (32 + (r & ~1u)) * 128 + lane * 4 + (r & 1) * 2;
      uint2 v[16]; int n = 0; bool ok;
      do {
        ok = true;
#pragma unroll
        for (int i = 0; i < 16; i++) asm volatile("ld.relaxed.gpu.global.v2.b32 {%0,%1}, [%2];" : "=r"(v[i].x), "=r"(v[i].y) : "l"(pb + (i >> 1) * 5120 + (i & 1) * 128) : "memory");
#pragma unroll
        for (int i = 0; i < 16; i++) ok = ok && ((v[i].x & v[i].y & 1u) == tag) && (((v[i].x | v[i].y) & 1u) == tag);
      } while (!ok && ++n < (1 << 18));
      float m0 = 0.f, m1 = 0.f;
#pragma unroll
      for (int i = 0; i < 16; i++) { m0 += __uint_as_float(v[i].x); m1 += __uint_as_float(v[i].y); }
      __syncwarp();
      uint32_t b0 = movm(pack_bf16(m0, m1));
      const uint32_t off = CH_MEM + (32 + (r >> 1)) * 256 + (r & 1) * 128 + g * 16 + t * 4;
      const uint32_t cl0 = mapa_v(sb, 0), clstep = mapa_v(sb, 1) - cl0;
#pragma unroll
      for (int d = 0; d < 8; d++) st_async1(cl0 + d * clstep + off, b0, cl0 + d * clstep + CH_BAR);
    }
  }
  if (blockIdx.x == 0 && tid == 0) PT(8);
  cluster_sync();
}
typedef CUresult (*EncodeFn)(CUtensorMap*, CUtensorMapDataType, cuuint32_t, void*, const cuuint64_t*, const cuuint64_t*, const cuuint32_t*, const cuuint32_t*,
                             CUtensorMapInterleave, CUtensorMapSwizzle, CUtensorMapL2promotion, CUtensorMapFloatOOBfill);
static EncodeFn g_enc;
static void mkmap(CUtensorMap* m, const void* ptr, int rows, int cols, int boxc, int boxr) {
  cuuint64_t dims[2] = {(cuuint64_t)cols, (cuuint64_t)rows}, strides[1] = {(cuuint64_t)cols * 2};
  cuuint32_t box[2] = {(cuuint32_t)boxc, (cuuint32_t)boxr}, es[2] = {1, 1};
  g_enc(m, CU_TENSOR_MAP_DATA_TYPE_BFLOAT16, 2, (void*)ptr, dims, strides, box, es, CU_TENSOR_MAP_INTERLEAVE_NONE, CU_TENSOR_MAP_SWIZZLE_128B,
        CU_TENSOR_MAP_L2_PROMOTION_L2_256B, CU_TENSOR_MAP_FLOAT_OOB_FILL_NONE);
}
static inline uint16_t mkjob(int type, int m, int n) { return (uint16_t)(type << 12 | m << 6 | n); }
static void schedule(GemmParams& p, const uint16_t* jobs, int nj, int ncl) {
  static const double cost[6] = {11.0, 11.0, 11.0, 26.5, 57.5, 51.5};
  double t[66] = {}; int cnt[66] = {};
  p.stride = 960 / ncl;
  for (int i = 0; i < 960; i++) p.job[i] = 0xFFFF;
  double g2_end = 0;
  for (int i = 0; i < nj; i++) {
    int b = 0;
    for (int c = 1; c < ncl; c++) if (t[c] < t[b] || (t[c] == t[b] && cnt[c] < cnt[b])) b = c;
    int ty = jobs[i] >> 12;
    if (ty == 4 && t[b] < g2_end) t[b] = g2_end;
    t[b] += cost[ty];
    if (ty == 3 && t[b] > g2_end) g2_end = t[b];
    p.job[b * p.stride + cnt[b]++] = jobs[i];
  }
}
template <class... A>
static void launch(void (*k)(A...), int grid, int block, int smem, int cluster, bool pdl, A... a) {
  cudaLaunchConfig_t c = {};
  c.gridDim = grid; c.blockDim = block; c.dynamicSmemBytes = smem; c.stream = cudaStreamPerThread;
  cudaLaunchAttribute at[2]; int n = 0;
  if (cluster > 1) { at[n].id = cudaLaunchAttributeClusterDimension; at[n].val.clusterDim.x = cluster; at[n].val.clusterDim.y = 1; at[n].val.clusterDim.z = 1; n++; }
  if (pdl) { at[n].id = cudaLaunchAttributeProgrammaticStreamSerialization; at[n].val.programmaticStreamSerializationAllowed = 1; n++; }
  c.attrs = at; c.numAttrs = n;
  cudaLaunchKernelEx(&c, k, a...);
}

extern "C" void kernel_launch(void* const* d_in, const int* in_sizes, int n_in, void* d_out, int out_size) {
  const bf16 *x = (const bf16*)d_in[0], *mem0 = (const bf16*)d_in[1], *Wq = (const bf16*)d_in[2], *Wk = (const bf16*)d_in[3], *Wv = (const bf16*)d_in[4],
             *Wo = (const bf16*)d_in[5], *w1 = (const bf16*)d_in[8], *b1 = (const bf16*)d_in[9], *w2 = (const bf16*)d_in[10], *b2 = (const bf16*)d_in[11];
  static bool init = false;
  static GemmParams pre, side, post;
  if (!init) {
    init = true;
    cudaDriverEntryPointQueryResult qr;
    cudaGetDriverEntryPoint("cuTensorMapEncodeTiled", (void**)&g_enc, cudaEnableDefault, &qr);
    void *xn, *h2, *o, *ut;
    cudaGetSymbolAddress(&xn, g_xn); cudaGetSymbolAddress(&h2, g_h2); cudaGetSymbolAddress(&o, g_o); cudaGetSymbolAddress(&ut, g_ut);
    GemmParams b = {};
    mkmap(&b.mA[0], xn, S_, D_, 64, 128); mkmap(&b.mA[1], w1, S_, F_, 64, 64); mkmap(&b.mA[2], w2, F_, S_, 64, 64); mkmap(&b.mA[3], o, S_, HD_, 64, 128);
    mkmap(&b.mB[0], Wq, D_, HD_, 64, 32); mkmap(&b.mB[1], Wk, D_, HD_, 64, 32); mkmap(&b.mB[2], Wv, D_, HD_, 64, 32);
    mkmap(&b.mB[3], h2, S_, D_, 64, 32); mkmap(&b.mB[4], ut, F_, D_, 64, 32); mkmap(&b.mB[5], Wo, HD_, D_, 64, 32);
    b.x = x; b.b1 = b1; b.b2 = b2; b.out = (bf16*)d_out;
    pre = b; side = b; post = b; side.kid = 1; post.kid = 2;
    static uint16_t jl[1024]; int n = 0;
    for (int m = 0; m < 8; m++) for (int j = 0; j < 16; j++) { jl[n++] = mkjob(1, m, j); jl[n++] = mkjob(2, m, j); }
    schedule(pre, jl, n, 66);
    n = 0;
    for (int m = 0; m < 18; m++) for (int j = 0; j < 3; j++) jl[n++] = mkjob(3, m, j);
    int qn = 0;
    for (; qn < 34; qn++) jl[n++] = mkjob(0, qn >> 4, qn & 15);
    for (int m = 0; m < 8; m++) for (int j = 0; j < 3; j++) jl[n++] = mkjob(4, m, j);
    for (; qn < 128; qn++) jl[n++] = mkjob(0, qn >> 4, qn & 15);
    schedule(side, jl, n, 34);
    side.wait_at_end = 1;
    n = 0;
    for (int m = 0; m < 8; m++) for (int j = 0; j < 3; j++) jl[n++] = mkjob(5, m, j);
    schedule(post, jl, n, 24);
    cudaFuncSetAttribute(gemm_kernel, cudaFuncAttributeMaxDynamicSharedMemorySize, GEMM_SMEM);
    cudaFuncSetAttribute(chain_kernel, cudaFuncAttributeMaxDynamicSharedMemorySize, CHAIN_SMEM);
  }
  launch(ln_kernel, 256, 256, 0, 1, false, x);
  launch(gemm_kernel, 132, 384, GEMM_SMEM, 2, false, pre);
  launch(chain_kernel, 64, 256, CHAIN_SMEM, 8, false, mem0, Wq, Wk, Wv, Wo);
  launch(gemm_kernel, 68, 384, GEMM_SMEM, 2, true, side);
  launch(attn_kernel, 512, 128, 0, 1, false);
  launch(gemm_kernel, 48, 384, GEMM_SMEM, 2, false, post);
}
```

```cpp
#include <cuda_runtime.h>
#include <cuda_bf16.h>
#include <cuda.h>
#include <stdint.h>

typedef __nv_bfloat16 bf16;
constexpr int S_ = 2048, D_ = 576, HD_ = 4096, F_ = 4608, NSEG = 64;

__device__ bf16 g_xn[S_ * D_];
__device__ bf16 g_h2[S_ * D_];
__device__ bf16 g_q[S_ * HD_];
__device__ bf16 g_k[S_ * HD_];
__device__ bf16 g_v[S_ * HD_];
__device__ bf16 g_o[S_ * HD_];
__device__ bf16 g_km[NSEG * 8 * HD_];
__device__ bf16 g_vm[NSEG * 8 * HD_];
__device__ bf16 g_ut[F_ * D_];
__device__ float g_yb[S_ * D_];
__device__ float g_part[2 * 8 * 8 * 5 * 32 * 4];
__device__ unsigned int g_cnt[64];

#define PT(i)
#define PC(i)
__device__ __forceinline__ uint32_t smem_u32(const void* p) { return (uint32_t)__cvta_generic_to_shared(p); }
__device__ __forceinline__ void mbar_init(uint32_t b, uint32_t c) { asm volatile("mbarrier.init.shared::cta.b64 [%0], %1;" ::"r"(b), "r"(c)); }
__device__ __forceinline__ void mbar_expect(uint32_t b, uint32_t bytes) { asm volatile("mbarrier.arrive.expect_tx.shared::cta.b64 _, [%0], %1;" ::"r"(b), "r"(bytes) : "memory"); }
__device__ __forceinline__ void mbar_wait(uint32_t b, uint32_t parity) {
  uint32_t ok;
  do { asm volatile("{\n.reg .pred p;\nmbarrier.try_wait.parity.shared::cta.b64 p, [%1], %2;\nselp.u32 %0, 1, 0, p;\n}" : "=r"(ok) : "r"(b), "r"(parity) : "memory"); } while (!ok);
}
__device__ __forceinline__ void mbar_wait_cl(uint32_t b, uint32_t parity) {
  uint32_t ok;
  do { asm volatile("{\n.reg .pred p;\nmbarrier.try_wait.parity.shared::cta.b64 p, [%1], %2;\nselp.u32 %0, 1, 0, p;\n}" : "=r"(ok) : "r"(b), "r"(parity) : "memory"); } while (!ok);
}
__device__ __forceinline__ uint32_t mapa(uint32_t a, uint32_t r) { uint32_t o; asm("mapa.shared::cluster.u32 %0, %1, %2;" : "=r"(o) : "r"(a), "r"(r)); return o; }
__device__ __forceinline__ void mbar_arrive_remote(uint32_t remote_b) { asm volatile("mbarrier.arrive.shared::cluster.b64 _, [%0];" ::"r"(remote_b) : "memory"); }
__device__ __forceinline__ uint32_t cluster_rank() { uint32_t r; asm("mov.u32 %0, %%cluster_ctarank;" : "=r"(r)); return r; }
__device__ __forceinline__ void cluster_sync() { asm volatile("barrier.cluster.arrive.release.aligned;\nbarrier.cluster.wait.acquire.aligned;" ::: "memory"); }
__device__ __forceinline__ void tma2d(uint32_t dst, const CUtensorMap* m, int c0, int c1, uint32_t bar) {
  asm volatile("cp.async.bulk.tensor.2d.shared::cluster.global.mbarrier::complete_tx::bytes [%0], [%1, {%3, %4}], [%2];"
               ::"r"(dst), "l"(m), "r"(bar), "r"(c0), "r"(c1) : "memory");
}
__device__ __forceinline__ void tma2d_mc(uint32_t dst, const CUtensorMap* m, int c0, int c1, uint32_t bar, uint16_t mask) {
  asm volatile("cp.async.bulk.tensor.2d.shared::cluster.global.mbarrier::complete_tx::bytes.multicast::cluster [%0], [%1, {%3, %4}], [%2], %5;"
               ::"r"(dst), "l"(m), "r"(bar), "r"(c0), "r"(c1), "h"(mask) : "memory");
}
__device__ __forceinline__ uint32_t pack_bf16(float a, float b) { __nv_bfloat162 t = __floats2bfloat162_rn(a, b); return *(uint32_t*)&t; }
__device__ __forceinline__ float2 unpack_bf16(uint32_t u) { return __bfloat1622float2(*(__nv_bfloat162*)&u); }
__device__ __forceinline__ void mma16816(float (&c)[4], const uint32_t (&a)[4], uint32_t b0, uint32_t b1) {
  asm volatile("mma.sync.aligned.m16n8k16.row.col.f32.bf16.bf16.f32 {%0,%1,%2,%3},{%4,%5,%6,%7},{%8,%9},{%0,%1,%2,%3};"
               : "+f"(c[0]), "+f"(c[1]), "+f"(c[2]), "+f"(c[3]) : "r"(a[0]), "r"(a[1]), "r"(a[2]), "r"(a[3]), "r"(b0), "r"(b1));
}
__device__ __forceinline__ void ldsm4(uint32_t (&r)[4], uint32_t a) { asm volatile("ldmatrix.sync.aligned.m8n8.x4.shared.b16 {%0,%1,%2,%3},[%4];" : "=r"(r[0]), "=r"(r[1]), "=r"(r[2]), "=r"(r[3]) : "r"(a) : "memory"); }
__device__ __forceinline__ void ldsm4t(uint32_t (&r)[4], uint32_t a) { asm volatile("ldmatrix.sync.aligned.m8n8.x4.trans.shared.b16 {%0,%1,%2,%3},[%4];" : "=r"(r[0]), "=r"(r[1]), "=r"(r[2]), "=r"(r[3]) : "r"(a) : "memory"); }
__device__ __forceinline__ uint32_t movm(uint32_t a) { uint32_t o; asm volatile("movmatrix.sync.aligned.m8n8.trans.b16 %0, %1;" : "=r"(o) : "r"(a)); return o; }
__device__ __forceinline__ void cp16(uint32_t dst, const void* src) { asm volatile("cp.async.cg.shared.global [%0], [%1], 16;" ::"r"(dst), "l"(src) : "memory"); }
__device__ __forceinline__ void pdl_wait() { asm volatile("griddepcontrol.wait;" ::: "memory"); }
__device__ __forceinline__ void pdl_launch() { asm volatile("griddepcontrol.launch_dependents;" ::: "memory"); }

__global__ void __launch_bounds__(256) ln_kernel(const bf16* __restrict__ x) {
  int row = blockIdx.x * 8 + (threadIdx.x >> 5), lane = threadIdx.x & 31;
  if (threadIdx.x == 0 && blockIdx.x == 0) { g_cnt[0] = 0; PT(0); }
  for (int i = blockIdx.x * 256 + threadIdx.x; i < 2 * 64 * 640; i += 256 * 256) g_part[i] = 0.f;
  const uint32_t* xr = (const uint32_t*)(x + (size_t)row * D_);
  float v[18]; float s = 0.f;
#pragma unroll
  for (int i = 0; i < 9; i++) { float2 f = unpack_bf16(xr[lane + 32 * i]); v[2 * i] = f.x; v[2 * i + 1] = f.y; s += f.x + f.y; }
#pragma unroll
  for (int pass = 0; pass < 2; pass++) {
#pragma unroll
    for (int o = 16; o; o >>= 1) s += __shfl_xor_sync(~0u, s, o);
    float m = s * (1.f / D_), q = 0.f;
#pragma unroll
    for (int i = 0; i < 18; i++) { v[i] -= m; q += v[i] * v[i]; }
#pragma unroll
    for (int o = 16; o; o >>= 1) q += __shfl_xor_sync(~0u, q, o);
    float r = 1.f / sqrtf(q * (1.f / D_) + 1e-5f);
    uint32_t* dst = (uint32_t*)((pass == 0 ? g_xn : g_h2) + (size_t)row * D_);
    s = 0.f;
#pragma unroll
    for (int i = 0; i < 9; i++) {
      uint32_t p = pack_bf16(v[2 * i] * r, v[2 * i + 1] * r);
      dst[lane + 32 * i] = p;
      float2 f = unpack_bf16(p); v[2 * i] = f.x; v[2 * i + 1] = f.y; s += f.x + f.y;
    }
  }
}

template<int TA> __device__ __forceinline__ void wgmma_n256(float (&d)[128], uint64_t da, uint64_t db, int sc) {
  asm volatile("{\n.reg .pred p;\nsetp.ne.b32 p, %130, 0;\n"
    "wgmma.mma_async.sync.aligned.m64n256k16.f32.bf16.bf16 {%0, %1, %2, %3, %4, %5, %6, %7, %8, %9, %10, %11, %12, %13, %14, %15, %16, %17, %18, %19, %20, %21, %22, %23, %24, %25, %26, %27, %28, %29, %30, %31, %32, %33, %34, %35, %36, %37, %38, %39, %40, %41, %42, %43, %44, %45, %46, %47, %48, %49, %50, %51, %52, %53, %54, %55, %56, %57, %58, %59, %60, %61, %62, %63, %64, %65, %66, %67, %68, %69, %70, %71, %72, %73, %74, %75, %76, %77, %78, %79, %80, %81, %82, %83, %84, %85, %86, %87, %88, %89, %90, %91, %92, %93, %94, %95, %96, %97, %98, %99, %100, %101, %102, %103, %104, %105, %106, %107, %108, %109, %110, %111, %112, %113, %114, %115, %116, %117, %118, %119, %120, %121, %122, %123, %124, %125, %126, %127}, %128, %129, p, 1, 1, %131, 1;\n}\n"
    : "+f"(d[0]), "+f"(d[1]), "+f"(d[2]), "+f"(d[3]), "+f"(d[4]), "+f"(d[5]), "+f"(d[6]), "+f"(d[7]), "+f"(d[8]), "+f"(d[9]), "+f"(d[10]), "+f"(d[11]), "+f"(d[12]), "+f"(d[13]), "+f"(d[14]), "+f"(d[15]), "+f"(d[16]), "+f"(d[17]), "+f"(d[18]), "+f"(d[19]), "+f"(d[20]), "+f"(d[21]), "+f"(d[22]), "+f"(d[23]), "+f"(d[24]), "+f"(d[25]), "+f"(d[26]), "+f"(d[27]), "+f"(d[28]), "+f"(d[29]), "+f"(d[30]), "+f"(d[31]), "+f"(d[32]), "+f"(d[33]), "+f"(d[34]), "+f"(d[35]), "+f"(d[36]), "+f"(d[37]), "+f"(d[38]), "+f"(d[39]), "+f"(d[40]), "+f"(d[41]), "+f"(d[42]), "+f"(d[43]), "+f"(d[44]), "+f"(d[45]), "+f"(d[46]), "+f"(d[47]), "+f"(d[48]), "+f"(d[49]), "+f"(d[50]), "+f"(d[51]), "+f"(d[52]), "+f"(d[53]), "+f"(d[54]), "+f"(d[55]), "+f"(d[56]), "+f"(d[57]), "+f"(d[58]), "+f"(d[59]), "+f"(d[60]), "+f"(d[61]), "+f"(d[62]), "+f"(d[63]), "+f"(d[64]), "+f"(d[65]), "+f"(d[66]), "+f"(d[67]), "+f"(d[68]), "+f"(d[69]), "+f"(d[70]), "+f"(d[71]), "+f"(d[72]), "+f"(d[73]), "+f"(d[74]), "+f"(d[75]), "+f"(d[76]), "+f"(d[77]), "+f"(d[78]), "+f"(d[79]), "+f"(d[80]), "+f"(d[81]), "+f"(d[82]), "+f"(d[83]), "+f"(d[84]), "+f"(d[85]), "+f"(d[86]), "+f"(d[87]), "+f"(d[88]), "+f"(d[89]), "+f"(d[90]), "+f"(d[91]), "+f"(d[92]), "+f"(d[93]), "+f"(d[94]), "+f"(d[95]), "+f"(d[96]), "+f"(d[97]), "+f"(d[98]), "+f"(d[99]), "+f"(d[100]), "+f"(d[101]), "+f"(d[102]), "+f"(d[103]), "+f"(d[104]), "+f"(d[105]), "+f"(d[106]), "+f"(d[107]), "+f"(d[108]), "+f"(d[109]), "+f"(d[110]), "+f"(d[111]), "+f"(d[112]), "+f"(d[113]), "+f"(d[114]), "+f"(d[115]), "+f"(d[116]), "+f"(d[117]), "+f"(d[118]), "+f"(d[119]), "+f"(d[120]), "+f"(d[121]), "+f"(d[122]), "+f"(d[123]), "+f"(d[124]), "+f"(d[125]), "+f"(d[126]), "+f"(d[127])
    : "l"(da), "l"(db), "r"(sc), "n"(TA));
}

template<int TA> __device__ __forceinline__ void wgmma_n192(float (&d)[128], uint64_t da, uint64_t db, int sc) {
  asm volatile("{\n.reg .pred p;\nsetp.ne.b32 p, %98, 0;\n"
    "wgmma.mma_async.sync.aligned.m64n192k16.f32.bf16.bf16 {%0, %1, %2, %3, %4, %5, %6, %7, %8, %9, %10, %11, %12, %13, %14, %15, %16, %17, %18, %19, %20, %21, %22, %23, %24, %25, %26, %27, %28, %29, %30, %31, %32, %33, %34, %35, %36, %37, %38, %39, %40, %41, %42, %43, %44, %45, %46, %47, %48, %49, %50, %51, %52, %53, %54, %55, %56, %57, %58, %59, %60, %61, %62, %63, %64, %65, %66, %67, %68, %69, %70, %71, %72, %73, %74, %75, %76, %77, %78, %79, %80, %81, %82, %83, %84, %85, %86, %87, %88, %89, %90, %91, %92, %93, %94, %95}, %96, %97, p, 1, 1, %99, 1;\n}\n"
    : "+f"(d[0]), "+f"(d[1]), "+f"(d[2]), "+f"(d[3]), "+f"(d[4]), "+f"(d[5]), "+f"(d[6]), "+f"(d[7]), "+f"(d[8]), "+f"(d[9]), "+f"(d[10]), "+f"(d[11]), "+f"(d[12]), "+f"(d[13]), "+f"(d[14]), "+f"(d[15]), "+f"(d[16]), "+f"(d[17]), "+f"(d[18]), "+f"(d[19]), "+f"(d[20]), "+f"(d[21]), "+f"(d[22]), "+f"(d[23]), "+f"(d[24]), "+f"(d[25]), "+f"(d[26]), "+f"(d[27]), "+f"(d[28]), "+f"(d[29]), "+f"(d[30]), "+f"(d[31]), "+f"(d[32]), "+f"(d[33]), "+f"(d[34]), "+f"(d[35]), "+f"(d[36]), "+f"(d[37]), "+f"(d[38]), "+f"(d[39]), "+f"(d[40]), "+f"(d[41]), "+f"(d[42]), "+f"(d[43]), "+f"(d[44]), "+f"(d[45]), "+f"(d[46]), "+f"(d[47]), "+f"(d[48]), "+f"(d[49]), "+f"(d[50]), "+f"(d[51]), "+f"(d[52]), "+f"(d[53]), "+f"(d[54]), "+f"(d[55]), "+f"(d[56]), "+f"(d[57]), "+f"(d[58]), "+f"(d[59]), "+f"(d[60]), "+f"(d[61]), "+f"(d[62]), "+f"(d[63]), "+f"(d[64]), "+f"(d[65]), "+f"(d[66]), "+f"(d[67]), "+f"(d[68]), "+f"(d[69]), "+f"(d[70]), "+f"(d[71]), "+f"(d[72]), "+f"(d[73]), "+f"(d[74]), "+f"(d[75]), "+f"(d[76]), "+f"(d[77]), "+f"(d[78]), "+f"(d[79]), "+f"(d[80]), "+f"(d[81]), "+f"(d[82]), "+f"(d[83]), "+f"(d[84]), "+f"(d[85]), "+f"(d[86]), "+f"(d[87]), "+f"(d[88]), "+f"(d[89]), "+f"(d[90]), "+f"(d[91]), "+f"(d[92]), "+f"(d[93]), "+f"(d[94]), "+f"(d[95])
    : "l"(da), "l"(db), "r"(sc), "n"(TA));
}

struct GemmParams {
  CUtensorMap mA[4];
  CUtensorMap mB[6];
  const bf16* x; const bf16* b1; const bf16* b2; bf16* out;
  int stride, kid;
  int wait_at_end;
  uint16_t job[960];
};
constexpr int NSTAGE = 4, STAGE_BYTES = 49152;
constexpr int GEMM_SMEM = NSTAGE * STAGE_BYTES + 8 * 2048 + 256 + 1024;

__device__ __forceinline__ uint64_t mkdesc(uint32_t addr, uint32_t lbo, uint32_t sbo) {
  return (uint64_t)((addr & 0x3FFFF) >> 4) | ((uint64_t)(lbo >> 4) << 16) | ((uint64_t)(sbo >> 4) << 32) | (1ull << 62);
}
__device__ __forceinline__ float gelu_tanh(float u) {
  float z = 0.7978845608028654f * (u + 0.044715f * u * u * u);
  float e = __expf(2.f * z);
  float th = 1.f - __fdividef(2.f, e + 1.f);
  return 0.5f * u * (1.f + th);
}
template <int BN, int TA>
__device__ __forceinline__ void gemm_mainloop(float (&d)[128], int kiters, uint32_t sbase, uint32_t fullb, uint32_t emptyb_l, uint32_t emptyb_r,
                                              int wg, int& stage, uint32_t& phase, bool elect) {
  int prev = -1;
  for (int k = 0; k < kiters; k++) {
    mbar_wait(fullb + stage * 8, phase);
    uint32_t a = sbase + stage * STAGE_BYTES + wg * 8192, b = sbase + stage * STAGE_BYTES + 16384;
    asm volatile("wgmma.fence.sync.aligned;" ::: "memory");
#pragma unroll
    for (int kk = 0; kk < 4; kk++) {
      uint64_t da = TA ? mkdesc(a + kk * 2048, 8192, 1024) : mkdesc(a + kk * 32, 16, 1024);
      uint64_t db = mkdesc(b + kk * 2048, 8192, 1024);
      if constexpr (BN == 256) wgmma_n256<TA>(d, da, db, (k | kk) != 0); else wgmma_n192<TA>(d, da, db, (k | kk) != 0);
    }
    asm volatile("wgmma.commit_group.sync.aligned;" ::: "memory");
    asm volatile("wgmma.wait_group.sync.aligned 1;" ::: "memory");
    if (prev >= 0 && elect) { mbar_arrive_remote(emptyb_l + prev * 8); mbar_arrive_remote(emptyb_r + prev * 8); }
    prev = stage;
    if (++stage == NSTAGE) { stage = 0; phase ^= 1; }
  }
  asm volatile("wgmma.wait_group.sync.aligned 0;" ::: "memory");
  if (elect) { mbar_arrive_remote(emptyb_l + prev * 8); mbar_arrive_remote(emptyb_r + prev * 8); }
}
template <int BN, class F>
__device__ __forceinline__ void store_tile(const float (&d)[128], uint32_t stg, bf16* dst, int ld, int lane, F f) {
#pragma unroll
  for (int c = 0; c < BN / 64; c++) {
#pragma unroll
    for (int i = 0; i < 8; i += 2) {
      const int o = c * 32 + i * 4;
      uint32_t r0 = f(d[o], d[o + 1], 0, c * 64 + i * 8), r1 = f(d[o + 2], d[o + 3], 1, c * 64 + i * 8);
      uint32_t r2 = f(d[o + 4], d[o + 5], 0, c * 64 + i * 8 + 8), r3 = f(d[o + 6], d[o + 7], 1, c * 64 + i * 8 + 8);
      int m = lane >> 3, row = (m & 1) * 8 + (lane & 7), ch = (i + (m >> 1)) ^ (row & 7);
      asm volatile("stmatrix.sync.aligned.m8n8.x4.shared.b16 [%0], {%1,%2,%3,%4};" ::"r"(stg + row * 128 + ch * 16), "r"(r0), "r"(r1), "r"(r2), "r"(r3) : "memory");
    }
    __syncwarp();
#pragma unroll
    for (int j = 0; j < 4; j++) {
      int idx = lane + 32 * j, row = idx >> 3, ch = idx & 7;
      uint4 v;
      asm volatile("ld.shared.v4.u32 {%0,%1,%2,%3}, [%4];" : "=r"(v.x), "=r"(v.y), "=r"(v.z), "=r"(v.w) : "r"(stg + row * 128 + ((ch ^ (row & 7)) * 16)));
      *(uint4*)(dst + (size_t)row * ld + c * 64 + ch * 8) = v;
    }
    __syncwarp();
  }
}

__global__ void __launch_bounds__(384, 1) gemm_kernel(const __grid_constant__ GemmParams p) {
  extern __shared__ uint8_t smem_raw[];
  const uint32_t sbase = (smem_u32(smem_raw) + 1023) & ~1023u;
  const uint32_t stg0 = sbase + NSTAGE * STAGE_BYTES, fullb = stg0 + 8 * 2048, emptyb = fullb + 64;
  const uint32_t rank = cluster_rank();
  const int wg = __shfl_sync(~0u, (int)(threadIdx.x >> 7), 0), lane = threadIdx.x & 31;
  const int cl = blockIdx.x >> 1;
  if (threadIdx.x == 0) {
    for (int i = 0; i < NSTAGE; i++) { mbar_init(fullb + i * 8, 1); mbar_init(emptyb + i * 8, 4); }
    asm volatile("fence.mbarrier_init.release.cluster;" ::: "memory");
  }
  cluster_sync();
  if (blockIdx.x == 0 && threadIdx.x == 0) PT(1 + p.kid * 2);
  const uint16_t* jobs = p.job + cl * p.stride;
  if (wg == 0) {
    asm volatile("setmaxnreg.dec.sync.aligned.u32 40;");
    if (threadIdx.x == 0) {
      int stage = 0; uint32_t phase = 1;
      for (int j = 0; j < p.stride; j++) {
        uint32_t job = jobs[j];
        if (job == 0xFFFF) break;
        int type = job >> 12, m = (job >> 6) & 63, n = job & 63;
        int row0 = m * 256 + rank * 128;
        int bn = type < 3 ? 256 : 192;
        int kit = type < 3 ? 9 : (type == 3 ? 32 : (type == 4 ? 72 : 64));
        const CUtensorMap* ma = &p.mA[type < 3 ? 0 : type - 2];
        const CUtensorMap* mb = &p.mB[type];
        bool ta = (type == 3 || type == 4);
        if (type == 4) {
          uint32_t v;
          do { asm volatile("ld.acquire.gpu.global.u32 %0, [%1];" : "=r"(v) : "l"(&g_cnt[0]) : "memory"); if (v < 108) __nanosleep(100); } while (v < 108);
          asm volatile("fence.proxy.async;" ::: "memory");
        }
        for (int k = 0; k < kit; k++) {
          mbar_wait_cl(emptyb + stage * 8, phase);
          uint32_t fb = fullb + stage * 8, a = sbase + stage * STAGE_BYTES, b = a + 16384;
          mbar_expect(fb, 16384 + bn * 128);
          if (ta) { tma2d(a, ma, row0, k * 64, fb); tma2d(a + 8192, ma, row0 + 64, k * 64, fb); }
          else tma2d(a, ma, k * 64, row0, fb);
          for (int i = 0; i < bn / 64; i++) tma2d_mc(b + i * 8192 + rank * 4096, mb, n * bn + i * 64, k * 64 + rank * 32, fb, (uint16_t)3);
          if (++stage == NSTAGE) { stage = 0; phase ^= 1; }
        }
      }
    }
    __syncwarp();
    if (p.wait_at_end) pdl_wait();
    cluster_sync();
  } else {
    asm volatile("setmaxnreg.inc.sync.aligned.u32 232;");
    const int cw = wg - 1, warp = __shfl_sync(~0u, (int)(threadIdx.x >> 5) & 3, 0);
    const uint32_t eb_l = mapa(emptyb, rank), eb_r = mapa(emptyb, rank ^ 1);
    const uint32_t stg = stg0 + (cw * 4 + warp) * 2048;
    const bool elect = (threadIdx.x & 127) == 0;
    const int g = lane >> 2, t = lane & 3;
    int stage = 0; uint32_t phase = 0;
    float d[128];
    for (int j = 0; j < p.stride; j++) {
      uint32_t job = jobs[j];
      if (job == 0xFFFF) break;
      int type = job >> 12, m = (job >> 6) & 63, n = job & 63;
      int row0 = m * 256 + rank * 128 + cw * 64 + warp * 16;
      if (type < 3) {
        gemm_mainloop<256, 0>(d, 9, sbase, fullb, eb_l, eb_r, cw, stage, phase, elect);
        bf16* dst = (type == 0 ? g_q : (type == 1 ? g_k : g_v)) + (size_t)row0 * HD_ + n * 256;
        store_tile<256>(d, stg, dst, HD_, lane, [](float a, float b, int, int) { return pack_bf16(a, b); });
      } else if (type == 3) {
        gemm_mainloop<192, 1>(d, 32, sbase, fullb, eb_l, eb_r, cw, stage, phase, elect);
        float bb[2] = {__bfloat162float(p.b1[row0 + g]), __bfloat162float(p.b1[row0 + g + 8])};
        store_tile<192>(d, stg, g_ut + (size_t)row0 * D_ + n * 192, D_, lane,
                        [&](float a, float b, int h, int) { return pack_bf16(gelu_tanh(a + bb[h]), gelu_tanh(b + bb[h])); });
        __threadfence();
        asm volatile("fence.proxy.async;" ::: "memory");
        asm volatile("bar.sync %0, 256;" ::"r"(1) : "memory");
        if (threadIdx.x == 128) atomicAdd(&g_cnt[0], 1);
      } else if (type == 4) {
        gemm_mainloop<192, 1>(d, 72, sbase, fullb, eb_l, eb_r, cw, stage, phase, elect);
        float bb[2] = {__bfloat162float(p.b2[row0 + g]), __bfloat162float(p.b2[row0 + g + 8])};
#pragma unroll
        for (int i = 0; i < 24; i++)
#pragma unroll
          for (int h = 0; h < 2; h++) {
            size_t off = (size_t)(row0 + g + h * 8) * D_ + n * 192 + i * 8 + t * 2;
            float2 xv = unpack_bf16(*(const uint32_t*)(p.x + off));
            *(float2*)(g_yb + off) = make_float2(d[i * 4 + h * 2] + bb[h] + xv.x, d[i * 4 + h * 2 + 1] + bb[h] + xv.y);
          }
      } else {
        gemm_mainloop<192, 0>(d, 64, sbase, fullb, eb_l, eb_r, cw, stage, phase, elect);
        const float* yb = g_yb + (size_t)(row0 + g) * D_ + n * 192 + t * 2;
        store_tile<192>(d, stg, p.out + (size_t)row0 * D_ + n * 192, D_, lane,
                        [&](float a, float b, int h, int c) { float2 y = *(const float2*)(yb + h * 8 * D_ + c); return pack_bf16(a + y.x, b + y.y); });
      }
      if (blockIdx.x == 0 && threadIdx.x == 128) PT(2048 + p.kid * 64 + j);
    }
    if (blockIdx.x == 0 && threadIdx.x == 128) PT(2 + p.kid * 2);
    if (p.wait_at_end) pdl_wait();
    cluster_sync();
  }
}

__global__ void __launch_bounds__(128) attn_kernel() {
  __shared__ __align__(128) uint8_t sm[4][48 * 256];
  const int warp = threadIdx.x >> 5, lane = threadIdx.x & 31, g = lane >> 2, t = lane & 3;
  const int id = blockIdx.x * 4 + warp, seg = id >> 5, h = id & 31;
  const uint32_t sv = smem_u32(sm[warp]);
  if (blockIdx.x == 0 && threadIdx.x == 0) PT(9);
  const size_t tok0 = (size_t)seg * 32;
  for (int i = lane; i < 40 * 16; i += 32) {
    int r = i >> 4, c = i & 15;
    const bf16* src = (r < 8 ? g_vm + ((size_t)seg * 8 + r) * HD_ : g_v + (tok0 + r - 8) * HD_) + h * 128 + c * 8;
    cp16(sv + r * 256 + ((c ^ (r & 7)) * 16), src);
  }
  for (int i = lane; i < 8 * 16; i += 32) *(uint4*)(sm[warp] + 40 * 256 + i * 16) = make_uint4(0, 0, 0, 0);
  asm volatile("cp.async.commit_group;" ::: "memory");
  float s[2][5][4];
#pragma unroll
  for (int m = 0; m < 2; m++)
#pragma unroll
    for (int n = 0; n < 5; n++) { s[m][n][0] = s[m][n][1] = s[m][n][2] = s[m][n][3] = 0.f; }
#pragma unroll
  for (int j = 0; j < 4; j++) {
    uint4 qa[2][2], kb[5];
#pragma unroll
    for (int m = 0; m < 2; m++)
#pragma unroll
      for (int hh = 0; hh < 2; hh++) qa[m][hh] = *(const uint4*)(g_q + (tok0 + m * 16 + hh * 8 + g) * HD_ + h * 128 + j * 32 + t * 8);
#pragma unroll
    for (int n = 0; n < 5; n++)
      kb[n] = *(const uint4*)((n == 0 ? g_km + ((size_t)seg * 8 + g) * HD_ : g_k + (tok0 + (n - 1) * 8 + g) * HD_) + h * 128 + j * 32 + t * 8);
#pragma unroll
    for (int m = 0; m < 2; m++) {
      uint32_t a0[4] = {qa[m][0].x, qa[m][1].x, qa[m][0].y, qa[m][1].y}, a1[4] = {qa[m][0].z, qa[m][1].z, qa[m][0].w, qa[m][1].w};
#pragma unroll
      for (int n = 0; n < 5; n++) { mma16816(s[m][n], a0, kb[n].x, kb[n].y); mma16816(s[m][n], a1, kb[n].z, kb[n].w); }
    }
  }
  const float sc = 0.08838834764831845f * 1.4426950408889634f;
  uint32_t pa[2][3][4];
#pragma unroll
  for (int m = 0; m < 2; m++) {
    float inv[2];
#pragma unroll
    for (int hh = 0; hh < 2; hh++) {
      int qi = 8 + m * 16 + hh * 8 + g;
      float mx = -INFINITY;
#pragma unroll
      for (int n = 0; n < 5; n++)
#pragma unroll
        for (int e = 0; e < 2; e++) { float& z = s[m][n][hh * 2 + e]; z = (n * 8 + t * 2 + e <= qi) ? z * sc : -INFINITY; mx = fmaxf(mx, z); }
      mx = fmaxf(mx, __shfl_xor_sync(~0u, mx, 1)); mx = fmaxf(mx, __shfl_xor_sync(~0u, mx, 2));
      float sum = 0.f;
#pragma unroll
      for (int n = 0; n < 5; n++)
#pragma unroll
        for (int e = 0; e < 2; e++) { float& z = s[m][n][hh * 2 + e]; z = exp2f(z - mx); sum += z; }
      sum += __shfl_xor_sync(~0u, sum, 1); sum += __shfl_xor_sync(~0u, sum, 2);
      inv[hh] = 1.f / sum;
    }
#pragma unroll
    for (int kk = 0; kk < 3; kk++) {
      pa[m][kk][0] = pack_bf16(s[m][2 * kk][0] * inv[0], s[m][2 * kk][1] * inv[0]);
      pa[m][kk][1] = pack_bf16(s[m][2 * kk][2] * inv[1], s[m][2 * kk][3] * inv[1]);
      if (kk < 2) {
        pa[m][kk][2] = pack_bf16(s[m][2 * kk + 1][0] * inv[0], s[m][2 * kk + 1][1] * inv[0]);
        pa[m][kk][3] = pack_bf16(s[m][2 * kk + 1][2] * inv[1], s[m][2 * kk + 1][3] * inv[1]);
      } else { pa[m][kk][2] = 0; pa[m][kk][3] = 0; }
    }
  }
  asm volatile("cp.async.wait_group 0;" ::: "memory");
  __syncwarp();
  uint32_t ov[2][16][2];
#pragma unroll
  for (int np = 0; np < 8; np++) {
    float o[2][2][4] = {};
#pragma unroll
    for (int kk = 0; kk < 3; kk++) {
      uint32_t b[4];
      int mi = lane >> 3, r = kk * 16 + (mi & 1) * 8 + (lane & 7), c = np * 2 + (mi >> 1);
      ldsm4t(b, sv + r * 256 + ((c ^ (r & 7)) * 16));
#pragma unroll
      for (int m = 0; m < 2; m++) { mma16816(o[m][0], pa[m][kk], b[0], b[1]); mma16816(o[m][1], pa[m][kk], b[2], b[3]); }
    }
#pragma unroll
    for (int m = 0; m < 2; m++)
#pragma unroll
      for (int q = 0; q < 2; q++) { ov[m][np * 2 + q][0] = pack_bf16(o[m][q][0], o[m][q][1]); ov[m][np * 2 + q][1] = pack_bf16(o[m][q][2], o[m][q][3]); }
  }
  __syncwarp();
#pragma unroll
  for (int m = 0; m < 2; m++)
#pragma unroll
    for (int n = 0; n < 16; n++)
#pragma unroll
      for (int hh = 0; hh < 2; hh++) {
        int r = m * 16 + hh * 8 + g;
        *(uint32_t*)(sm[warp] + r * 256 + ((n ^ (r & 7)) * 16) + t * 4) = ov[m][n][hh];
      }
  __syncwarp();
#pragma unroll
  for (int i = 0; i < 16; i++) {
    int idx = lane + 32 * i, r = idx >> 4, c = idx & 15;
    *(uint4*)(g_o + (tok0 + r) * HD_ + h * 128 + c * 8) = *(const uint4*)(sm[warp] + r * 256 + ((c ^ (r & 7)) * 16));
  }
}
constexpr int CH_WV = 0;
constexpr int CH_MEM = CH_WV + 73728;
constexpr int CH_KB = CH_MEM + 9216;
constexpr int CH_VB = CH_KB + 12288;
constexpr int CH_WO = CH_VB + 12288;
constexpr int CH_Q = CH_WO + 81920;
constexpr int CH_R1 = CH_Q + 1024;
constexpr int CH_SC = CH_R1 + 4096;
constexpr int CH_OF = CH_SC + 3584;
constexpr int CH_R2 = CH_OF + 8192;
constexpr int CH_BAR = CH_R2 + 12288;
constexpr int CHAIN_SMEM = CH_BAR + 64 + 1024;
#define POLL_DELAY 250
__device__ __forceinline__ void st_async1(uint32_t a, uint32_t v, uint32_t bar) { asm volatile("st.async.weak.shared::cluster.mbarrier::complete_tx::bytes.b32 [%0], %1, [%2];" ::"r"(a), "r"(v), "r"(bar) : "memory"); }
__device__ __forceinline__ void st_async2(uint32_t a, uint32_t v0, uint32_t v1, uint32_t bar) { asm volatile("st.async.weak.shared::cluster.mbarrier::complete_tx::bytes.v2.b32 [%0], {%1, %2}, [%3];" ::"r"(a), "r"(v0), "r"(v1), "r"(bar) : "memory"); }
__device__ __forceinline__ uint4 lds128(uint32_t a) { uint4 v; asm volatile("ld.shared.v4.u32 {%0,%1,%2,%3}, [%4];" : "=r"(v.x), "=r"(v.y), "=r"(v.z), "=r"(v.w) : "r"(a) : "memory"); return v; }
__device__ __forceinline__ void sts128f(uint32_t a, const float (&c)[4]) { asm volatile("st.shared.v4.f32 [%0], {%1,%2,%3,%4};" ::"r"(a), "f"(c[0]), "f"(c[1]), "f"(c[2]), "f"(c[3]) : "memory"); }
__device__ __forceinline__ void sts32(uint32_t a, uint32_t v) { asm volatile("st.shared.u32 [%0], %1;" ::"r"(a), "r"(v) : "memory"); }
__device__ __forceinline__ void mbar_wait_b(uint32_t b, uint32_t parity) {
  uint32_t ok; int n = 0;
  do { asm volatile("{\n.reg .pred p;\nmbarrier.try_wait.parity.shared::cta.b64 p, [%1], %2;\nselp.u32 %0, 1, 0, p;\n}" : "=r"(ok) : "r"(b), "r"(parity) : "memory"); } while (!ok && ++n < (1 << 20));
}
__device__ __forceinline__ uint32_t mapa_v(uint32_t a, uint32_t r) { uint32_t o; asm volatile("mapa.shared::cluster.u32 %0, %1, %2;" : "=r"(o) : "r"(a), "r"(r)); return o; }
__device__ __forceinline__ uint32_t tid_v() { uint32_t o; asm volatile("mov.u32 %0, %%tid.x;" : "=r"(o)); return o; }
template <int ACC>
__device__ __forceinline__ void wg_rs(float (&d)[4], const uint32_t (&a)[4], uint32_t dlo) {
  uint64_t db = ((uint64_t)16 << 32) | dlo;
  asm volatile("{\n.reg .pred p;\nsetp.ne.b32 p, %9, 0;\nwgmma.mma_async.sync.aligned.m64n8k16.f32.bf16.bf16 {%0,%1,%2,%3}, {%4,%5,%6,%7}, %8, p, 1, 1, 0;\n}"
               : "+f"(d[0]), "+f"(d[1]), "+f"(d[2]), "+f"(d[3]) : "r"(a[0]), "r"(a[1]), "r"(a[2]), "r"(a[3]), "l"(db), "n"(ACC));
}
template <int N>
__device__ __forceinline__ void wg_wait(float (&d)[N][4]) {
  asm volatile("wgmma.commit_group.sync.aligned;\nwgmma.wait_group.sync.aligned 0;" ::: "memory");
#pragma unroll
  for (int i = 0; i < N; i++) asm volatile("" : "+f"(d[i][0]), "+f"(d[i][1]), "+f"(d[i][2]), "+f"(d[i][3]) :: "memory");
}
#define BAR_ALL() asm volatile("bar.sync 0, 256;" ::: "memory")

__global__ void __launch_bounds__(256, 1) chain_kernel(const bf16* __restrict__ mem0, const bf16* __restrict__ Wq, const bf16* __restrict__ Wk,
                                                       const bf16* __restrict__ Wv, const bf16* __restrict__ Wo) {
  extern __shared__ uint8_t smem_raw[];
  const uint32_t sb = (smem_u32(smem_raw) + 1023) & ~1023u;
  const int tid = threadIdx.x, warp = __shfl_sync(~0u, tid >> 5, 0), wgi = __shfl_sync(~0u, tid >> 7, 0), lane = tid & 31, g = lane >> 2, t = lane & 3;
  const uint32_t r = cluster_rank();
  const int c = blockIdx.x >> 3, h = 4 * c + (r >> 1), j0 = h * 128 + (r & 1) * 64;
  const uint32_t bm = sb + CH_BAR, bs = bm + 8, bo = bm + 16;
  pdl_launch();
  if (blockIdx.x == 0 && tid == 0) PT(7);
  if (tid == 0) { mbar_init(bm, 1); mbar_init(bs, 1); mbar_init(bo, 1); asm volatile("fence.mbarrier_init.release.cluster;" ::: "memory"); }
  const int mi = lane >> 3, l7 = lane & 7;
  for (int i = tid; i < 576 * 8; i += 256) {
    int row = i >> 3, ch = i & 7;
    cp16(sb + CH_WV + row * 128 + ((ch ^ (row & 7)) * 16), Wq + (size_t)row * HD_ + j0 + ch * 8);
    cp16(sb + CH_WO + row * 128 + ((ch ^ (row & 7)) * 16), Wk + (size_t)row * HD_ + j0 + ch * 8);
  }
  asm volatile("cp.async.commit_group;\ncp.async.wait_group 0;" ::: "memory");
  BAR_ALL();
  uint32_t w1[36][4];
#pragma unroll
  for (int i = 0; i < 36; i++) {
    int row = i * 16 + (mi >> 1) * 8 + l7, ch = ((warp & 3) * 2 + (mi & 1)) ^ (row & 7);
    ldsm4t(w1[i], sb + (wgi ? CH_WO : CH_WV) + row * 128 + ch * 16);
  }
  BAR_ALL();
  for (int i = tid; i < 512 * 10; i += 256) {
    int row = i / 10, ch = i - row * 10;
    cp16(sb + CH_WV + row * 176 + ch * 16, Wo + (size_t)(c * 512 + row) * D_ + (ch < 8 ? r * 64 + ch * 8 : 512 + (r >> 1) * 16 + (ch - 8) * 8));
  }
  asm volatile("cp.async.commit_group;\ncp.async.wait_group 0;" ::: "memory");
  BAR_ALL();
  const int kperm = 2 * ((mi >> 1) * 2 + (l7 >> 2)) + (l7 & 1) + 8 * ((l7 >> 1) & 1);
  for (int i = 0; i < 16; i++) {
    uint32_t a[4];
    ldsm4t(a, sb + CH_WV + ((wgi * 16 + i) * 16 + kperm) * 176 + ((warp & 3) * 2 + (mi & 1)) * 16);
    asm volatile("st.shared.v4.u32 [%0], {%1,%2,%3,%4};" ::"r"(sb + CH_WO + 8192 + (warp * 16 + i) * 512 + lane * 16), "r"(a[0]), "r"(a[1]), "r"(a[2]), "r"(a[3]) : "memory");
  }
  for (int u = warp; u < 16; u += 8) {
    uint32_t a[4];
    ldsm4t(a, sb + CH_WV + (((r & 1) * 16 + u) * 16 + kperm) * 176 + (8 + (mi & 1)) * 16);
    asm volatile("st.shared.v4.u32 [%0], {%1,%2,%3,%4};" ::"r"(sb + CH_WO + u * 512 + lane * 16), "r"(a[0]), "r"(a[1]), "r"(a[2]), "r"(a[3]) : "memory");
  }
  BAR_ALL();
  for (int i = tid; i < 576 * 8; i += 256) {
    int row = i >> 3, ch = i & 7;
    cp16(sb + CH_WV + row * 128 + ((ch ^ (row & 7)) * 16), Wv + (size_t)row * HD_ + j0 + ch * 8);
  }
  for (int i = tid; i < 8 * 72; i += 256) {
    int row = i / 72, ch = i - row * 72;
    cp16(sb + CH_MEM + ch * 128 + row * 16, mem0 + row * D_ + ch * 8);
  }
  for (int i = tid; i < 4 * 64; i += 256) {
    int b = i >> 6, o = i & 63;
    asm volatile("st.shared.v4.u32 [%0], {%1,%1,%1,%1};" ::"r"(sb + CH_KB + b * 6144 + 40 * 128 + o * 16), "r"(0) : "memory");
  }
  pdl_wait();
  auto prefetch_kv = [&](int s, int tid) {
#pragma unroll
    for (int i = 0; i < 2; i++) {
      int u = tid + i * 256, which = u >> 8, row = (u & 255) >> 3, ch = u & 7;
      const bf16* src = (which ? g_v : g_k) + (size_t)(s * 32 + row) * HD_ + j0 + ch * 8;
      cp16(sb + (which ? CH_VB : CH_KB) + (s & 1) * 6144 + (row + 8) * 128 + ((ch ^ (row & 7)) * 16), src);
    }
    asm volatile("cp.async.commit_group;" ::: "memory");
  };
  prefetch_kv(0, tid);
  asm volatile("cp.async.wait_group 0;" ::: "memory");
  asm volatile("fence.proxy.async.shared::cta;" ::: "memory");
  BAR_ALL();
  cluster_sync();
  const uint32_t dsb = ((sb & 0x3FFFF) >> 4) | (8u << 16);
  if (blockIdx.x == 0 && tid == 0) PT(10);
#define CP(i) if (blockIdx.x == 0 && lane == 0 && warp == (((i) == 5 || (i) == 7) ? 4 : 0)) PC(64 + s * 16 + (i))
  for (int s = 0; s < NSEG; s++) {
    const int tid = tid_v(), lane = tid & 31, g = lane >> 2, t = lane & 3, mi = lane >> 3, l7 = lane & 7;
    CP(0);
    const uint32_t par = s & 1, kb = sb + CH_KB + par * 6144, vb = sb + CH_VB + par * 6144;
    if (s > 0) mbar_wait_b(bm, par ^ 1);
    CP(1);
    if (tid == 0 && s < NSEG - 1) { mbar_expect(bs, 2560); mbar_expect(bo, 8192); mbar_expect(bm, 9216); }
    auto phase1 = [&]() {
      float pa[3][4] = {};
#pragma unroll
      for (int i = 0; i < 36; i += 2) {
        uint32_t b[4];
        ldsm4(b, sb + CH_MEM + i * 256 + mi * 128 + l7 * 16);
        mma16816(pa[i % 3], w1[i], b[0], b[1]); mma16816(pa[(i + 1) % 3], w1[i + 1], b[2], b[3]);
      }
      CP(2);
      uint32_t b0 = movm(pack_bf16(pa[0][0] + pa[1][0] + pa[2][0], pa[0][1] + pa[1][1] + pa[2][1]));
      uint32_t b1 = movm(pack_bf16(pa[0][2] + pa[1][2] + pa[2][2], pa[0][3] + pa[1][3] + pa[2][3]));
      uint32_t dst = (wgi ? kb : sb + CH_Q) + g * 128 + t * 4;
      sts32(dst + ((((warp & 3) * 2) ^ g) * 16), b0); sts32(dst + ((((warp & 3) * 2 + 1) ^ g) * 16), b1);
      if (wgi) { uint32_t* gp = (uint32_t*)(g_km + ((size_t)s * 8 + g) * HD_ + j0 + (warp & 3) * 16 + t * 2); gp[0] = b0; gp[4] = b1; }
      asm volatile("cp.async.wait_group 0;" ::: "memory");
    };
    if (wgi == 0) {
      phase1();
      BAR_ALL();
      CP(4);
      if (s + 1 < NSEG) { prefetch_kv(s + 1, tid); asm volatile("bar.sync 6, 224;" ::: "memory"); }
      float va[4][4];
      asm volatile("wgmma.fence.sync.aligned;" ::: "memory");
      const uint32_t dwa = (((sb + CH_WV) & 0x3FFFF) >> 4) | ((8192u >> 4) << 16);
#pragma unroll
      for (int ks = 0; ks < 36; ks++) {
        uint64_t da = ((uint64_t)(0x40000000u | (1024 >> 4)) << 32) | (dwa + ks * 128), db = ((uint64_t)16 << 32) | (dsb + ((CH_MEM + ks * 256) >> 4));
        if (ks < 4)
          asm volatile("{\n.reg .pred p;\nsetp.ne.b32 p, 0, 0;\nwgmma.mma_async.sync.aligned.m64n8k16.f32.bf16.bf16 {%0,%1,%2,%3}, %4, %5, p, 1, 1, 1, 0;\n}"
                       : "=f"(va[ks & 3][0]), "=f"(va[ks & 3][1]), "=f"(va[ks & 3][2]), "=f"(va[ks & 3][3]) : "l"(da), "l"(db));
        else
          asm volatile("{\n.reg .pred p;\nsetp.ne.b32 p, 1, 0;\nwgmma.mma_async.sync.aligned.m64n8k16.f32.bf16.bf16 {%0,%1,%2,%3}, %4, %5, p, 1, 1, 1, 0;\n}"
                       : "+f"(va[ks & 3][0]), "+f"(va[ks & 3][1]), "+f"(va[ks & 3][2]), "+f"(va[ks & 3][3]) : "l"(da), "l"(db));
      }
      wg_wait(va);
      CP(6);
      uint32_t b0 = movm(pack_bf16(va[0][0] + va[1][0] + va[2][0] + va[3][0], va[0][1] + va[1][1] + va[2][1] + va[3][1]));
      uint32_t b1 = movm(pack_bf16(va[0][2] + va[1][2] + va[2][2] + va[3][2], va[0][3] + va[1][3] + va[2][3] + va[3][3]));
      sts32(vb + g * 128 + t * 4 + (((warp * 2) ^ g) * 16), b0); sts32(vb + g * 128 + t * 4 + (((warp * 2 + 1) ^ g) * 16), b1);
      uint32_t* gp = (uint32_t*)(g_vm + ((size_t)s * 8 + g) * HD_ + j0 + warp * 16 + t * 2); gp[0] = b0; gp[4] = b1;
      asm volatile("bar.arrive 7, 256;" ::: "memory");
    } else {
      phase1();
      BAR_ALL();
      if (warp < 7 && s < NSEG - 1) {
        const int mt = warp - 4;
        const uint32_t sc_l = mapa_v(sb + CH_SC + (r & 1) * 1792, r), sc_r = mapa_v(sb + CH_SC + (r & 1) * 1792, r ^ 1), bs_l = mapa_v(bs, r), bs_r = mapa_v(bs, r ^ 1);
        float sa[4][4] = {};
#pragma unroll
        for (int kp = 0; kp < 2; kp++) {
          uint32_t b[4], a0[4], a1[4];
          ldsm4(b, sb + CH_Q + l7 * 128 + (((kp * 4 + mi) ^ l7) * 16));
          int row = mt * 16 + (mi & 1) * 8 + l7;
          ldsm4(a0, kb + row * 128 + (((kp * 4 + (mi >> 1)) ^ l7) * 16));
          ldsm4(a1, kb + row * 128 + (((kp * 4 + 2 + (mi >> 1)) ^ l7) * 16));
          mma16816(sa[2 * kp], a0, b[0], b[1]); mma16816(sa[2 * kp + 1], a1, b[2], b[3]);
        }
        asm volatile("bar.arrive 6, 224;" :: "f"(sa[0][0]), "f"(sa[1][0]), "f"(sa[2][0]), "f"(sa[3][0]) : "memory");
#pragma unroll
        for (int e = 0; e < 4; e++) {
          uint32_t off = ((2 * t + (e & 1)) * 56 + mt * 16 + (e >> 1) * 8 + g) * 4, v = __float_as_uint((sa[0][e] + sa[1][e]) + (sa[2][e] + sa[3][e]));
          if (mt < 2 || e < 2) { st_async1(sc_r + off, v, bs_r); st_async1(sc_l + off, v, bs_l); }
        }
        CP(5);
      }
      if (s < NSEG - 1) {
        prefetch_kv(s + 1, tid);
        const int w3 = warp & 3;
        uint32_t vt[3][4];
#pragma unroll
        for (int kk = 1; kk < 3; kk++) { int row = kk * 16 + (mi >> 1) * 8 + l7; ldsm4t(vt[kk], vb + row * 128 + (((w3 * 2 + (mi & 1)) ^ l7) * 16)); }
        mbar_wait_b(bs, par);
        CP(7);
        float z[10]; float mx = -INFINITY;
        const float scl = 0.08838834764831845f * 1.4426950408889634f;
#pragma unroll
        for (int i = 0; i < 5; i++) {
          float2 u0, u1; uint32_t a = sb + CH_SC + (g * 56 + i * 8 + 2 * t) * 4;
          asm volatile("ld.shared.v2.f32 {%0,%1}, [%2];" : "=f"(u0.x), "=f"(u0.y) : "r"(a) : "memory");
          asm volatile("ld.shared.v2.f32 {%0,%1}, [%2];" : "=f"(u1.x), "=f"(u1.y) : "r"(a + 1792) : "memory");
          z[2 * i] = (u0.x + u1.x) * scl; z[2 * i + 1] = (u0.y + u1.y) * scl;
        }
        mx = fmaxf(fmaxf(fmaxf(z[0], z[1]), fmaxf(z[2], z[3])), fmaxf(fmaxf(fmaxf(z[4], z[5]), fmaxf(z[6], z[7])), fmaxf(z[8], z[9])));
        mx = fmaxf(mx, __shfl_xor_sync(~0u, mx, 1)); mx = fmaxf(mx, __shfl_xor_sync(~0u, mx, 2));
        uint32_t pb[5];
#pragma unroll
        for (int i = 0; i < 5; i++) pb[i] = pack_bf16(exp2f(z[2 * i] - mx), exp2f(z[2 * i + 1] - mx));
        const uint32_t ones[4] = {0x3F803F80u, 0x3F803F80u, 0x3F803F80u, 0x3F803F80u};
        float o0[4] = {}, o1[4] = {}, o2[4] = {}, s0[4] = {}, s1[4] = {}, s2[4] = {};
        mma16816(s0, ones, pb[0], pb[1]);
        mma16816(o1, vt[1], pb[2], pb[3]); mma16816(s1, ones, pb[2], pb[3]);
        mma16816(o2, vt[2], pb[4], 0u); mma16816(s2, ones, pb[4], 0u);
        asm volatile("bar.sync 7, 256;" ::: "memory");
        ldsm4t(vt[0], vb + ((mi >> 1) * 8 + l7) * 128 + (((w3 * 2 + (mi & 1)) ^ l7) * 16));
        mma16816(o0, vt[0], pb[0], pb[1]);
        const float i0 = __fdividef(1.f, s0[0] + s1[0] + s2[0]), i1 = __fdividef(1.f, s0[1] + s1[1] + s2[1]);
        uint32_t f0 = movm(pack_bf16((o0[0] + o1[0] + o2[0]) * i0, (o0[1] + o1[1] + o2[1]) * i1));
        uint32_t f1 = movm(pack_bf16((o0[2] + o1[2] + o2[2]) * i0, (o0[3] + o1[3] + o2[3]) * i1));
        const int ks = r * 4 + w3;
        const uint32_t off = CH_OF + ks * 256 + (t >> 1) * 128 + g * 16 + (t & 1) * 8;
        const uint32_t cl0 = mapa_v(sb, 0), clstep = mapa_v(sb, 1) - cl0;
#pragma unroll
        for (int d = 0; d < 8; d++) st_async2(cl0 + d * clstep + off, f0, f1, cl0 + d * clstep + CH_BAR + 16);
      } else asm volatile("bar.sync 7, 256;" ::: "memory");
    }
    if (s == NSEG - 1) break;
    CP(8);
    uint32_t wo[16][4];
#pragma unroll
    for (int i = 0; i < 16; i++) { uint4 v = lds128(sb + CH_WO + 8192 + (warp * 16 + i) * 512 + lane * 16); wo[i][0] = v.x; wo[i][1] = v.y; wo[i][2] = v.z; wo[i][3] = v.w; }
    mbar_wait_b(bo, par);
    CP(9);
    const uint32_t tag = ((s >> 1) + 1) & 1;
    float* pbase = g_part + (size_t)par * 8 * 5120 + lane * 4;
    auto put = [&](int slot, const float (&a)[4]) {
      asm volatile("st.relaxed.gpu.global.v4.b32 [%0], {%1,%2,%3,%4};" ::"l"(pbase + c * 5120 + slot * 128), "r"((__float_as_uint(a[0]) & ~1u) | tag),
                   "r"((__float_as_uint(a[1]) & ~1u) | tag), "r"((__float_as_uint(a[2]) & ~1u) | tag), "r"((__float_as_uint(a[3]) & ~1u) | tag) : "memory");
    };
    {
      float acc[4][4];
      asm volatile("wgmma.fence.sync.aligned;" ::: "memory");
      const uint32_t dof = dsb + ((CH_OF >> 4) + wgi * 256);
#pragma unroll
      for (int i = 0; i < 16; i++) { if (i < 4) wg_rs<0>(acc[i & 3], wo[i], dof + i * 16); else wg_rs<1>(acc[i & 3], wo[i], dof + i * 16); }
      wg_wait(acc);
#pragma unroll
      for (int e = 0; e < 4; e++) acc[0][e] = (acc[0][e] + acc[1][e]) + (acc[2][e] + acc[3][e]);
      CP(10);
      const int w3 = warp & 3;
      if (wgi) {
        sts128f(sb + CH_R2 + w3 * 512 + lane * 16, acc[0]);
        asm volatile("bar.arrive %0, 64;" ::"r"(1 + w3) : "memory");
        if (w3 < 2) {
          float ex[2][4] = {};
#pragma unroll
          for (int i = 0; i < 8; i += 2) {
            uint32_t b[4]; ldsm4(b, sb + CH_OF + ((r & 1) * 16 + w3 * 8 + i) * 256 + mi * 128 + l7 * 16);
            uint4 v0 = lds128(sb + CH_WO + (w3 * 8 + i) * 512 + lane * 16), v1 = lds128(sb + CH_WO + (w3 * 8 + i + 1) * 512 + lane * 16);
            uint32_t a0[4] = {v0.x, v0.y, v0.z, v0.w}, a1[4] = {v1.x, v1.y, v1.z, v1.w};
            mma16816(ex[0], a0, b[0], b[1]); mma16816(ex[1], a1, b[2], b[3]);
          }
#pragma unroll
          for (int e = 0; e < 4; e++) ex[0][e] += ex[1][e];
          if (w3 == 1) { sts128f(sb + CH_R2 + 4 * 512 + lane * 16, ex[0]); asm volatile("bar.arrive 5, 64;" ::: "memory"); }
          else {
            asm volatile("bar.sync 5, 64;" ::: "memory");
            uint4 v = lds128(sb + CH_R2 + 4 * 512 + lane * 16);
            ex[0][0] += __uint_as_float(v.x); ex[0][1] += __uint_as_float(v.y); ex[0][2] += __uint_as_float(v.z); ex[0][3] += __uint_as_float(v.w);
            put(32 + r, ex[0]);
          }
        }
      } else {
        asm volatile("bar.sync %0, 64;" ::"r"(1 + w3) : "memory");
        uint4 v = lds128(sb + CH_R2 + w3 * 512 + lane * 16);
        acc[0][0] += __uint_as_float(v.x); acc[0][1] += __uint_as_float(v.y); acc[0][2] += __uint_as_float(v.z); acc[0][3] += __uint_as_float(v.w);
        put(r * 4 + w3, acc[0]);
      }
    }
    CP(11);
    if (warp < 4 || warp == 6) { long long t0 = clock64(); while (clock64() - t0 < POLL_DELAY) {} }
    if (warp < 4) {
      const float* pb = pbase + (r * 4 + warp) * 128;
      uint4 v[8]; int n = 0; bool ok;
      do {
        ok = true;
#pragma unroll
        for (int i = 0; i < 8; i++) asm volatile("ld.relaxed.gpu.global.v4.b32 {%0,%1,%2,%3}, [%4];" : "=r"(v[i].x), "=r"(v[i].y), "=r"(v[i].z), "=r"(v[i].w) : "l"(pb + i * 5120) : "memory");
#pragma unroll
        for (int i = 0; i < 8; i++) ok = ok && (((v[i].x & v[i].y & v[i].z & v[i].w & 1u) == tag) && (((v[i].x | v[i].y | v[i].z | v[i].w) & 1u) == tag));
      } while (!ok && ++n < (1 << 18));
      float m[4] = {};
#pragma unroll
      for (int i = 0; i < 8; i++) { m[0] += __uint_as_float(v[i].x); m[1] += __uint_as_float(v[i].y); m[2] += __uint_as_float(v[i].z); m[3] += __uint_as_float(v[i].w); }
      __syncwarp();
      CP(12);
      uint32_t b0 = movm(pack_bf16(m[0], m[1])), b1 = movm(pack_bf16(m[2], m[3]));
      const uint32_t off = CH_MEM + (r * 4 + warp) * 256 + g * 16 + t * 4;
      const uint32_t cl0 = mapa_v(sb, 0), clstep = mapa_v(sb, 1) - cl0;
#pragma unroll
      for (int d = 0; d < 8; d++) { st_async1(cl0 + d * clstep + off, b0, cl0 + d * clstep + CH_BAR); st_async1(cl0 + d * clstep + off + 128, b1, cl0 + d * clstep + CH_BAR); }
    } else if (warp == 6) {
      const float* pb = pbase - lane * 4 + (32 + (r & ~1u)) * 128 + lane * 4 + (r & 1) * 2;
      uint2 v[16]; int n = 0; bool ok;
      do {
        ok = true;
#pragma unroll
        for (int i = 0; i < 16; i++) asm volatile("ld.relaxed.gpu.global.v2.b32 {%0,%1}, [%2];" : "=r"(v[i].x), "=r"(v[i].y) : "l"(pb + (i >> 1) * 5120 + (i & 1) * 128) : "memory");
#pragma unroll
        for (int i = 0; i < 16; i++) ok = ok && ((v[i].x & v[i].y & 1u) == tag) && (((v[i].x | v[i].y) & 1u) == tag);
      } while (!ok && ++n < (1 << 18));
      float m0 = 0.f, m1 = 0.f;
#pragma unroll
      for (int i = 0; i < 16; i++) { m0 += __uint_as_float(v[i].x); m1 += __uint_as_float(v[i].y); }
      __syncwarp();
      uint32_t b0 = movm(pack_bf16(m0, m1));
      const uint32_t off = CH_MEM + (32 + (r >> 1)) * 256 + (r & 1) * 128 + g * 16 + t * 4;
      const uint32_t cl0 = mapa_v(sb, 0), clstep = mapa_v(sb, 1) - cl0;
#pragma unroll
      for (int d = 0; d < 8; d++) st_async1(cl0 + d * clstep + off, b0, cl0 + d * clstep + CH_BAR);
    }
  }
  if (blockIdx.x == 0 && tid == 0) PT(8);
  cluster_sync();
}
typedef CUresult (*EncodeFn)(CUtensorMap*, CUtensorMapDataType, cuuint32_t, void*, const cuuint64_t*, const cuuint64_t*, const cuuint32_t*, const cuuint32_t*,
                             CUtensorMapInterleave, CUtensorMapSwizzle, CUtensorMapL2promotion, CUtensorMapFloatOOBfill);
static EncodeFn g_enc;
static void mkmap(CUtensorMap* m, const void* ptr, int rows, int cols, int boxc, int boxr) {
  cuuint64_t dims[2] = {(cuuint64_t)cols, (cuuint64_t)rows}, strides[1] = {(cuuint64_t)cols * 2};
  cuuint32_t box[2] = {(cuuint32_t)boxc, (cuuint32_t)boxr}, es[2] = {1, 1};
  g_enc(m, CU_TENSOR_MAP_DATA_TYPE_BFLOAT16, 2, (void*)ptr, dims, strides, box, es, CU_TENSOR_MAP_INTERLEAVE_NONE, CU_TENSOR_MAP_SWIZZLE_128B,
        CU_TENSOR_MAP_L2_PROMOTION_L2_256B, CU_TENSOR_MAP_FLOAT_OOB_FILL_NONE);
}
static inline uint16_t mkjob(int type, int m, int n) { return (uint16_t)(type << 12 | m << 6 | n); }
static void schedule(GemmParams& p, const uint16_t* jobs, int nj, int ncl) {
  static const double cost[6] = {11.0, 11.0, 11.0, 26.5, 57.5, 51.5};
  double t[66] = {}; int cnt[66] = {};
  p.stride = 960 / ncl;
  for (int i = 0; i < 960; i++) p.job[i] = 0xFFFF;
  double g2_end = 0;
  for (int i = 0; i < nj; i++) {
    int b = 0;
    for (int c = 1; c < ncl; c++) if (t[c] < t[b] || (t[c] == t[b] && cnt[c] < cnt[b])) b = c;
    int ty = jobs[i] >> 12;
    if (ty == 4 && t[b] < g2_end) t[b] = g2_end;
    t[b] += cost[ty];
    if (ty == 3 && t[b] > g2_end) g2_end = t[b];
    p.job[b * p.stride + cnt[b]++] = jobs[i];
  }
}
template <class... A>
static void launch(void (*k)(A...), int grid, int block, int smem, int cluster, bool pdl, A... a) {
  cudaLaunchConfig_t c = {};
  c.gridDim = grid; c.blockDim = block; c.dynamicSmemBytes = smem; c.stream = cudaStreamPerThread;
  cudaLaunchAttribute at[2]; int n = 0;
  if (cluster > 1) { at[n].id = cudaLaunchAttributeClusterDimension; at[n].val.clusterDim.x = cluster; at[n].val.clusterDim.y = 1; at[n].val.clusterDim.z = 1; n++; }
  if (pdl) { at[n].id = cudaLaunchAttributeProgrammaticStreamSerialization; at[n].val.programmaticStreamSerializationAllowed = 1; n++; }
  c.attrs = at; c.numAttrs = n;
  cudaLaunchKernelEx(&c, k, a...);
}

extern "C" void kernel_launch(void* const* d_in, const int* in_sizes, int n_in, void* d_out, int out_size) {
  const bf16 *x = (const bf16*)d_in[0], *mem0 = (const bf16*)d_in[1], *Wq = (const bf16*)d_in[2], *Wk = (const bf16*)d_in[3], *Wv = (const bf16*)d_in[4],
             *Wo = (const bf16*)d_in[5], *w1 = (const bf16*)d_in[8], *b1 = (const bf16*)d_in[9], *w2 = (const bf16*)d_in[10], *b2 = (const bf16*)d_in[11];
  static bool init = false;
  static GemmParams pre, side, post;
  if (!init) {
    init = true;
    cudaDriverEntryPointQueryResult qr;
    cudaGetDriverEntryPoint("cuTensorMapEncodeTiled", (void**)&g_enc, cudaEnableDefault, &qr);
    void *xn, *h2, *o, *ut;
    cudaGetSymbolAddress(&xn, g_xn); cudaGetSymbolAddress(&h2, g_h2); cudaGetSymbolAddress(&o, g_o); cudaGetSymbolAddress(&ut, g_ut);
    GemmParams b = {};
    mkmap(&b.mA[0], xn, S_, D_, 64, 128); mkmap(&b.mA[1], w1, S_, F_, 64, 64); mkmap(&b.mA[2], w2, F_, S_, 64, 64); mkmap(&b.mA[3], o, S_, HD_, 64, 128);
    mkmap(&b.mB[0], Wq, D_, HD_, 64, 32); mkmap(&b.mB[1], Wk, D_, HD_, 64, 32); mkmap(&b.mB[2], Wv, D_, HD_, 64, 32);
    mkmap(&b.mB[3], h2, S_, D_, 64, 32); mkmap(&b.mB[4], ut, F_, D_, 64, 32); mkmap(&b.mB[5], Wo, HD_, D_, 64, 32);
    b.x = x; b.b1 = b1; b.b2 = b2; b.out = (bf16*)d_out;
    pre = b; side = b; post = b; side.kid = 1; post.kid = 2;
    static uint16_t jl[1024]; int n = 0;
    for (int m = 0; m < 8; m++) for (int j = 0; j < 16; j++) { jl[n++] = mkjob(1, m, j); jl[n++] = mkjob(2, m, j); }
    schedule(pre, jl, n, 66);
    n = 0;
    for (int m = 0; m < 18; m++) for (int j = 0; j < 3; j++) jl[n++] = mkjob(3, m, j);
    int qn = 0;
    for (; qn < 34; qn++) jl[n++] = mkjob(0, qn >> 4, qn & 15);
    for (int m = 0; m < 8; m++) for (int j = 0; j < 3; j++) jl[n++] = mkjob(4, m, j);
    for (; qn < 128; qn++) jl[n++] = mkjob(0, qn >> 4, qn & 15);
    schedule(side, jl, n, 34);
    side.wait_at_end = 1;
    n = 0;
    for (int m = 0; m < 8; m++) for (int j = 0; j < 3; j++) jl[n++] = mkjob(5, m, j);
    schedule(post, jl, n, 24);
    cudaFuncSetAttribute(gemm_kernel, cudaFuncAttributeMaxDynamicSharedMemorySize, GEMM_SMEM);
    cudaFuncSetAttribute(chain_kernel, cudaFuncAttributeMaxDynamicSharedMemorySize, CHAIN_SMEM);
  }
  launch(ln_kernel, 256, 256, 0, 1, false, x);
  launch(gemm_kernel, 132, 384, GEMM_SMEM, 2, false, pre);
  launch(chain_kernel, 64, 256, CHAIN_SMEM, 8, false, mem0, Wq, Wk, Wv, Wo);
  launch(gemm_kernel, 68, 384, GEMM_SMEM, 2, true, side);
  launch(attn_kernel, 512, 128, 0, 1, false);
  launch(gemm_kernel, 48, 384, GEMM_SMEM, 2, false, post);
}
```

```cpp
#include <cuda_runtime.h>
#include <cuda_bf16.h>
#include <cuda.h>
#include <stdint.h>

typedef __nv_bfloat16 bf16;
constexpr int S_ = 2048, D_ = 576, HD_ = 4096, F_ = 4608, NSEG = 64;

__device__ bf16 g_xn[S_ * D_];
__device__ bf16 g_h2[S_ * D_];
__device__ bf16 g_q[S_ * HD_];
__device__ bf16 g_k[S_ * HD_];
__device__ bf16 g_v[S_ * HD_];
__device__ bf16 g_o[S_ * HD_];
__device__ bf16 g_km[NSEG * 8 * HD_];
__device__ bf16 g_vm[NSEG * 8 * HD_];
__device__ bf16 g_ut[F_ * D_];
__device__ float g_yb[S_ * D_];
__device__ float g_part[2 * 8 * 8 * 5 * 32 * 4];
__device__ unsigned int g_cnt[128];

#define PT(i)
#define PC(i)
__device__ __forceinline__ uint32_t smem_u32(const void* p) { return (uint32_t)__cvta_generic_to_shared(p); }
__device__ __forceinline__ void mbar_init(uint32_t b, uint32_t c) { asm volatile("mbarrier.init.shared::cta.b64 [%0], %1;" ::"r"(b), "r"(c)); }
__device__ __forceinline__ void mbar_expect(uint32_t b, uint32_t bytes) { asm volatile("mbarrier.arrive.expect_tx.shared::cta.b64 _, [%0], %1;" ::"r"(b), "r"(bytes) : "memory"); }
__device__ __forceinline__ void mbar_wait(uint32_t b, uint32_t parity) {
  uint32_t ok;
  do { asm volatile("{\n.reg .pred p;\nmbarrier.try_wait.parity.shared::cta.b64 p, [%1], %2;\nselp.u32 %0, 1, 0, p;\n}" : "=r"(ok) : "r"(b), "r"(parity) : "memory"); } while (!ok);
}
__device__ __forceinline__ void mbar_wait_cl(uint32_t b, uint32_t parity) {
  uint32_t ok;
  do { asm volatile("{\n.reg .pred p;\nmbarrier.try_wait.parity.shared::cta.b64 p, [%1], %2;\nselp.u32 %0, 1, 0, p;\n}" : "=r"(ok) : "r"(b), "r"(parity) : "memory"); } while (!ok);
}
__device__ __forceinline__ uint32_t mapa(uint32_t a, uint32_t r) { uint32_t o; asm("mapa.shared::cluster.u32 %0, %1, %2;" : "=r"(o) : "r"(a), "r"(r)); return o; }
__device__ __forceinline__ void mbar_arrive_remote(uint32_t remote_b) { asm volatile("mbarrier.arrive.shared::cluster.b64 _, [%0];" ::"r"(remote_b) : "memory"); }
__device__ __forceinline__ uint32_t cluster_rank() { uint32_t r; asm("mov.u32 %0, %%cluster_ctarank;" : "=r"(r)); return r; }
__device__ __forceinline__ void cluster_sync() { asm volatile("barrier.cluster.arrive.release.aligned;\nbarrier.cluster.wait.acquire.aligned;" ::: "memory"); }
__device__ __forceinline__ void tma2d(uint32_t dst, const CUtensorMap* m, int c0, int c1, uint32_t bar) {
  asm volatile("cp.async.bulk.tensor.2d.shared::cluster.global.mbarrier::complete_tx::bytes [%0], [%1, {%3, %4}], [%2];"
               ::"r"(dst), "l"(m), "r"(bar), "r"(c0), "r"(c1) : "memory");
}
__device__ __forceinline__ void tma2d_mc(uint32_t dst, const CUtensorMap* m, int c0, int c1, uint32_t bar, uint16_t mask) {
  asm volatile("cp.async.bulk.tensor.2d.shared::cluster.global.mbarrier::complete_tx::bytes.multicast::cluster [%0], [%1, {%3, %4}], [%2], %5;"
               ::"r"(dst), "l"(m), "r"(bar), "r"(c0), "r"(c1), "h"(mask) : "memory");
}
__device__ __forceinline__ uint32_t pack_bf16(float a, float b) { __nv_bfloat162 t = __floats2bfloat162_rn(a, b); return *(uint32_t*)&t; }
__device__ __forceinline__ float2 unpack_bf16(uint32_t u) { return __bfloat1622float2(*(__nv_bfloat162*)&u); }
__device__ __forceinline__ void mma16816(float (&c)[4], const uint32_t (&a)[4], uint32_t b0, uint32_t b1) {
  asm volatile("mma.sync.aligned.m16n8k16.row.col.f32.bf16.bf16.f32 {%0,%1,%2,%3},{%4,%5,%6,%7},{%8,%9},{%0,%1,%2,%3};"
               : "+f"(c[0]), "+f"(c[1]), "+f"(c[2]), "+f"(c[3]) : "r"(a[0]), "r"(a[1]), "r"(a[2]), "r"(a[3]), "r"(b0), "r"(b1));
}
__device__ __forceinline__ void ldsm4(uint32_t (&r)[4], uint32_t a) { asm volatile("ldmatrix.sync.aligned.m8n8.x4.shared.b16 {%0,%1,%2,%3},[%4];" : "=r"(r[0]), "=r"(r[1]), "=r"(r[2]), "=r"(r[3]) : "r"(a) : "memory"); }
__device__ __forceinline__ void ldsm4t(uint32_t (&r)[4], uint32_t a) { asm volatile("ldmatrix.sync.aligned.m8n8.x4.trans.shared.b16 {%0,%1,%2,%3},[%4];" : "=r"(r[0]), "=r"(r[1]), "=r"(r[2]), "=r"(r[3]) : "r"(a) : "memory"); }
__device__ __forceinline__ uint32_t movm(uint32_t a) { uint32_t o; asm volatile("movmatrix.sync.aligned.m8n8.trans.b16 %0, %1;" : "=r"(o) : "r"(a)); return o; }
__device__ __forceinline__ void cp16(uint32_t dst, const void* src) { asm volatile("cp.async.cg.shared.global [%0], [%1], 16;" ::"r"(dst), "l"(src) : "memory"); }
__device__ __forceinline__ void pdl_wait() { asm volatile("griddepcontrol.wait;" ::: "memory"); }
__device__ __forceinline__ void pdl_launch() { asm volatile("griddepcontrol.launch_dependents;" ::: "memory"); }

__device__ __forceinline__ void wait_cnt(const unsigned int* c, unsigned int target) {
  uint32_t v; int n = 0;
  do { asm volatile("ld.acquire.gpu.global.u32 %0, [%1];" : "=r"(v) : "l"(c) : "memory"); if (v >= target) break; __nanosleep(64); } while (++n < (1 << 22));
}
__global__ void __launch_bounds__(256) ln_kernel(const bf16* __restrict__ x) {
  int row = blockIdx.x * 8 + (threadIdx.x >> 5), lane = threadIdx.x & 31;
  if (blockIdx.x == 0 && threadIdx.x < 128) { g_cnt[threadIdx.x] = 0; if (threadIdx.x == 0) PT(0); }
  for (int i = blockIdx.x * 256 + threadIdx.x; i < 2 * 64 * 640; i += 256 * 256) g_part[i] = 0.f;
  const uint32_t* xr = (const uint32_t*)(x + (size_t)row * D_);
  float v[18]; float s = 0.f;
#pragma unroll
  for (int i = 0; i < 9; i++) { float2 f = unpack_bf16(xr[lane + 32 * i]); v[2 * i] = f.x; v[2 * i + 1] = f.y; s += f.x + f.y; }
#pragma unroll
  for (int pass = 0; pass < 2; pass++) {
#pragma unroll
    for (int o = 16; o; o >>= 1) s += __shfl_xor_sync(~0u, s, o);
    float m = s * (1.f / D_), q = 0.f;
#pragma unroll
    for (int i = 0; i < 18; i++) { v[i] -= m; q += v[i] * v[i]; }
#pragma unroll
    for (int o = 16; o; o >>= 1) q += __shfl_xor_sync(~0u, q, o);
    float r = 1.f / sqrtf(q * (1.f / D_) + 1e-5f);
    uint32_t* dst = (uint32_t*)((pass == 0 ? g_xn : g_h2) + (size_t)row * D_);
    s = 0.f;
#pragma unroll
    for (int i = 0; i < 9; i++) {
      uint32_t p = pack_bf16(v[2 * i] * r, v[2 * i + 1] * r);
      dst[lane + 32 * i] = p;
      float2 f = unpack_bf16(p); v[2 * i] = f.x; v[2 * i + 1] = f.y; s += f.x + f.y;
    }
  }
}

template<int TA> __device__ __forceinline__ void wgmma_n256(float (&d)[128], uint64_t da, uint64_t db, int sc) {
  asm volatile("{\n.reg .pred p;\nsetp.ne.b32 p, %130, 0;\n"
    "wgmma.mma_async.sync.aligned.m64n256k16.f32.bf16.bf16 {%0, %1, %2, %3, %4, %5, %6, %7, %8, %9, %10, %11, %12, %13, %14, %15, %16, %17, %18, %19, %20, %21, %22, %23, %24, %25, %26, %27, %28, %29, %30, %31, %32, %33, %34, %35, %36, %37, %38, %39, %40, %41, %42, %43, %44, %45, %46, %47, %48, %49, %50, %51, %52, %53, %54, %55, %56, %57, %58, %59, %60, %61, %62, %63, %64, %65, %66, %67, %68, %69, %70, %71, %72, %73, %74, %75, %76, %77, %78, %79, %80, %81, %82, %83, %84, %85, %86, %87, %88, %89, %90, %91, %92, %93, %94, %95, %96, %97, %98, %99, %100, %101, %102, %103, %104, %105, %106, %107, %108, %109, %110, %111, %112, %113, %114, %115, %116, %117, %118, %119, %120, %121, %122, %123, %124, %125, %126, %127}, %128, %129, p, 1, 1, %131, 1;\n}\n"
    : "+f"(d[0]), "+f"(d[1]), "+f"(d[2]), "+f"(d[3]), "+f"(d[4]), "+f"(d[5]), "+f"(d[6]), "+f"(d[7]), "+f"(d[8]), "+f"(d[9]), "+f"(d[10]), "+f"(d[11]), "+f"(d[12]), "+f"(d[13]), "+f"(d[14]), "+f"(d[15]), "+f"(d[16]), "+f"(d[17]), "+f"(d[18]), "+f"(d[19]), "+f"(d[20]), "+f"(d[21]), "+f"(d[22]), "+f"(d[23]), "+f"(d[24]), "+f"(d[25]), "+f"(d[26]), "+f"(d[27]), "+f"(d[28]), "+f"(d[29]), "+f"(d[30]), "+f"(d[31]), "+f"(d[32]), "+f"(d[33]), "+f"(d[34]), "+f"(d[35]), "+f"(d[36]), "+f"(d[37]), "+f"(d[38]), "+f"(d[39]), "+f"(d[40]), "+f"(d[41]), "+f"(d[42]), "+f"(d[43]), "+f"(d[44]), "+f"(d[45]), "+f"(d[46]), "+f"(d[47]), "+f"(d[48]), "+f"(d[49]), "+f"(d[50]), "+f"(d[51]), "+f"(d[52]), "+f"(d[53]), "+f"(d[54]), "+f"(d[55]), "+f"(d[56]), "+f"(d[57]), "+f"(d[58]), "+f"(d[59]), "+f"(d[60]), "+f"(d[61]), "+f"(d[62]), "+f"(d[63]), "+f"(d[64]), "+f"(d[65]), "+f"(d[66]), "+f"(d[67]), "+f"(d[68]), "+f"(d[69]), "+f"(d[70]), "+f"(d[71]), "+f"(d[72]), "+f"(d[73]), "+f"(d[74]), "+f"(d[75]), "+f"(d[76]), "+f"(d[77]), "+f"(d[78]), "+f"(d[79]), "+f"(d[80]), "+f"(d[81]), "+f"(d[82]), "+f"(d[83]), "+f"(d[84]), "+f"(d[85]), "+f"(d[86]), "+f"(d[87]), "+f"(d[88]), "+f"(d[89]), "+f"(d[90]), "+f"(d[91]), "+f"(d[92]), "+f"(d[93]), "+f"(d[94]), "+f"(d[95]), "+f"(d[96]), "+f"(d[97]), "+f"(d[98]), "+f"(d[99]), "+f"(d[100]), "+f"(d[101]), "+f"(d[102]), "+f"(d[103]), "+f"(d[104]), "+f"(d[105]), "+f"(d[106]), "+f"(d[107]), "+f"(d[108]), "+f"(d[109]), "+f"(d[110]), "+f"(d[111]), "+f"(d[112]), "+f"(d[113]), "+f"(d[114]), "+f"(d[115]), "+f"(d[116]), "+f"(d[117]), "+f"(d[118]), "+f"(d[119]), "+f"(d[120]), "+f"(d[121]), "+f"(d[122]), "+f"(d[123]), "+f"(d[124]), "+f"(d[125]), "+f"(d[126]), "+f"(d[127])
    : "l"(da), "l"(db), "r"(sc), "n"(TA));
}

template<int TA> __device__ __forceinline__ void wgmma_n192(float (&d)[128], uint64_t da, uint64_t db, int sc) {
  asm volatile("{\n.reg .pred p;\nsetp.ne.b32 p, %98, 0;\n"
    "wgmma.mma_async.sync.aligned.m64n192k16.f32.bf16.bf16 {%0, %1, %2, %3, %4, %5, %6, %7, %8, %9, %10, %11, %12, %13, %14, %15, %16, %17, %18, %19, %20, %21, %22, %23, %24, %25, %26, %27, %28, %29, %30, %31, %32, %33, %34, %35, %36, %37, %38, %39, %40, %41, %42, %43, %44, %45, %46, %47, %48, %49, %50, %51, %52, %53, %54, %55, %56, %57, %58, %59, %60, %61, %62, %63, %64, %65, %66, %67, %68, %69, %70, %71, %72, %73, %74, %75, %76, %77, %78, %79, %80, %81, %82, %83, %84, %85, %86, %87, %88, %89, %90, %91, %92, %93, %94, %95}, %96, %97, p, 1, 1, %99, 1;\n}\n"
    : "+f"(d[0]), "+f"(d[1]), "+f"(d[2]), "+f"(d[3]), "+f"(d[4]), "+f"(d[5]), "+f"(d[6]), "+f"(d[7]), "+f"(d[8]), "+f"(d[9]), "+f"(d[10]), "+f"(d[11]), "+f"(d[12]), "+f"(d[13]), "+f"(d[14]), "+f"(d[15]), "+f"(d[16]), "+f"(d[17]), "+f"(d[18]), "+f"(d[19]), "+f"(d[20]), "+f"(d[21]), "+f"(d[22]), "+f"(d[23]), "+f"(d[24]), "+f"(d[25]), "+f"(d[26]), "+f"(d[27]), "+f"(d[28]), "+f"(d[29]), "+f"(d[30]), "+f"(d[31]), "+f"(d[32]), "+f"(d[33]), "+f"(d[34]), "+f"(d[35]), "+f"(d[36]), "+f"(d[37]), "+f"(d[38]), "+f"(d[39]), "+f"(d[40]), "+f"(d[41]), "+f"(d[42]), "+f"(d[43]), "+f"(d[44]), "+f"(d[45]), "+f"(d[46]), "+f"(d[47]), "+f"(d[48]), "+f"(d[49]), "+f"(d[50]), "+f"(d[51]), "+f"(d[52]), "+f"(d[53]), "+f"(d[54]), "+f"(d[55]), "+f"(d[56]), "+f"(d[57]), "+f"(d[58]), "+f"(d[59]), "+f"(d[60]), "+f"(d[61]), "+f"(d[62]), "+f"(d[63]), "+f"(d[64]), "+f"(d[65]), "+f"(d[66]), "+f"(d[67]), "+f"(d[68]), "+f"(d[69]), "+f"(d[70]), "+f"(d[71]), "+f"(d[72]), "+f"(d[73]), "+f"(d[74]), "+f"(d[75]), "+f"(d[76]), "+f"(d[77]), "+f"(d[78]), "+f"(d[79]), "+f"(d[80]), "+f"(d[81]), "+f"(d[82]), "+f"(d[83]), "+f"(d[84]), "+f"(d[85]), "+f"(d[86]), "+f"(d[87]), "+f"(d[88]), "+f"(d[89]), "+f"(d[90]), "+f"(d[91]), "+f"(d[92]), "+f"(d[93]), "+f"(d[94]), "+f"(d[95])
    : "l"(da), "l"(db), "r"(sc), "n"(TA));
}

struct GemmParams {
  CUtensorMap mA[4];
  CUtensorMap mB[6];
  const bf16* x; const bf16* b1; const bf16* b2; bf16* out;
  int stride, kid;
  int wait_at_end;
  uint16_t job[960];
};
constexpr int NSTAGE = 4, STAGE_BYTES = 49152;
constexpr int GEMM_SMEM = NSTAGE * STAGE_BYTES + 8 * 2048 + 256 + 1024;

__device__ __forceinline__ uint64_t mkdesc(uint32_t addr, uint32_t lbo, uint32_t sbo) {
  return (uint64_t)((addr & 0x3FFFF) >> 4) | ((uint64_t)(lbo >> 4) << 16) | ((uint64_t)(sbo >> 4) << 32) | (1ull << 62);
}
__device__ __forceinline__ float gelu_tanh(float u) {
  float z = 0.7978845608028654f * (u + 0.044715f * u * u * u);
  float e = __expf(2.f * z);
  float th = 1.f - __fdividef(2.f, e + 1.f);
  return 0.5f * u * (1.f + th);
}
template <int BN, int TA>
__device__ __forceinline__ void gemm_mainloop(float (&d)[128], int kiters, uint32_t sbase, uint32_t fullb, uint32_t emptyb_l, uint32_t emptyb_r,
                                              int wg, int& stage, uint32_t& phase, bool elect) {
  int prev = -1;
  for (int k = 0; k < kiters; k++) {
    mbar_wait(fullb + stage * 8, phase);
    uint32_t a = sbase + stage * STAGE_BYTES + wg * 8192, b = sbase + stage * STAGE_BYTES + 16384;
    asm volatile("wgmma.fence.sync.aligned;" ::: "memory");
#pragma unroll
    for (int kk = 0; kk < 4; kk++) {
      uint64_t da = TA ? mkdesc(a + kk * 2048, 8192, 1024) : mkdesc(a + kk * 32, 16, 1024);
      uint64_t db = mkdesc(b + kk * 2048, 8192, 1024);
      if constexpr (BN == 256) wgmma_n256<TA>(d, da, db, (k | kk) != 0); else wgmma_n192<TA>(d, da, db, (k | kk) != 0);
    }
    asm volatile("wgmma.commit_group.sync.aligned;" ::: "memory");
    asm volatile("wgmma.wait_group.sync.aligned 1;" ::: "memory");
    if (prev >= 0 && elect) { mbar_arrive_remote(emptyb_l + prev * 8); mbar_arrive_remote(emptyb_r + prev * 8); }
    prev = stage;
    if (++stage == NSTAGE) { stage = 0; phase ^= 1; }
  }
  asm volatile("wgmma.wait_group.sync.aligned 0;" ::: "memory");
  if (elect) { mbar_arrive_remote(emptyb_l + prev * 8); mbar_arrive_remote(emptyb_r + prev * 8); }
}
template <int BN, class F>
__device__ __forceinline__ void store_tile(const float (&d)[128], uint32_t stg, bf16* dst, int ld, int lane, F f) {
#pragma unroll
  for (int c = 0; c < BN / 64; c++) {
#pragma unroll
    for (int i = 0; i < 8; i += 2) {
      const int o = c * 32 + i * 4;
      uint32_t r0 = f(d[o], d[o + 1], 0, c * 64 + i * 8), r1 = f(d[o + 2], d[o + 3], 1, c * 64 + i * 8);
      uint32_t r2 = f(d[o + 4], d[o + 5], 0, c * 64 + i * 8 + 8), r3 = f(d[o + 6], d[o + 7], 1, c * 64 + i * 8 + 8);
      int m = lane >> 3, row = (m & 1) * 8 + (lane & 7), ch = (i + (m >> 1)) ^ (row & 7);
      asm volatile("stmatrix.sync.aligned.m8n8.x4.shared.b16 [%0], {%1,%2,%3,%4};" ::"r"(stg + row * 128 + ch * 16), "r"(r0), "r"(r1), "r"(r2), "r"(r3) : "memory");
    }
    __syncwarp();
#pragma unroll
    for (int j = 0; j < 4; j++) {
      int idx = lane + 32 * j, row = idx >> 3, ch = idx & 7;
      uint4 v;
      asm volatile("ld.shared.v4.u32 {%0,%1,%2,%3}, [%4];" : "=r"(v.x), "=r"(v.y), "=r"(v.z), "=r"(v.w) : "r"(stg + row * 128 + ((ch ^ (row & 7)) * 16)));
      *(uint4*)(dst + (size_t)row * ld + c * 64 + ch * 8) = v;
    }
    __syncwarp();
  }
}

__device__ __forceinline__ void attn_unit(int seg, int h, uint8_t* sm, int lane) {
  const int g = lane >> 2, t = lane & 3;
  const uint32_t sv = smem_u32(sm);
  const size_t tok0 = (size_t)seg * 32;
  for (int i = lane; i < 40 * 16; i += 32) {
    int r = i >> 4, c = i & 15;
    const bf16* src = (r < 8 ? g_vm + ((size_t)seg * 8 + r) * HD_ : g_v + (tok0 + r - 8) * HD_) + h * 128 + c * 8;
    cp16(sv + r * 256 + ((c ^ (r & 7)) * 16), src);
  }
  for (int i = lane; i < 8 * 16; i += 32) *(uint4*)(sm + 40 * 256 + i * 16) = make_uint4(0, 0, 0, 0);
  asm volatile("cp.async.commit_group;" ::: "memory");
  float s[2][5][4];
#pragma unroll
  for (int m = 0; m < 2; m++)
#pragma unroll
    for (int n = 0; n < 5; n++) { s[m][n][0] = s[m][n][1] = s[m][n][2] = s[m][n][3] = 0.f; }
#pragma unroll
  for (int j = 0; j < 4; j++) {
    uint4 qa[2][2], kb[5];
#pragma unroll
    for (int m = 0; m < 2; m++)
#pragma unroll
      for (int hh = 0; hh < 2; hh++) qa[m][hh] = *(const uint4*)(g_q + (tok0 + m * 16 + hh * 8 + g) * HD_ + h * 128 + j * 32 + t * 8);
#pragma unroll
    for (int n = 0; n < 5; n++)
      kb[n] = *(const uint4*)((n == 0 ? g_km + ((size_t)seg * 8 + g) * HD_ : g_k + (tok0 + (n - 1) * 8 + g) * HD_) + h * 128 + j * 32 + t * 8);
#pragma unroll
    for (int m = 0; m < 2; m++) {
      uint32_t a0[4] = {qa[m][0].x, qa[m][1].x, qa[m][0].y, qa[m][1].y}, a1[4] = {qa[m][0].z, qa[m][1].z, qa[m][0].w, qa[m][1].w};
#pragma unroll
      for (int n = 0; n < 5; n++) { mma16816(s[m][n], a0, kb[n].x, kb[n].y); mma16816(s[m][n], a1, kb[n].z, kb[n].w); }
    }
  }
  const float sc = 0.08838834764831845f * 1.4426950408889634f;
  uint32_t pa[2][3][4];
#pragma unroll
  for (int m = 0; m < 2; m++) {
    float inv[2];
#pragma unroll
    for (int hh = 0; hh < 2; hh++) {
      int qi = 8 + m * 16 + hh * 8 + g;
      float mx = -INFINITY;
#pragma unroll
      for (int n = 0; n < 5; n++)
#pragma unroll
        for (int e = 0; e < 2; e++) { float& z = s[m][n][hh * 2 + e]; z = (n * 8 + t * 2 + e <= qi) ? z * sc : -INFINITY; mx = fmaxf(mx, z); }
      mx = fmaxf(mx, __shfl_xor_sync(~0u, mx, 1)); mx = fmaxf(mx, __shfl_xor_sync(~0u, mx, 2));
      float sum = 0.f;
#pragma unroll
      for (int n = 0; n < 5; n++)
#pragma unroll
        for (int e = 0; e < 2; e++) { float& z = s[m][n][hh * 2 + e]; z = exp2f(z - mx); sum += z; }
      sum += __shfl_xor_sync(~0u, sum, 1); sum += __shfl_xor_sync(~0u, sum, 2);
      inv[hh] = 1.f / sum;
    }
#pragma unroll
    for (int kk = 0; kk < 3; kk++) {
      pa[m][kk][0] = pack_bf16(s[m][2 * kk][0] * inv[0], s[m][2 * kk][1] * inv[0]);
      pa[m][kk][1] = pack_bf16(s[m][2 * kk][2] * inv[1], s[m][2 * kk][3] * inv[1]);
      if (kk < 2) {
        pa[m][kk][2] = pack_bf16(s[m][2 * kk + 1][0] * inv[0], s[m][2 * kk + 1][1] * inv[0]);
        pa[m][kk][3] = pack_bf16(s[m][2 * kk + 1][2] * inv[1], s[m][2 * kk + 1][3] * inv[1]);
      } else { pa[m][kk][2] = 0; pa[m][kk][3] = 0; }
    }
  }
  asm volatile("cp.async.wait_group 0;" ::: "memory");
  __syncwarp();
  uint32_t ov[2][16][2];
#pragma unroll
  for (int np = 0; np < 8; np++) {
    float o[2][2][4] = {};
#pragma unroll
    for (int kk = 0; kk < 3; kk++) {
      uint32_t b[4];
      int mi = lane >> 3, r = kk * 16 + (mi & 1) * 8 + (lane & 7), c = np * 2 + (mi >> 1);
      ldsm4t(b, sv + r * 256 + ((c ^ (r & 7)) * 16));
#pragma unroll
      for (int m = 0; m < 2; m++) { mma16816(o[m][0], pa[m][kk], b[0], b[1]); mma16816(o[m][1], pa[m][kk], b[2], b[3]); }
    }
#pragma unroll
    for (int m = 0; m < 2; m++)
#pragma unroll
      for (int q = 0; q < 2; q++) { ov[m][np * 2 + q][0] = pack_bf16(o[m][q][0], o[m][q][1]); ov[m][np * 2 + q][1] = pack_bf16(o[m][q][2], o[m][q][3]); }
  }
  __syncwarp();
#pragma unroll
  for (int m = 0; m < 2; m++)
#pragma unroll
    for (int n = 0; n < 16; n++)
#pragma unroll
      for (int hh = 0; hh < 2; hh++) {
        int r = m * 16 + hh * 8 + g;
        *(uint32_t*)(sm + r * 256 + ((n ^ (r & 7)) * 16) + t * 4) = ov[m][n][hh];
      }
  __syncwarp();
#pragma unroll
  for (int i = 0; i < 16; i++) {
    int idx = lane + 32 * i, r = idx >> 4, c = idx & 15;
    *(uint4*)(g_o + (tok0 + r) * HD_ + h * 128 + c * 8) = *(const uint4*)(sm + r * 256 + ((c ^ (r & 7)) * 16));
  }
}

__global__ void __launch_bounds__(384, 1) gemm_kernel(const __grid_constant__ GemmParams p) {
  extern __shared__ uint8_t smem_raw[];
  const uint32_t sbase = (smem_u32(smem_raw) + 1023) & ~1023u;
  const uint32_t stg0 = sbase + NSTAGE * STAGE_BYTES, fullb = stg0 + 8 * 2048, emptyb = fullb + 64;
  const uint32_t rank = cluster_rank();
  const int wg = __shfl_sync(~0u, (int)(threadIdx.x >> 7), 0), lane = threadIdx.x & 31;
  const int cl = blockIdx.x >> 1;
  if (threadIdx.x == 0) {
    for (int i = 0; i < NSTAGE; i++) { mbar_init(fullb + i * 8, 1); mbar_init(emptyb + i * 8, 4); }
    asm volatile("fence.mbarrier_init.release.cluster;" ::: "memory");
  }
  cluster_sync();
  if (blockIdx.x == 0 && threadIdx.x == 0) PT(1 + p.kid * 2);
  const uint16_t* jobs = p.job + cl * p.stride;
  if (wg == 0) {
    asm volatile("setmaxnreg.dec.sync.aligned.u32 40;");
    if (threadIdx.x == 0) {
      int stage = 0; uint32_t phase = 1;
      for (int j = 0; j < p.stride; j++) {
        uint32_t job = jobs[j];
        if (job == 0xFFFF) break;
        int type = job >> 12, m = (job >> 6) & 63, n = job & 63;
        int row0 = m * 256 + rank * 128;
        int bn = type < 3 ? 256 : 192;
        if (type == 6) {
          for (int k = 0; k < NSTAGE; k++) {
            mbar_wait_cl(emptyb + stage * 8, phase);
            asm volatile("mbarrier.arrive.shared::cta.b64 _, [%0];" ::"r"(fullb + stage * 8) : "memory");
            if (++stage == NSTAGE) { stage = 0; phase ^= 1; }
          }
          continue;
        }
        int kit = type < 3 ? 9 : (type == 3 ? 32 : (type == 4 ? 72 : (type == 5 ? 64 : 8)));
        int k0 = 0;
        if (type == 7) { k0 = (n / 3) * 8; n = n % 3; type = 5; }
        else if (type == 5) wait_cnt(&g_cnt[16 + m], 32);
        const CUtensorMap* ma = &p.mA[type < 3 ? 0 : type - 2];
        const CUtensorMap* mb = &p.mB[type];
        bool ta = (type == 3 || type == 4);
        if (type >= 4) {
          if (type == 4) wait_cnt(&g_cnt[0], 108);
          asm volatile("fence.proxy.async;" ::: "memory");
        }
        for (int k = k0; k < k0 + kit; k++) {
          mbar_wait_cl(emptyb + stage * 8, phase);
          uint32_t fb = fullb + stage * 8, a = sbase + stage * STAGE_BYTES, b = a + 16384;
          mbar_expect(fb, 16384 + bn * 128);
          if (ta) { tma2d(a, ma, row0, k * 64, fb); tma2d(a + 8192, ma, row0 + 64, k * 64, fb); }
          else tma2d(a, ma, k * 64, row0, fb);
          for (int i = 0; i < bn / 64; i++) tma2d_mc(b + i * 8192 + rank * 4096, mb, n * bn + i * 64, k * 64 + rank * 32, fb, (uint16_t)3);
          if (++stage == NSTAGE) { stage = 0; phase ^= 1; }
        }
      }
    }
    __syncwarp();
    if (p.wait_at_end) pdl_wait();
    cluster_sync();
  } else {
    asm volatile("setmaxnreg.inc.sync.aligned.u32 232;");
    const int cw = wg - 1, warp = __shfl_sync(~0u, (int)(threadIdx.x >> 5) & 3, 0);
    const uint32_t eb_l = mapa(emptyb, rank), eb_r = mapa(emptyb, rank ^ 1);
    const uint32_t stg = stg0 + (cw * 4 + warp) * 2048;
    const bool elect = (threadIdx.x & 127) == 0;
    const int g = lane >> 2, t = lane & 3;
    int stage = 0; uint32_t phase = 0;
    float d[128];
    for (int j = 0; j < p.stride; j++) {
      uint32_t job = jobs[j];
      if (job == 0xFFFF) break;
      int type = job >> 12, m = (job >> 6) & 63, n = job & 63;
      int row0 = m * 256 + rank * 128 + cw * 64 + warp * 16;
      if (type < 3) {
        gemm_mainloop<256, 0>(d, 9, sbase, fullb, eb_l, eb_r, cw, stage, phase, elect);
        bf16* dst = (type == 0 ? g_q : (type == 1 ? g_k : g_v)) + (size_t)row0 * HD_ + n * 256;
        store_tile<256>(d, stg, dst, HD_, lane, [](float a, float b, int, int) { return pack_bf16(a, b); });
        __threadfence();
        asm volatile("bar.sync %0, 256;" ::"r"(1) : "memory");
        if (threadIdx.x == 128) atomicAdd(&g_cnt[(type ? 8 : 40) + m], 1);
      } else if (type == 3) {
        gemm_mainloop<192, 1>(d, 32, sbase, fullb, eb_l, eb_r, cw, stage, phase, elect);
        float bb[2] = {__bfloat162float(p.b1[row0 + g]), __bfloat162float(p.b1[row0 + g + 8])};
        store_tile<192>(d, stg, g_ut + (size_t)row0 * D_ + n * 192, D_, lane,
                        [&](float a, float b, int h, int) { return pack_bf16(gelu_tanh(a + bb[h]), gelu_tanh(b + bb[h])); });
        __threadfence();
        asm volatile("fence.proxy.async;" ::: "memory");
        asm volatile("bar.sync %0, 256;" ::"r"(1) : "memory");
        if (threadIdx.x == 128) atomicAdd(&g_cnt[0], 1);
      } else if (type == 4) {
        gemm_mainloop<192, 1>(d, 72, sbase, fullb, eb_l, eb_r, cw, stage, phase, elect);
        float bb[2] = {__bfloat162float(p.b2[row0 + g]), __bfloat162float(p.b2[row0 + g + 8])};
#pragma unroll
        for (int i = 0; i < 24; i++)
#pragma unroll
          for (int h = 0; h < 2; h++) {
            size_t off = (size_t)(row0 + g + h * 8) * D_ + n * 192 + i * 8 + t * 2;
            float2 xv = unpack_bf16(*(const uint32_t*)(p.x + off));
            *(float2*)(g_yb + off) = make_float2(d[i * 4 + h * 2] + bb[h] + xv.x, d[i * 4 + h * 2 + 1] + bb[h] + xv.y);
          }
        __threadfence();
        asm volatile("bar.sync %0, 256;" ::"r"(1) : "memory");
        if (threadIdx.x == 128) atomicAdd(&g_cnt[24 + m], 1);
      } else if (type == 6) {
        const int st0 = stage;
        for (int k = 0; k < NSTAGE; k++) { mbar_wait(fullb + stage * 8, phase); if (++stage == NSTAGE) { stage = 0; phase ^= 1; } }
        const int seg = m * 8 + (n >> 1), w8 = cw * 4 + warp;
        if (lane == 0) { wait_cnt(&g_cnt[40 + m], 32); wait_cnt(&g_cnt[64 + seg], 64); }
        __syncwarp();
        attn_unit(seg, (n & 1) * 16 + rank * 8 + w8, smem_raw + (sbase - smem_u32(smem_raw)) + w8 * 12288, lane);
        __threadfence();
        asm volatile("fence.proxy.async;" ::: "memory");
        asm volatile("bar.sync %0, 256;" ::"r"(1) : "memory");
        if (elect) for (int k = 0; k < NSTAGE; k++) { mbar_arrive_remote(eb_l + k * 8); mbar_arrive_remote(eb_r + k * 8); }
        if (threadIdx.x == 128) atomicAdd(&g_cnt[16 + m], 1);
        (void)st0;
#pragma unroll
        for (int i = 0; i < 128; i++) d[i] = 0.f;
      } else if (type == 7) {
        const int nt = n % 3;
        gemm_mainloop<192, 0>(d, 8, sbase, fullb, eb_l, eb_r, cw, stage, phase, elect);
#pragma unroll
        for (int i = 0; i < 24; i++)
#pragma unroll
          for (int h = 0; h < 2; h++)
            atomicAdd((float2*)(g_yb + (size_t)(row0 + g + h * 8) * D_ + nt * 192 + i * 8 + t * 2), make_float2(d[i * 4 + h * 2], d[i * 4 + h * 2 + 1]));
        __threadfence();
        asm volatile("bar.sync %0, 256;" ::"r"(1) : "memory");
        volatile uint32_t* lastf = (volatile uint32_t*)(smem_raw + (emptyb + 64 - smem_u32(smem_raw)));
        if (threadIdx.x == 128) { *lastf = atomicAdd(&g_cnt[48 + ((m - 6) * 3 + nt) * 2 + rank], 1); __threadfence(); }
        asm volatile("bar.sync %0, 256;" ::"r"(1) : "memory");
        if (*lastf == 7) {
          const int r0 = m * 256 + rank * 128;
          for (int i = threadIdx.x - 128; i < 128 * 48; i += 256) {
            int rr = i / 48, cc = (i - rr * 48) * 4;
            size_t off = (size_t)(r0 + rr) * D_ + nt * 192 + cc;
            float4 y = __ldcg((const float4*)(g_yb + off));
            *(uint2*)(p.out + off) = make_uint2(pack_bf16(y.x, y.y), pack_bf16(y.z, y.w));
          }
        }
        asm volatile("bar.sync %0, 256;" ::"r"(1) : "memory");
      } else {
        gemm_mainloop<192, 0>(d, 64, sbase, fullb, eb_l, eb_r, cw, stage, phase, elect);
        if (lane == 0) wait_cnt(&g_cnt[24 + m], 6);
        __syncwarp();
        const float* yb = g_yb + (size_t)(row0 + g) * D_ + n * 192 + t * 2;
        store_tile<192>(d, stg, p.out + (size_t)row0 * D_ + n * 192, D_, lane,
                        [&](float a, float b, int h, int c) { float2 y = *(const float2*)(yb + h * 8 * D_ + c); return pack_bf16(a + y.x, b + y.y); });
      }
      if (blockIdx.x == 0 && threadIdx.x == 128) PT(2048 + p.kid * 64 + j);
    }
    if (blockIdx.x == 0 && threadIdx.x == 128) PT(2 + p.kid * 2);
    if (p.wait_at_end) pdl_wait();
    cluster_sync();
  }
}

__global__ void __launch_bounds__(128) attn_kernel(int seg0) {
  __shared__ __align__(128) uint8_t sm[4][48 * 256];
  const int warp = threadIdx.x >> 5, id = blockIdx.x * 4 + warp;
  if (blockIdx.x == 0 && threadIdx.x == 0) PT(9);
  attn_unit(seg0 + (id >> 5), id & 31, sm[warp], threadIdx.x & 31);
}
constexpr int CH_WV = 0;
constexpr int CH_MEM = CH_WV + 73728;
constexpr int CH_KB = CH_MEM + 9216;
constexpr int CH_VB = CH_KB + 12288;
constexpr int CH_WO = CH_VB + 12288;
constexpr int CH_Q = CH_WO + 81920;
constexpr int CH_R1 = CH_Q + 1024;
constexpr int CH_SC = CH_R1 + 4096;
constexpr int CH_OF = CH_SC + 3584;
constexpr int CH_R2 = CH_OF + 8192;
constexpr int CH_BAR = CH_R2 + 12288;
constexpr int CHAIN_SMEM = CH_BAR + 64 + 1024;
#define POLL_DELAY 250
__device__ __forceinline__ void st_async1(uint32_t a, uint32_t v, uint32_t bar) { asm volatile("st.async.weak.shared::cluster.mbarrier::complete_tx::bytes.b32 [%0], %1, [%2];" ::"r"(a), "r"(v), "r"(bar) : "memory"); }
__device__ __forceinline__ void st_async2(uint32_t a, uint32_t v0, uint32_t v1, uint32_t bar) { asm volatile("st.async.weak.shared::cluster.mbarrier::complete_tx::bytes.v2.b32 [%0], {%1, %2}, [%3];" ::"r"(a), "r"(v0), "r"(v1), "r"(bar) : "memory"); }
__device__ __forceinline__ uint4 lds128(uint32_t a) { uint4 v; asm volatile("ld.shared.v4.u32 {%0,%1,%2,%3}, [%4];" : "=r"(v.x), "=r"(v.y), "=r"(v.z), "=r"(v.w) : "r"(a) : "memory"); return v; }
__device__ __forceinline__ void sts128f(uint32_t a, const float (&c)[4]) { asm volatile("st.shared.v4.f32 [%0], {%1,%2,%3,%4};" ::"r"(a), "f"(c[0]), "f"(c[1]), "f"(c[2]), "f"(c[3]) : "memory"); }
__device__ __forceinline__ void sts32(uint32_t a, uint32_t v) { asm volatile("st.shared.u32 [%0], %1;" ::"r"(a), "r"(v) : "memory"); }
__device__ __forceinline__ void mbar_wait_b(uint32_t b, uint32_t parity) {
  uint32_t ok; int n = 0;
  do { asm volatile("{\n.reg .pred p;\nmbarrier.try_wait.parity.shared::cta.b64 p, [%1], %2;\nselp.u32 %0, 1, 0, p;\n}" : "=r"(ok) : "r"(b), "r"(parity) : "memory"); } while (!ok && ++n < (1 << 20));
}
__device__ __forceinline__ uint32_t mapa_v(uint32_t a, uint32_t r) { uint32_t o; asm volatile("mapa.shared::cluster.u32 %0, %1, %2;" : "=r"(o) : "r"(a), "r"(r)); return o; }
__device__ __forceinline__ uint32_t tid_v() { uint32_t o; asm volatile("mov.u32 %0, %%tid.x;" : "=r"(o)); return o; }
template <int ACC>
__device__ __forceinline__ void wg_rs(float (&d)[4], const uint32_t (&a)[4], uint32_t dlo) {
  uint64_t db = ((uint64_t)16 << 32) | dlo;
  asm volatile("{\n.reg .pred p;\nsetp.ne.b32 p, %9, 0;\nwgmma.mma_async.sync.aligned.m64n8k16.f32.bf16.bf16 {%0,%1,%2,%3}, {%4,%5,%6,%7}, %8, p, 1, 1, 0;\n}"
               : "+f"(d[0]), "+f"(d[1]), "+f"(d[2]), "+f"(d[3]) : "r"(a[0]), "r"(a[1]), "r"(a[2]), "r"(a[3]), "l"(db), "n"(ACC));
}
template <int N>
__device__ __forceinline__ void wg_wait(float (&d)[N][4]) {
  asm volatile("wgmma.commit_group.sync.aligned;\nwgmma.wait_group.sync.aligned 0;" ::: "memory");
#pragma unroll
  for (int i = 0; i < N; i++) asm volatile("" : "+f"(d[i][0]), "+f"(d[i][1]), "+f"(d[i][2]), "+f"(d[i][3]) :: "memory");
}
#define BAR_ALL() asm volatile("bar.sync 0, 256;" ::: "memory")

__global__ void __launch_bounds__(256, 1) chain_kernel(const bf16* __restrict__ mem0, const bf16* __restrict__ Wq, const bf16* __restrict__ Wk,
                                                       const bf16* __restrict__ Wv, const bf16* __restrict__ Wo) {
  extern __shared__ uint8_t smem_raw[];
  const uint32_t sb = (smem_u32(smem_raw) + 1023) & ~1023u;
  const int tid = threadIdx.x, warp = __shfl_sync(~0u, tid >> 5, 0), wgi = __shfl_sync(~0u, tid >> 7, 0), lane = tid & 31, g = lane >> 2, t = lane & 3;
  const uint32_t r = cluster_rank();
  const int c = blockIdx.x >> 3, h = 4 * c + (r >> 1), j0 = h * 128 + (r & 1) * 64;
  const uint32_t bm = sb + CH_BAR, bs = bm + 8, bo = bm + 16;
  pdl_launch();
  if (blockIdx.x == 0 && tid == 0) PT(7);
  if (tid == 0) { mbar_init(bm, 1); mbar_init(bs, 1); mbar_init(bo, 1); asm volatile("fence.mbarrier_init.release.cluster;" ::: "memory"); }
  const int mi = lane >> 3, l7 = lane & 7;
  for (int i = tid; i < 576 * 8; i += 256) {
    int row = i >> 3, ch = i & 7;
    cp16(sb + CH_WV + row * 128 + ((ch ^ (row & 7)) * 16), Wq + (size_t)row * HD_ + j0 + ch * 8);
    cp16(sb + CH_WO + row * 128 + ((ch ^ (row & 7)) * 16), Wk + (size_t)row * HD_ + j0 + ch * 8);
  }
  asm volatile("cp.async.commit_group;\ncp.async.wait_group 0;" ::: "memory");
  BAR_ALL();
  uint32_t w1[36][4];
#pragma unroll
  for (int i = 0; i < 36; i++) {
    int row = i * 16 + (mi >> 1) * 8 + l7, ch = ((warp & 3) * 2 + (mi & 1)) ^ (row & 7);
    ldsm4t(w1[i], sb + (wgi ? CH_WO : CH_WV) + row * 128 + ch * 16);
  }
  BAR_ALL();
  for (int i = tid; i < 512 * 10; i += 256) {
    int row = i / 10, ch = i - row * 10;
    cp16(sb + CH_WV + row * 176 + ch * 16, Wo + (size_t)(c * 512 + row) * D_ + (ch < 8 ? r * 64 + ch * 8 : 512 + (r >> 1) * 16 + (ch - 8) * 8));
  }
  asm volatile("cp.async.commit_group;\ncp.async.wait_group 0;" ::: "memory");
  BAR_ALL();
  const int kperm = 2 * ((mi >> 1) * 2 + (l7 >> 2)) + (l7 & 1) + 8 * ((l7 >> 1) & 1);
  for (int i = 0; i < 16; i++) {
    uint32_t a[4];
    ldsm4t(a, sb + CH_WV + ((wgi * 16 + i) * 16 + kperm) * 176 + ((warp & 3) * 2 + (mi & 1)) * 16);
    asm volatile("st.shared.v4.u32 [%0], {%1,%2,%3,%4};" ::"r"(sb + CH_WO + 8192 + (warp * 16 + i) * 512 + lane * 16), "r"(a[0]), "r"(a[1]), "r"(a[2]), "r"(a[3]) : "memory");
  }
  for (int u = warp; u < 16; u += 8) {
    uint32_t a[4];
    ldsm4t(a, sb + CH_WV + (((r & 1) * 16 + u) * 16 + kperm) * 176 + (8 + (mi & 1)) * 16);
    asm volatile("st.shared.v4.u32 [%0], {%1,%2,%3,%4};" ::"r"(sb + CH_WO + u * 512 + lane * 16), "r"(a[0]), "r"(a[1]), "r"(a[2]), "r"(a[3]) : "memory");
  }
  BAR_ALL();
  for (int i = tid; i < 576 * 8; i += 256) {
    int row = i >> 3, ch = i & 7;
    cp16(sb + CH_WV + row * 128 + ((ch ^ (row & 7)) * 16), Wv + (size_t)row * HD_ + j0 + ch * 8);
  }
  for (int i = tid; i < 8 * 72; i += 256) {
    int row = i / 72, ch = i - row * 72;
    cp16(sb + CH_MEM + ch * 128 + row * 16, mem0 + row * D_ + ch * 8);
  }
  for (int i = tid; i < 4 * 64; i += 256) {
    int b = i >> 6, o = i & 63;
    asm volatile("st.shared.v4.u32 [%0], {%1,%1,%1,%1};" ::"r"(sb + CH_KB + b * 6144 + 40 * 128 + o * 16), "r"(0) : "memory");
  }
  auto prefetch_kv = [&](int s, int tid) {
    if ((s & 7) == 0) { if ((tid & 31) == 0) wait_cnt(&g_cnt[8 + (s >> 3)], 64); __syncwarp(); }
#pragma unroll
    for (int i = 0; i < 2; i++) {
      int u = tid + i * 256, which = u >> 8, row = (u & 255) >> 3, ch = u & 7;
      const bf16* src = (which ? g_v : g_k) + (size_t)(s * 32 + row) * HD_ + j0 + ch * 8;
      cp16(sb + (which ? CH_VB : CH_KB) + (s & 1) * 6144 + (row + 8) * 128 + ((ch ^ (row & 7)) * 16), src);
    }
    asm volatile("cp.async.commit_group;" ::: "memory");
  };
  prefetch_kv(0, tid);
  asm volatile("cp.async.wait_group 0;" ::: "memory");
  asm volatile("fence.proxy.async.shared::cta;" ::: "memory");
  BAR_ALL();
  cluster_sync();
  const uint32_t dsb = ((sb & 0x3FFFF) >> 4) | (8u << 16);
  if (blockIdx.x == 0 && tid == 0) PT(10);
#define CP(i) if (blockIdx.x == 0 && lane == 0 && warp == (((i) == 5 || (i) == 7) ? 4 : 0)) PC(64 + s * 16 + (i))
  for (int s = 0; s < NSEG; s++) {
    const int tid = tid_v(), lane = tid & 31, g = lane >> 2, t = lane & 3, mi = lane >> 3, l7 = lane & 7;
    CP(0);
    const uint32_t par = s & 1, kb = sb + CH_KB + par * 6144, vb = sb + CH_VB + par * 6144;
    if (s > 0) mbar_wait_b(bm, par ^ 1);
    CP(1);
    if (tid == 0 && s < NSEG - 1) { mbar_expect(bs, 2560); mbar_expect(bo, 8192); mbar_expect(bm, 9216); }
    auto phase1 = [&]() {
      float pa[3][4] = {};
#pragma unroll
      for (int i = 0; i < 36; i += 2) {
        uint32_t b[4];
        ldsm4(b, sb + CH_MEM + i * 256 + mi * 128 + l7 * 16);
        mma16816(pa[i % 3], w1[i], b[0], b[1]); mma16816(pa[(i + 1) % 3], w1[i + 1], b[2], b[3]);
      }
      CP(2);
      uint32_t b0 = movm(pack_bf16(pa[0][0] + pa[1][0] + pa[2][0], pa[0][1] + pa[1][1] + pa[2][1]));
      uint32_t b1 = movm(pack_bf16(pa[0][2] + pa[1][2] + pa[2][2], pa[0][3] + pa[1][3] + pa[2][3]));
      uint32_t dst = (wgi ? kb : sb + CH_Q) + g * 128 + t * 4;
      sts32(dst + ((((warp & 3) * 2) ^ g) * 16), b0); sts32(dst + ((((warp & 3) * 2 + 1) ^ g) * 16), b1);
      if (wgi) { uint32_t* gp = (uint32_t*)(g_km + ((size_t)s * 8 + g) * HD_ + j0 + (warp & 3) * 16 + t * 2); gp[0] = b0; gp[4] = b1; }
      asm volatile("cp.async.wait_group 0;" ::: "memory");
    };
    if (wgi == 0) {
      phase1();
      BAR_ALL();
      CP(4);
      if (s + 1 < NSEG) { prefetch_kv(s + 1, tid); asm volatile("bar.sync 6, 224;" ::: "memory"); }
      float va[4][4];
      asm volatile("wgmma.fence.sync.aligned;" ::: "memory");
      const uint32_t dwa = (((sb + CH_WV) & 0x3FFFF) >> 4) | ((8192u >> 4) << 16);
#pragma unroll
      for (int ks = 0; ks < 36; ks++) {
        uint64_t da = ((uint64_t)(0x40000000u | (1024 >> 4)) << 32) | (dwa + ks * 128), db = ((uint64_t)16 << 32) | (dsb + ((CH_MEM + ks * 256) >> 4));
        if (ks < 4)
          asm volatile("{\n.reg .pred p;\nsetp.ne.b32 p, 0, 0;\nwgmma.mma_async.sync.aligned.m64n8k16.f32.bf16.bf16 {%0,%1,%2,%3}, %4, %5, p, 1, 1, 1, 0;\n}"
                       : "=f"(va[ks & 3][0]), "=f"(va[ks & 3][1]), "=f"(va[ks & 3][2]), "=f"(va[ks & 3][3]) : "l"(da), "l"(db));
        else
          asm volatile("{\n.reg .pred p;\nsetp.ne.b32 p, 1, 0;\nwgmma.mma_async.sync.aligned.m64n8k16.f32.bf16.bf16 {%0,%1,%2,%3}, %4, %5, p, 1, 1, 1, 0;\n}"
                       : "+f"(va[ks & 3][0]), "+f"(va[ks & 3][1]), "+f"(va[ks & 3][2]), "+f"(va[ks & 3][3]) : "l"(da), "l"(db));
      }
      wg_wait(va);
      CP(6);
      uint32_t b0 = movm(pack_bf16(va[0][0] + va[1][0] + va[2][0] + va[3][0], va[0][1] + va[1][1] + va[2][1] + va[3][1]));
      uint32_t b1 = movm(pack_bf16(va[0][2] + va[1][2] + va[2][2] + va[3][2], va[0][3] + va[1][3] + va[2][3] + va[3][3]));
      sts32(vb + g * 128 + t * 4 + (((warp * 2) ^ g) * 16), b0); sts32(vb + g * 128 + t * 4 + (((warp * 2 + 1) ^ g) * 16), b1);
      uint32_t* gp = (uint32_t*)(g_vm + ((size_t)s * 8 + g) * HD_ + j0 + warp * 16 + t * 2); gp[0] = b0; gp[4] = b1;
      asm volatile("bar.arrive 7, 256;" ::: "memory");
    } else {
      phase1();
      BAR_ALL();
      if (warp == 7 && lane == 0 && s > 0) { __threadfence(); atomicAdd(&g_cnt[64 + s - 1], 1); }
      if (warp < 7 && s < NSEG - 1) {
        const int mt = warp - 4;
        const uint32_t sc_l = mapa_v(sb + CH_SC + (r & 1) * 1792, r), sc_r = mapa_v(sb + CH_SC + (r & 1) * 1792, r ^ 1), bs_l = mapa_v(bs, r), bs_r = mapa_v(bs, r ^ 1);
        float sa[4][4] = {};
#pragma unroll
        for (int kp = 0; kp < 2; kp++) {
          uint32_t b[4], a0[4], a1[4];
          ldsm4(b, sb + CH_Q + l7 * 128 + (((kp * 4 + mi) ^ l7) * 16));
          int row = mt * 16 + (mi & 1) * 8 + l7;
          ldsm4(a0, kb + row * 128 + (((kp * 4 + (mi >> 1)) ^ l7) * 16));
          ldsm4(a1, kb + row * 128 + (((kp * 4 + 2 + (mi >> 1)) ^ l7) * 16));
          mma16816(sa[2 * kp], a0, b[0], b[1]); mma16816(sa[2 * kp + 1], a1, b[2], b[3]);
        }
        asm volatile("bar.arrive 6, 224;" :: "f"(sa[0][0]), "f"(sa[1][0]), "f"(sa[2][0]), "f"(sa[3][0]) : "memory");
#pragma unroll
        for (int e = 0; e < 4; e++) {
          uint32_t off = ((2 * t + (e & 1)) * 56 + mt * 16 + (e >> 1) * 8 + g) * 4, v = __float_as_uint((sa[0][e] + sa[1][e]) + (sa[2][e] + sa[3][e]));
          if (mt < 2 || e < 2) { st_async1(sc_r + off, v, bs_r); st_async1(sc_l + off, v, bs_l); }
        }
        CP(5);
      }
      if (s < NSEG - 1) {
        prefetch_kv(s + 1, tid);
        const int w3 = warp & 3;
        uint32_t vt[3][4];
#pragma unroll
        for (int kk = 1; kk < 3; kk++) { int row = kk * 16 + (mi >> 1) * 8 + l7; ldsm4t(vt[kk], vb + row * 128 + (((w3 * 2 + (mi & 1)) ^ l7) * 16)); }
        mbar_wait_b(bs, par);
        CP(7);
        float z[10]; float mx = -INFINITY;
        const float scl = 0.08838834764831845f * 1.4426950408889634f;
#pragma unroll
        for (int i = 0; i < 5; i++) {
          float2 u0, u1; uint32_t a = sb + CH_SC + (g * 56 + i * 8 + 2 * t) * 4;
          asm volatile("ld.shared.v2.f32 {%0,%1}, [%2];" : "=f"(u0.x), "=f"(u0.y) : "r"(a) : "memory");
          asm volatile("ld.shared.v2.f32 {%0,%1}, [%2];" : "=f"(u1.x), "=f"(u1.y) : "r"(a + 1792) : "memory");
          z[2 * i] = (u0.x + u1.x) * scl; z[2 * i + 1] = (u0.y + u1.y) * scl;
        }
        mx = fmaxf(fmaxf(fmaxf(z[0], z[1]), fmaxf(z[2], z[3])), fmaxf(fmaxf(fmaxf(z[4], z[5]), fmaxf(z[6], z[7])), fmaxf(z[8], z[9])));
        mx = fmaxf(mx, __shfl_xor_sync(~0u, mx, 1)); mx = fmaxf(mx, __shfl_xor_sync(~0u, mx, 2));
        uint32_t pb[5];
#pragma unroll
        for (int i = 0; i < 5; i++) pb[i] = pack_bf16(exp2f(z[2 * i] - mx), exp2f(z[2 * i + 1] - mx));
        const uint32_t ones[4] = {0x3F803F80u, 0x3F803F80u, 0x3F803F80u, 0x3F803F80u};
        float o0[4] = {}, o1[4] = {}, o2[4] = {}, s0[4] = {}, s1[4] = {}, s2[4] = {};
        mma16816(s0, ones, pb[0], pb[1]);
        mma16816(o1, vt[1], pb[2], pb[3]); mma16816(s1, ones, pb[2], pb[3]);
        mma16816(o2, vt[2], pb[4], 0u); mma16816(s2, ones, pb[4], 0u);
        asm volatile("bar.sync 7, 256;" ::: "memory");
        ldsm4t(vt[0], vb + ((mi >> 1) * 8 + l7) * 128 + (((w3 * 2 + (mi & 1)) ^ l7) * 16));
        mma16816(o0, vt[0], pb[0], pb[1]);
        const float i0 = __fdividef(1.f, s0[0] + s1[0] + s2[0]), i1 = __fdividef(1.f, s0[1] + s1[1] + s2[1]);
        uint32_t f0 = movm(pack_bf16((o0[0] + o1[0] + o2[0]) * i0, (o0[1] + o1[1] + o2[1]) * i1));
        uint32_t f1 = movm(pack_bf16((o0[2] + o1[2] + o2[2]) * i0, (o0[3] + o1[3] + o2[3]) * i1));
        const int ks = r * 4 + w3;
        const uint32_t off = CH_OF + ks * 256 + (t >> 1) * 128 + g * 16 + (t & 1) * 8;
        const uint32_t cl0 = mapa_v(sb, 0), clstep = mapa_v(sb, 1) - cl0;
#pragma unroll
        for (int d = 0; d < 8; d++) st_async2(cl0 + d * clstep + off, f0, f1, cl0 + d * clstep + CH_BAR + 16);
      } else asm volatile("bar.sync 7, 256;" ::: "memory");
    }
    if (s == NSEG - 1) break;
    CP(8);
    uint32_t wo[16][4];
#pragma unroll
    for (int i = 0; i < 16; i++) { uint4 v = lds128(sb + CH_WO + 8192 + (warp * 16 + i) * 512 + lane * 16); wo[i][0] = v.x; wo[i][1] = v.y; wo[i][2] = v.z; wo[i][3] = v.w; }
    mbar_wait_b(bo, par);
    CP(9);
    const uint32_t tag = ((s >> 1) + 1) & 1;
    float* pbase = g_part + (size_t)par * 8 * 5120 + lane * 4;
    auto put = [&](int slot, const float (&a)[4]) {
      asm volatile("st.relaxed.gpu.global.v4.b32 [%0], {%1,%2,%3,%4};" ::"l"(pbase + c * 5120 + slot * 128), "r"((__float_as_uint(a[0]) & ~1u) | tag),
                   "r"((__float_as_uint(a[1]) & ~1u) | tag), "r"((__float_as_uint(a[2]) & ~1u) | tag), "r"((__float_as_uint(a[3]) & ~1u) | tag) : "memory");
    };
    {
      float acc[4][4];
      asm volatile("wgmma.fence.sync.aligned;" ::: "memory");
      const uint32_t dof = dsb + ((CH_OF >> 4) + wgi * 256);
#pragma unroll
      for (int i = 0; i < 16; i++) { if (i < 4) wg_rs<0>(acc[i & 3], wo[i], dof + i * 16); else wg_rs<1>(acc[i & 3], wo[i], dof + i * 16); }
      wg_wait(acc);
#pragma unroll
      for (int e = 0; e < 4; e++) acc[0][e] = (acc[0][e] + acc[1][e]) + (acc[2][e] + acc[3][e]);
      CP(10);
      const int w3 = warp & 3;
      if (wgi) {
        sts128f(sb + CH_R2 + w3 * 512 + lane * 16, acc[0]);
        asm volatile("bar.arrive %0, 64;" ::"r"(1 + w3) : "memory");
        if (w3 < 2) {
          float ex[2][4] = {};
#pragma unroll
          for (int i = 0; i < 8; i += 2) {
            uint32_t b[4]; ldsm4(b, sb + CH_OF + ((r & 1) * 16 + w3 * 8 + i) * 256 + mi * 128 + l7 * 16);
            uint4 v0 = lds128(sb + CH_WO + (w3 * 8 + i) * 512 + lane * 16), v1 = lds128(sb + CH_WO + (w3 * 8 + i + 1) * 512 + lane * 16);
            uint32_t a0[4] = {v0.x, v0.y, v0.z, v0.w}, a1[4] = {v1.x, v1.y, v1.z, v1.w};
            mma16816(ex[0], a0, b[0], b[1]); mma16816(ex[1], a1, b[2], b[3]);
          }
#pragma unroll
          for (int e = 0; e < 4; e++) ex[0][e] += ex[1][e];
          if (w3 == 1) { sts128f(sb + CH_R2 + 4 * 512 + lane * 16, ex[0]); asm volatile("bar.arrive 5, 64;" ::: "memory"); }
          else {
            asm volatile("bar.sync 5, 64;" ::: "memory");
            uint4 v = lds128(sb + CH_R2 + 4 * 512 + lane * 16);
            ex[0][0] += __uint_as_float(v.x); ex[0][1] += __uint_as_float(v.y); ex[0][2] += __uint_as_float(v.z); ex[0][3] += __uint_as_float(v.w);
            put(32 + r, ex[0]);
          }
        }
      } else {
        asm volatile("bar.sync %0, 64;" ::"r"(1 + w3) : "memory");
        uint4 v = lds128(sb + CH_R2 + w3 * 512 + lane * 16);
        acc[0][0] += __uint_as_float(v.x); acc[0][1] += __uint_as_float(v.y); acc[0][2] += __uint_as_float(v.z); acc[0][3] += __uint_as_float(v.w);
        put(r * 4 + w3, acc[0]);
      }
    }
    CP(11);
    if (warp < 4 || warp == 6) { long long t0 = clock64(); while (clock64() - t0 < POLL_DELAY) {} }
    if (warp < 4) {
      const float* pb = pbase + (r * 4 + warp) * 128;
      uint4 v[8]; int n = 0; bool ok;
      do {
        ok = true;
#pragma unroll
        for (int i = 0; i < 8; i++) asm volatile("ld.relaxed.gpu.global.v4.b32 {%0,%1,%2,%3}, [%4];" : "=r"(v[i].x), "=r"(v[i].y), "=r"(v[i].z), "=r"(v[i].w) : "l"(pb + i * 5120) : "memory");
#pragma unroll
        for (int i = 0; i < 8; i++) ok = ok && (((v[i].x & v[i].y & v[i].z & v[i].w & 1u) == tag) && (((v[i].x | v[i].y | v[i].z | v[i].w) & 1u) == tag));
      } while (!ok && ++n < (1 << 18));
      float m[4] = {};
#pragma unroll
      for (int i = 0; i < 8; i++) { m[0] += __uint_as_float(v[i].x); m[1] += __uint_as_float(v[i].y); m[2] += __uint_as_float(v[i].z); m[3] += __uint_as_float(v[i].w); }
      __syncwarp();
      CP(12);
      uint32_t b0 = movm(pack_bf16(m[0], m[1])), b1 = movm(pack_bf16(m[2], m[3]));
      const uint32_t off = CH_MEM + (r * 4 + warp) * 256 + g * 16 + t * 4;
      const uint32_t cl0 = mapa_v(sb, 0), clstep = mapa_v(sb, 1) - cl0;
#pragma unroll
      for (int d = 0; d < 8; d++) { st_async1(cl0 + d * clstep + off, b0, cl0 + d * clstep + CH_BAR); st_async1(cl0 + d * clstep + off + 128, b1, cl0 + d * clstep + CH_BAR); }
    } else if (warp == 6) {
      const float* pb = pbase - lane * 4 + (32 + (r & ~1u)) * 128 + lane * 4 + (r & 1) * 2;
      uint2 v[16]; int n = 0; bool ok;
      do {
        ok = true;
#pragma unroll
        for (int i = 0; i < 16; i++) asm volatile("ld.relaxed.gpu.global.v2.b32 {%0,%1}, [%2];" : "=r"(v[i].x), "=r"(v[i].y) : "l"(pb + (i >> 1) * 5120 + (i & 1) * 128) : "memory");
#pragma unroll
        for (int i = 0; i < 16; i++) ok = ok && ((v[i].x & v[i].y & 1u) == tag) && (((v[i].x | v[i].y) & 1u) == tag);
      } while (!ok && ++n < (1 << 18));
      float m0 = 0.f, m1 = 0.f;
#pragma unroll
      for (int i = 0; i < 16; i++) { m0 += __uint_as_float(v[i].x); m1 += __uint_as_float(v[i].y); }
      __syncwarp();
      uint32_t b0 = movm(pack_bf16(m0, m1));
      const uint32_t off = CH_MEM + (32 + (r >> 1)) * 256 + (r & 1) * 128 + g * 16 + t * 4;
      const uint32_t cl0 = mapa_v(sb, 0), clstep = mapa_v(sb, 1) - cl0;
#pragma unroll
      for (int d = 0; d < 8; d++) st_async1(cl0 + d * clstep + off, b0, cl0 + d * clstep + CH_BAR);
    }
  }
  if (blockIdx.x == 0 && tid == 0) PT(8);
  cluster_sync();
}
typedef CUresult (*EncodeFn)(CUtensorMap*, CUtensorMapDataType, cuuint32_t, void*, const cuuint64_t*, const cuuint64_t*, const cuuint32_t*, const cuuint32_t*,
                             CUtensorMapInterleave, CUtensorMapSwizzle, CUtensorMapL2promotion, CUtensorMapFloatOOBfill);
static EncodeFn g_enc;
static void mkmap(CUtensorMap* m, const void* ptr, int rows, int cols, int boxc, int boxr) {
  cuuint64_t dims[2] = {(cuuint64_t)cols, (cuuint64_t)rows}, strides[1] = {(cuuint64_t)cols * 2};
  cuuint32_t box[2] = {(cuuint32_t)boxc, (cuuint32_t)boxr}, es[2] = {1, 1};
  g_enc(m, CU_TENSOR_MAP_DATA_TYPE_BFLOAT16, 2, (void*)ptr, dims, strides, box, es, CU_TENSOR_MAP_INTERLEAVE_NONE, CU_TENSOR_MAP_SWIZZLE_128B,
        CU_TENSOR_MAP_L2_PROMOTION_L2_256B, CU_TENSOR_MAP_FLOAT_OOB_FILL_NONE);
}
constexpr double CH_T0 = 20.0, CH_DT = 3.8;
static inline uint16_t mkjob(int type, int m, int n) { return (uint16_t)(type << 12 | m << 6 | n); }
static void schedule_side(GemmParams& p, const uint16_t* base, int nb, int ncl) {
  static const double cost[8] = {7.3, 7.3, 7.3, 19.0, 47.0, 33.0, 9.0, 5.0};
  double t[66] = {}; int cnt[66] = {};
  p.stride = 960 / ncl;
  for (int i = 0; i < 960; i++) p.job[i] = 0xFFFF;
  double g2_end = 0, q_end[8] = {}, g3_end[8] = {}, at_end[8] = {}; int qn[8] = {}, g3n[8] = {}, atn[8] = {};
  int bi = 0, ai = 0, gi = 0;
  while (bi < nb || ai < 96 || gi < 18) {
    int b = 0;
    for (int c = 1; c < ncl; c++) if (t[c] < t[b] || (t[c] == t[b] && cnt[c] < cnt[b])) b = c;
    const double inf = 1e30;
    int am = ai >> 4, gm = gi / 3;
    double ra = ai < 96 && qn[am] == 16 ? (q_end[am] > CH_T0 + CH_DT * (am * 8 + ((ai & 15) >> 1) + 2) ? q_end[am] : CH_T0 + CH_DT * (am * 8 + ((ai & 15) >> 1) + 2)) : inf;
    double rg = gi < 18 && atn[gm] == 16 && g3n[gm] == 3 ? at_end[gm] : inf;
    uint16_t job; double start = t[b];
    if (rg <= t[b] || (bi >= nb && rg < inf && (rg <= ra || (gi < 18 && ai >= 96)))) { job = mkjob(5, gm, gi % 3); gi++; if (rg > start) start = rg; }
    else if (ra <= t[b] || bi >= nb) { job = mkjob(6, am, ai & 15); ai++; if (ra > start) start = ra; }
    else job = base[bi++];
    int ty = job >> 12, m = (job >> 6) & 63;
    if (ty == 4 && start < g2_end) start = g2_end;
    t[b] = start + cost[ty];
    if (ty == 3 && t[b] > g2_end) g2_end = t[b];
    if (ty == 0) { qn[m]++; if (t[b] > q_end[m]) q_end[m] = t[b]; }
    if (ty == 4) { g3n[m]++; if (t[b] > g3_end[m]) g3_end[m] = t[b]; }
    if (ty == 6) { atn[m]++; if (t[b] > at_end[m]) at_end[m] = t[b]; }
    p.job[b * p.stride + cnt[b]++] = job;
  }
}
template <class... A>
static void launch(void (*k)(A...), int grid, int block, int smem, int cluster, bool pdl, A... a) {
  cudaLaunchConfig_t c = {};
  c.gridDim = grid; c.blockDim = block; c.dynamicSmemBytes = smem; c.stream = cudaStreamPerThread;
  cudaLaunchAttribute at[2]; int n = 0;
  if (cluster > 1) { at[n].id = cudaLaunchAttributeClusterDimension; at[n].val.clusterDim.x = cluster; at[n].val.clusterDim.y = 1; at[n].val.clusterDim.z = 1; n++; }
  if (pdl) { at[n].id = cudaLaunchAttributeProgrammaticStreamSerialization; at[n].val.programmaticStreamSerializationAllowed = 1; n++; }
  c.attrs = at; c.numAttrs = n;
  cudaLaunchKernelEx(&c, k, a...);
}

extern "C" void kernel_launch(void* const* d_in, const int* in_sizes, int n_in, void* d_out, int out_size) {
  const bf16 *x = (const bf16*)d_in[0], *mem0 = (const bf16*)d_in[1], *Wq = (const bf16*)d_in[2], *Wk = (const bf16*)d_in[3], *Wv = (const bf16*)d_in[4],
             *Wo = (const bf16*)d_in[5], *w1 = (const bf16*)d_in[8], *b1 = (const bf16*)d_in[9], *w2 = (const bf16*)d_in[10], *b2 = (const bf16*)d_in[11];
  static bool init = false;
  static GemmParams side, post;
  if (!init) {
    init = true;
    cudaDriverEntryPointQueryResult qr;
    cudaGetDriverEntryPoint("cuTensorMapEncodeTiled", (void**)&g_enc, cudaEnableDefault, &qr);
    void *xn, *h2, *o, *ut;
    cudaGetSymbolAddress(&xn, g_xn); cudaGetSymbolAddress(&h2, g_h2); cudaGetSymbolAddress(&o, g_o); cudaGetSymbolAddress(&ut, g_ut);
    GemmParams b = {};
    mkmap(&b.mA[0], xn, S_, D_, 64, 128); mkmap(&b.mA[1], w1, S_, F_, 64, 64); mkmap(&b.mA[2], w2, F_, S_, 64, 64); mkmap(&b.mA[3], o, S_, HD_, 64, 128);
    mkmap(&b.mB[0], Wq, D_, HD_, 64, 32); mkmap(&b.mB[1], Wk, D_, HD_, 64, 32); mkmap(&b.mB[2], Wv, D_, HD_, 64, 32);
    mkmap(&b.mB[3], h2, S_, D_, 64, 32); mkmap(&b.mB[4], ut, F_, D_, 64, 32); mkmap(&b.mB[5], Wo, HD_, D_, 64, 32);
    b.x = x; b.b1 = b1; b.b2 = b2; b.out = (bf16*)d_out;
    side = b; post = b; side.kid = 1; post.kid = 2;
    static uint16_t jl[1024]; int n = 0;
    for (int m = 0; m < 8; m++) {
      for (int j = 0; j < 16; j++) { jl[n++] = mkjob(1, m, j); jl[n++] = mkjob(2, m, j); }
      if (m >= 2) for (int j = 0; j < 16; j++) jl[n++] = mkjob(0, m - 2, j);
    }
    for (int m = 0; m < 18; m++) for (int j = 0; j < 3; j++) jl[n++] = mkjob(3, m, j);
    for (int m = 0; m < 8; m++) for (int j = 0; j < 3; j++) jl[n++] = mkjob(4, m, j);
    for (int m = 6; m < 8; m++) for (int j = 0; j < 16; j++) jl[n++] = mkjob(0, m, j);
    schedule_side(side, jl, n, 34);
    side.wait_at_end = 1;
    post.stride = 1;
    for (int i = 0; i < 960; i++) post.job[i] = 0xFFFF;
    for (int i = 0; i < 48; i++) post.job[i] = mkjob(7, 6 + i / 24, i % 24);
    cudaFuncSetAttribute(gemm_kernel, cudaFuncAttributeMaxDynamicSharedMemorySize, GEMM_SMEM);
    cudaFuncSetAttribute(chain_kernel, cudaFuncAttributeMaxDynamicSharedMemorySize, CHAIN_SMEM);
  }
  launch(ln_kernel, 256, 256, 0, 1, false, x);
  launch(chain_kernel, 64, 256, CHAIN_SMEM, 8, false, mem0, Wq, Wk, Wv, Wo);
  launch(gemm_kernel, 68, 384, GEMM_SMEM, 2, true, side);
  launch(attn_kernel, 128, 128, 0, 1, false, 48);
  launch(gemm_kernel, 96, 384, GEMM_SMEM, 2, false, post);
}
```

```cpp
#include <cuda_runtime.h>
#include <cuda_bf16.h>
#include <cuda.h>
#include <stdint.h>

typedef __nv_bfloat16 bf16;
constexpr int S_ = 2048, D_ = 576, HD_ = 4096, F_ = 4608, NSEG = 64;

__device__ bf16 g_xn[S_ * D_];
__device__ bf16 g_h2[S_ * D_];
__device__ bf16 g_q[S_ * HD_];
__device__ bf16 g_k[S_ * HD_];
__device__ bf16 g_v[S_ * HD_];
__device__ bf16 g_o[S_ * HD_];
__device__ bf16 g_km[NSEG * 8 * HD_];
__device__ bf16 g_vm[NSEG * 8 * HD_];
__device__ bf16 g_ut[F_ * D_];
__device__ float g_yb[S_ * D_];
__device__ float g_part[2 * 8 * 8 * 5 * 32 * 4];
__device__ unsigned int g_cnt[192];

#define PT(i)
#define PC(i)
__device__ __forceinline__ uint32_t smem_u32(const void* p) { return (uint32_t)__cvta_generic_to_shared(p); }
__device__ __forceinline__ void mbar_init(uint32_t b, uint32_t c) { asm volatile("mbarrier.init.shared::cta.b64 [%0], %1;" ::"r"(b), "r"(c)); }
__device__ __forceinline__ void mbar_expect(uint32_t b, uint32_t bytes) { asm volatile("mbarrier.arrive.expect_tx.shared::cta.b64 _, [%0], %1;" ::"r"(b), "r"(bytes) : "memory"); }
__device__ __forceinline__ void mbar_wait(uint32_t b, uint32_t parity) {
  uint32_t ok;
  do { asm volatile("{\n.reg .pred p;\nmbarrier.try_wait.parity.shared::cta.b64 p, [%1], %2;\nselp.u32 %0, 1, 0, p;\n}" : "=r"(ok) : "r"(b), "r"(parity) : "memory"); } while (!ok);
}
__device__ __forceinline__ void mbar_wait_cl(uint32_t b, uint32_t parity) {
  uint32_t ok;
  do { asm volatile("{\n.reg .pred p;\nmbarrier.try_wait.parity.shared::cta.b64 p, [%1], %2;\nselp.u32 %0, 1, 0, p;\n}" : "=r"(ok) : "r"(b), "r"(parity) : "memory"); } while (!ok);
}
__device__ __forceinline__ uint32_t mapa(uint32_t a, uint32_t r) { uint32_t o; asm("mapa.shared::cluster.u32 %0, %1, %2;" : "=r"(o) : "r"(a), "r"(r)); return o; }
__device__ __forceinline__ void mbar_arrive_remote(uint32_t remote_b) { asm volatile("mbarrier.arrive.shared::cluster.b64 _, [%0];" ::"r"(remote_b) : "memory"); }
__device__ __forceinline__ uint32_t cluster_rank() { uint32_t r; asm("mov.u32 %0, %%cluster_ctarank;" : "=r"(r)); return r; }
__device__ __forceinline__ void cluster_sync() { asm volatile("barrier.cluster.arrive.release.aligned;\nbarrier.cluster.wait.acquire.aligned;" ::: "memory"); }
__device__ __forceinline__ void tma2d(uint32_t dst, const CUtensorMap* m, int c0, int c1, uint32_t bar) {
  asm volatile("cp.async.bulk.tensor.2d.shared::cluster.global.mbarrier::complete_tx::bytes [%0], [%1, {%3, %4}], [%2];"
               ::"r"(dst), "l"(m), "r"(bar), "r"(c0), "r"(c1) : "memory");
}
__device__ __forceinline__ void tma2d_mc(uint32_t dst, const CUtensorMap* m, int c0, int c1, uint32_t bar, uint16_t mask) {
  asm volatile("cp.async.bulk.tensor.2d.shared::cluster.global.mbarrier::complete_tx::bytes.multicast::cluster [%0], [%1, {%3, %4}], [%2], %5;"
               ::"r"(dst), "l"(m), "r"(bar), "r"(c0), "r"(c1), "h"(mask) : "memory");
}
__device__ __forceinline__ uint32_t pack_bf16(float a, float b) { __nv_bfloat162 t = __floats2bfloat162_rn(a, b); return *(uint32_t*)&t; }
__device__ __forceinline__ float2 unpack_bf16(uint32_t u) { return __bfloat1622float2(*(__nv_bfloat162*)&u); }
__device__ __forceinline__ void mma16816(float (&c)[4], const uint32_t (&a)[4], uint32_t b0, uint32_t b1) {
  asm volatile("mma.sync.aligned.m16n8k16.row.col.f32.bf16.bf16.f32 {%0,%1,%2,%3},{%4,%5,%6,%7},{%8,%9},{%0,%1,%2,%3};"
               : "+f"(c[0]), "+f"(c[1]), "+f"(c[2]), "+f"(c[3]) : "r"(a[0]), "r"(a[1]), "r"(a[2]), "r"(a[3]), "r"(b0), "r"(b1));
}
__device__ __forceinline__ void ldsm4(uint32_t (&r)[4], uint32_t a) { asm volatile("ldmatrix.sync.aligned.m8n8.x4.shared.b16 {%0,%1,%2,%3},[%4];" : "=r"(r[0]), "=r"(r[1]), "=r"(r[2]), "=r"(r[3]) : "r"(a) : "memory"); }
__device__ __forceinline__ void ldsm4t(uint32_t (&r)[4], uint32_t a) { asm volatile("ldmatrix.sync.aligned.m8n8.x4.trans.shared.b16 {%0,%1,%2,%3},[%4];" : "=r"(r[0]), "=r"(r[1]), "=r"(r[2]), "=r"(r[3]) : "r"(a) : "memory"); }
__device__ __forceinline__ uint32_t movm(uint32_t a) { uint32_t o; asm volatile("movmatrix.sync.aligned.m8n8.trans.b16 %0, %1;" : "=r"(o) : "r"(a)); return o; }
__device__ __forceinline__ void cp16(uint32_t dst, const void* src) { asm volatile("cp.async.cg.shared.global [%0], [%1], 16;" ::"r"(dst), "l"(src) : "memory"); }
__device__ __forceinline__ void pdl_wait() { asm volatile("griddepcontrol.wait;" ::: "memory"); }
__device__ __forceinline__ void pdl_launch() { asm volatile("griddepcontrol.launch_dependents;" ::: "memory"); }

__device__ __forceinline__ void wait_cnt(const unsigned int* c, unsigned int target) {
  uint32_t v; int n = 0;
  do { asm volatile("ld.acquire.gpu.global.u32 %0, [%1];" : "=r"(v) : "l"(c) : "memory"); if (v >= target) break; __nanosleep(64); } while (++n < (1 << 22));
}
__global__ void __launch_bounds__(256) ln_kernel(const bf16* __restrict__ x) {
  int row = blockIdx.x * 8 + (threadIdx.x >> 5), lane = threadIdx.x & 31;
  if (blockIdx.x == 0 && threadIdx.x < 192) { g_cnt[threadIdx.x] = 0; if (threadIdx.x == 0) PT(0); }
  for (int i = blockIdx.x * 256 + threadIdx.x; i < 2 * 64 * 640; i += 256 * 256) g_part[i] = 0.f;
  const uint32_t* xr = (const uint32_t*)(x + (size_t)row * D_);
  float v[18]; float s = 0.f;
#pragma unroll
  for (int i = 0; i < 9; i++) { float2 f = unpack_bf16(xr[lane + 32 * i]); v[2 * i] = f.x; v[2 * i + 1] = f.y; s += f.x + f.y; }
#pragma unroll
  for (int pass = 0; pass < 2; pass++) {
#pragma unroll
    for (int o = 16; o; o >>= 1) s += __shfl_xor_sync(~0u, s, o);
    float m = s * (1.f / D_), q = 0.f;
#pragma unroll
    for (int i = 0; i < 18; i++) { v[i] -= m; q += v[i] * v[i]; }
#pragma unroll
    for (int o = 16; o; o >>= 1) q += __shfl_xor_sync(~0u, q, o);
    float r = 1.f / sqrtf(q * (1.f / D_) + 1e-5f);
    uint32_t* dst = (uint32_t*)((pass == 0 ? g_xn : g_h2) + (size_t)row * D_);
    s = 0.f;
#pragma unroll
    for (int i = 0; i < 9; i++) {
      uint32_t p = pack_bf16(v[2 * i] * r, v[2 * i + 1] * r);
      dst[lane + 32 * i] = p;
      float2 f = unpack_bf16(p); v[2 * i] = f.x; v[2 * i + 1] = f.y; s += f.x + f.y;
    }
  }
}

template<int TA> __device__ __forceinline__ void wgmma_n256(float (&d)[128], uint64_t da, uint64_t db, int sc) {
  asm volatile("{\n.reg .pred p;\nsetp.ne.b32 p, %130, 0;\n"
    "wgmma.mma_async.sync.aligned.m64n256k16.f32.bf16.bf16 {%0, %1, %2, %3, %4, %5, %6, %7, %8, %9, %10, %11, %12, %13, %14, %15, %16, %17, %18, %19, %20, %21, %22, %23, %24, %25, %26, %27, %28, %29, %30, %31, %32, %33, %34, %35, %36, %37, %38, %39, %40, %41, %42, %43, %44, %45, %46, %47, %48, %49, %50, %51, %52, %53, %54, %55, %56, %57, %58, %59, %60, %61, %62, %63, %64, %65, %66, %67, %68, %69, %70, %71, %72, %73, %74, %75, %76, %77, %78, %79, %80, %81, %82, %83, %84, %85, %86, %87, %88, %89, %90, %91, %92, %93, %94, %95, %96, %97, %98, %99, %100, %101, %102, %103, %104, %105, %106, %107, %108, %109, %110, %111, %112, %113, %114, %115, %116, %117, %118, %119, %120, %121, %122, %123, %124, %125, %126, %127}, %128, %129, p, 1, 1, %131, 1;\n}\n"
    : "+f"(d[0]), "+f"(d[1]), "+f"(d[2]), "+f"(d[3]), "+f"(d[4]), "+f"(d[5]), "+f"(d[6]), "+f"(d[7]), "+f"(d[8]), "+f"(d[9]), "+f"(d[10]), "+f"(d[11]), "+f"(d[12]), "+f"(d[13]), "+f"(d[14]), "+f"(d[15]), "+f"(d[16]), "+f"(d[17]), "+f"(d[18]), "+f"(d[19]), "+f"(d[20]), "+f"(d[21]), "+f"(d[22]), "+f"(d[23]), "+f"(d[24]), "+f"(d[25]), "+f"(d[26]), "+f"(d[27]), "+f"(d[28]), "+f"(d[29]), "+f"(d[30]), "+f"(d[31]), "+f"(d[32]), "+f"(d[33]), "+f"(d[34]), "+f"(d[35]), "+f"(d[36]), "+f"(d[37]), "+f"(d[38]), "+f"(d[39]), "+f"(d[40]), "+f"(d[41]), "+f"(d[42]), "+f"(d[43]), "+f"(d[44]), "+f"(d[45]), "+f"(d[46]), "+f"(d[47]), "+f"(d[48]), "+f"(d[49]), "+f"(d[50]), "+f"(d[51]), "+f"(d[52]), "+f"(d[53]), "+f"(d[54]), "+f"(d[55]), "+f"(d[56]), "+f"(d[57]), "+f"(d[58]), "+f"(d[59]), "+f"(d[60]), "+f"(d[61]), "+f"(d[62]), "+f"(d[63]), "+f"(d[64]), "+f"(d[65]), "+f"(d[66]), "+f"(d[67]), "+f"(d[68]), "+f"(d[69]), "+f"(d[70]), "+f"(d[71]), "+f"(d[72]), "+f"(d[73]), "+f"(d[74]), "+f"(d[75]), "+f"(d[76]), "+f"(d[77]), "+f"(d[78]), "+f"(d[79]), "+f"(d[80]), "+f"(d[81]), "+f"(d[82]), "+f"(d[83]), "+f"(d[84]), "+f"(d[85]), "+f"(d[86]), "+f"(d[87]), "+f"(d[88]), "+f"(d[89]), "+f"(d[90]), "+f"(d[91]), "+f"(d[92]), "+f"(d[93]), "+f"(d[94]), "+f"(d[95]), "+f"(d[96]), "+f"(d[97]), "+f"(d[98]), "+f"(d[99]), "+f"(d[100]), "+f"(d[101]), "+f"(d[102]), "+f"(d[103]), "+f"(d[104]), "+f"(d[105]), "+f"(d[106]), "+f"(d[107]), "+f"(d[108]), "+f"(d[109]), "+f"(d[110]), "+f"(d[111]), "+f"(d[112]), "+f"(d[113]), "+f"(d[114]), "+f"(d[115]), "+f"(d[116]), "+f"(d[117]), "+f"(d[118]), "+f"(d[119]), "+f"(d[120]), "+f"(d[121]), "+f"(d[122]), "+f"(d[123]), "+f"(d[124]), "+f"(d[125]), "+f"(d[126]), "+f"(d[127])
    : "l"(da), "l"(db), "r"(sc), "n"(TA));
}

template<int TA> __device__ __forceinline__ void wgmma_n192(float (&d)[128], uint64_t da, uint64_t db, int sc) {
  asm volatile("{\n.reg .pred p;\nsetp.ne.b32 p, %98, 0;\n"
    "wgmma.mma_async.sync.aligned.m64n192k16.f32.bf16.bf16 {%0, %1, %2, %3, %4, %5, %6, %7, %8, %9, %10, %11, %12, %13, %14, %15, %16, %17, %18, %19, %20, %21, %22, %23, %24, %25, %26, %27, %28, %29, %30, %31, %32, %33, %34, %35, %36, %37, %38, %39, %40, %41, %42, %43, %44, %45, %46, %47, %48, %49, %50, %51, %52, %53, %54, %55, %56, %57, %58, %59, %60, %61, %62, %63, %64, %65, %66, %67, %68, %69, %70, %71, %72, %73, %74, %75, %76, %77, %78, %79, %80, %81, %82, %83, %84, %85, %86, %87, %88, %89, %90, %91, %92, %93, %94, %95}, %96, %97, p, 1, 1, %99, 1;\n}\n"
    : "+f"(d[0]), "+f"(d[1]), "+f"(d[2]), "+f"(d[3]), "+f"(d[4]), "+f"(d[5]), "+f"(d[6]), "+f"(d[7]), "+f"(d[8]), "+f"(d[9]), "+f"(d[10]), "+f"(d[11]), "+f"(d[12]), "+f"(d[13]), "+f"(d[14]), "+f"(d[15]), "+f"(d[16]), "+f"(d[17]), "+f"(d[18]), "+f"(d[19]), "+f"(d[20]), "+f"(d[21]), "+f"(d[22]), "+f"(d[23]), "+f"(d[24]), "+f"(d[25]), "+f"(d[26]), "+f"(d[27]), "+f"(d[28]), "+f"(d[29]), "+f"(d[30]), "+f"(d[31]), "+f"(d[32]), "+f"(d[33]), "+f"(d[34]), "+f"(d[35]), "+f"(d[36]), "+f"(d[37]), "+f"(d[38]), "+f"(d[39]), "+f"(d[40]), "+f"(d[41]), "+f"(d[42]), "+f"(d[43]), "+f"(d[44]), "+f"(d[45]), "+f"(d[46]), "+f"(d[47]), "+f"(d[48]), "+f"(d[49]), "+f"(d[50]), "+f"(d[51]), "+f"(d[52]), "+f"(d[53]), "+f"(d[54]), "+f"(d[55]), "+f"(d[56]), "+f"(d[57]), "+f"(d[58]), "+f"(d[59]), "+f"(d[60]), "+f"(d[61]), "+f"(d[62]), "+f"(d[63]), "+f"(d[64]), "+f"(d[65]), "+f"(d[66]), "+f"(d[67]), "+f"(d[68]), "+f"(d[69]), "+f"(d[70]), "+f"(d[71]), "+f"(d[72]), "+f"(d[73]), "+f"(d[74]), "+f"(d[75]), "+f"(d[76]), "+f"(d[77]), "+f"(d[78]), "+f"(d[79]), "+f"(d[80]), "+f"(d[81]), "+f"(d[82]), "+f"(d[83]), "+f"(d[84]), "+f"(d[85]), "+f"(d[86]), "+f"(d[87]), "+f"(d[88]), "+f"(d[89]), "+f"(d[90]), "+f"(d[91]), "+f"(d[92]), "+f"(d[93]), "+f"(d[94]), "+f"(d[95])
    : "l"(da), "l"(db), "r"(sc), "n"(TA));
}

struct GemmParams {
  CUtensorMap mA[4];
  CUtensorMap mB[6];
  const bf16* x; const bf16* b1; const bf16* b2; bf16* out;
  int stride, kid;
  int wait_at_end;
  uint16_t job[960];
};
constexpr int NSTAGE = 4, STAGE_BYTES = 49152;
constexpr int GEMM_SMEM = NSTAGE * STAGE_BYTES + 8 * 2048 + 256 + 1024;

__device__ __forceinline__ uint64_t mkdesc(uint32_t addr, uint32_t lbo, uint32_t sbo) {
  return (uint64_t)((addr & 0x3FFFF) >> 4) | ((uint64_t)(lbo >> 4) << 16) | ((uint64_t)(sbo >> 4) << 32) | (1ull << 62);
}
__device__ __forceinline__ float gelu_tanh(float u) {
  float z = 0.7978845608028654f * (u + 0.044715f * u * u * u);
  float e = __expf(2.f * z);
  float th = 1.f - __fdividef(2.f, e + 1.f);
  return 0.5f * u * (1.f + th);
}
template <int BN, int TA>
__device__ __forceinline__ void gemm_mainloop(float (&d)[128], int kiters, uint32_t sbase, uint32_t fullb, uint32_t emptyb_l, uint32_t emptyb_r,
                                              int wg, int& stage, uint32_t& phase, bool elect) {
  int prev = -1;
  for (int k = 0; k < kiters; k++) {
    mbar_wait(fullb + stage * 8, phase);
    uint32_t a = sbase + stage * STAGE_BYTES + wg * 8192, b = sbase + stage * STAGE_BYTES + 16384;
    asm volatile("wgmma.fence.sync.aligned;" ::: "memory");
#pragma unroll
    for (int kk = 0; kk < 4; kk++) {
      uint64_t da = TA ? mkdesc(a + kk * 2048, 8192, 1024) : mkdesc(a + kk * 32, 16, 1024);
      uint64_t db = mkdesc(b + kk * 2048, 8192, 1024);
      if constexpr (BN == 256) wgmma_n256<TA>(d, da, db, (k | kk) != 0); else wgmma_n192<TA>(d, da, db, (k | kk) != 0);
    }
    asm volatile("wgmma.commit_group.sync.aligned;" ::: "memory");
    asm volatile("wgmma.wait_group.sync.aligned 1;" ::: "memory");
    if (prev >= 0 && elect) { mbar_arrive_remote(emptyb_l + prev * 8); mbar_arrive_remote(emptyb_r + prev * 8); }
    prev = stage;
    if (++stage == NSTAGE) { stage = 0; phase ^= 1; }
  }
  asm volatile("wgmma.wait_group.sync.aligned 0;" ::: "memory");
  if (elect) { mbar_arrive_remote(emptyb_l + prev * 8); mbar_arrive_remote(emptyb_r + prev * 8); }
}
template <int BN, class F>
__device__ __forceinline__ void store_tile(const float (&d)[128], uint32_t stg, bf16* dst, int ld, int lane, F f) {
#pragma unroll
  for (int c = 0; c < BN / 64; c++) {
#pragma unroll
    for (int i = 0; i < 8; i += 2) {
      const int o = c * 32 + i * 4;
      uint32_t r0 = f(d[o], d[o + 1], 0, c * 64 + i * 8), r1 = f(d[o + 2], d[o + 3], 1, c * 64 + i * 8);
      uint32_t r2 = f(d[o + 4], d[o + 5], 0, c * 64 + i * 8 + 8), r3 = f(d[o + 6], d[o + 7], 1, c * 64 + i * 8 + 8);
      int m = lane >> 3, row = (m & 1) * 8 + (lane & 7), ch = (i + (m >> 1)) ^ (row & 7);
      asm volatile("stmatrix.sync.aligned.m8n8.x4.shared.b16 [%0], {%1,%2,%3,%4};" ::"r"(stg + row * 128 + ch * 16), "r"(r0), "r"(r1), "r"(r2), "r"(r3) : "memory");
    }
    __syncwarp();
#pragma unroll
    for (int j = 0; j < 4; j++) {
      int idx = lane + 32 * j, row = idx >> 3, ch = idx & 7;
      uint4 v;
      asm volatile("ld.shared.v4.u32 {%0,%1,%2,%3}, [%4];" : "=r"(v.x), "=r"(v.y), "=r"(v.z), "=r"(v.w) : "r"(stg + row * 128 + ((ch ^ (row & 7)) * 16)));
      *(uint4*)(dst + (size_t)row * ld + c * 64 + ch * 8) = v;
    }
    __syncwarp();
  }
}

__device__ __forceinline__ void attn_unit(int seg, int h, uint8_t* sm, int lane) {
  const int g = lane >> 2, t = lane & 3;
  const uint32_t sv = smem_u32(sm);
  const size_t tok0 = (size_t)seg * 32;
  for (int i = lane; i < 40 * 16; i += 32) {
    int r = i >> 4, c = i & 15;
    const bf16* src = (r < 8 ? g_vm + ((size_t)seg * 8 + r) * HD_ : g_v + (tok0 + r - 8) * HD_) + h * 128 + c * 8;
    cp16(sv + r * 256 + ((c ^ (r & 7)) * 16), src);
  }
  for (int i = lane; i < 8 * 16; i += 32) *(uint4*)(sm + 40 * 256 + i * 16) = make_uint4(0, 0, 0, 0);
  asm volatile("cp.async.commit_group;" ::: "memory");
  float s[2][5][4];
#pragma unroll
  for (int m = 0; m < 2; m++)
#pragma unroll
    for (int n = 0; n < 5; n++) { s[m][n][0] = s[m][n][1] = s[m][n][2] = s[m][n][3] = 0.f; }
#pragma unroll
  for (int j = 0; j < 4; j++) {
    uint4 qa[2][2], kb[5];
#pragma unroll
    for (int m = 0; m < 2; m++)
#pragma unroll
      for (int hh = 0; hh < 2; hh++) qa[m][hh] = *(const uint4*)(g_q + (tok0 + m * 16 + hh * 8 + g) * HD_ + h * 128 + j * 32 + t * 8);
#pragma unroll
    for (int n = 0; n < 5; n++)
      kb[n] = *(const uint4*)((n == 0 ? g_km + ((size_t)seg * 8 + g) * HD_ : g_k + (tok0 + (n - 1) * 8 + g) * HD_) + h * 128 + j * 32 + t * 8);
#pragma unroll
    for (int m = 0; m < 2; m++) {
      uint32_t a0[4] = {qa[m][0].x, qa[m][1].x, qa[m][0].y, qa[m][1].y}, a1[4] = {qa[m][0].z, qa[m][1].z, qa[m][0].w, qa[m][1].w};
#pragma unroll
      for (int n = 0; n < 5; n++) { mma16816(s[m][n], a0, kb[n].x, kb[n].y); mma16816(s[m][n], a1, kb[n].z, kb[n].w); }
    }
  }
  const float sc = 0.08838834764831845f * 1.4426950408889634f;
  uint32_t pa[2][3][4];
#pragma unroll
  for (int m = 0; m < 2; m++) {
    float inv[2];
#pragma unroll
    for (int hh = 0; hh < 2; hh++) {
      int qi = 8 + m * 16 + hh * 8 + g;
      float mx = -INFINITY;
#pragma unroll
      for (int n = 0; n < 5; n++)
#pragma unroll
        for (int e = 0; e < 2; e++) { float& z = s[m][n][hh * 2 + e]; z = (n * 8 + t * 2 + e <= qi) ? z * sc : -INFINITY; mx = fmaxf(mx, z); }
      mx = fmaxf(mx, __shfl_xor_sync(~0u, mx, 1)); mx = fmaxf(mx, __shfl_xor_sync(~0u, mx, 2));
      float sum = 0.f;
#pragma unroll
      for (int n = 0; n < 5; n++)
#pragma unroll
        for (int e = 0; e < 2; e++) { float& z = s[m][n][hh * 2 + e]; z = exp2f(z - mx); sum += z; }
      sum += __shfl_xor_sync(~0u, sum, 1); sum += __shfl_xor_sync(~0u, sum, 2);
      inv[hh] = 1.f / sum;
    }
#pragma unroll
    for (int kk = 0; kk < 3; kk++) {
      pa[m][kk][0] = pack_bf16(s[m][2 * kk][0] * inv[0], s[m][2 * kk][1] * inv[0]);
      pa[m][kk][1] = pack_bf16(s[m][2 * kk][2] * inv[1], s[m][2 * kk][3] * inv[1]);
      if (kk < 2) {
        pa[m][kk][2] = pack_bf16(s[m][2 * kk + 1][0] * inv[0], s[m][2 * kk + 1][1] * inv[0]);
        pa[m][kk][3] = pack_bf16(s[m][2 * kk + 1][2] * inv[1], s[m][2 * kk + 1][3] * inv[1]);
      } else { pa[m][kk][2] = 0; pa[m][kk][3] = 0; }
    }
  }
  asm volatile("cp.async.wait_group 0;" ::: "memory");
  __syncwarp();
  uint32_t ov[2][16][2];
#pragma unroll
  for (int np = 0; np < 8; np++) {
    float o[2][2][4] = {};
#pragma unroll
    for (int kk = 0; kk < 3; kk++) {
      uint32_t b[4];
      int mi = lane >> 3, r = kk * 16 + (mi & 1) * 8 + (lane & 7), c = np * 2 + (mi >> 1);
      ldsm4t(b, sv + r * 256 + ((c ^ (r & 7)) * 16));
#pragma unroll
      for (int m = 0; m < 2; m++) { mma16816(o[m][0], pa[m][kk], b[0], b[1]); mma16816(o[m][1], pa[m][kk], b[2], b[3]); }
    }
#pragma unroll
    for (int m = 0; m < 2; m++)
#pragma unroll
      for (int q = 0; q < 2; q++) { ov[m][np * 2 + q][0] = pack_bf16(o[m][q][0], o[m][q][1]); ov[m][np * 2 + q][1] = pack_bf16(o[m][q][2], o[m][q][3]); }
  }
  __syncwarp();
#pragma unroll
  for (int m = 0; m < 2; m++)
#pragma unroll
    for (int n = 0; n < 16; n++)
#pragma unroll
      for (int hh = 0; hh < 2; hh++) {
        int r = m * 16 + hh * 8 + g;
        *(uint32_t*)(sm + r * 256 + ((n ^ (r & 7)) * 16) + t * 4) = ov[m][n][hh];
      }
  __syncwarp();
#pragma unroll
  for (int i = 0; i < 16; i++) {
    int idx = lane + 32 * i, r = idx >> 4, c = idx & 15;
    *(uint4*)(g_o + (tok0 + r) * HD_ + h * 128 + c * 8) = *(const uint4*)(sm + r * 256 + ((c ^ (r & 7)) * 16));
  }
}

__global__ void __launch_bounds__(384, 1) gemm_kernel(const __grid_constant__ GemmParams p) {
  extern __shared__ uint8_t smem_raw[];
  const uint32_t sbase = (smem_u32(smem_raw) + 1023) & ~1023u;
  const uint32_t stg0 = sbase + NSTAGE * STAGE_BYTES, fullb = stg0 + 8 * 2048, emptyb = fullb + 64;
  const uint32_t rank = cluster_rank();
  const int wg = __shfl_sync(~0u, (int)(threadIdx.x >> 7), 0), lane = threadIdx.x & 31;
  const int cl = blockIdx.x >> 1;
  if (threadIdx.x == 0) {
    for (int i = 0; i < NSTAGE; i++) { mbar_init(fullb + i * 8, 1); mbar_init(emptyb + i * 8, 4); }
    asm volatile("fence.mbarrier_init.release.cluster;" ::: "memory");
  }
  cluster_sync();
  if (blockIdx.x == 0 && threadIdx.x == 0) PT(1 + p.kid * 2);
  const uint16_t* jobs = p.job + cl * p.stride;
  if (wg == 0) {
    asm volatile("setmaxnreg.dec.sync.aligned.u32 40;");
    if (threadIdx.x == 0) {
      int stage = 0; uint32_t phase = 1;
      for (int j = 0; j < p.stride; j++) {
        uint32_t job = jobs[j];
        if (job == 0xFFFF) break;
        int type = job >> 12, m = (job >> 6) & 63, n = job & 63;
        int row0 = m * 256 + rank * 128;
        int bn = type < 3 ? 256 : 192;
        if (type == 6) {
          for (int k = 0; k < NSTAGE; k++) {
            mbar_wait_cl(emptyb + stage * 8, phase);
            asm volatile("mbarrier.arrive.shared::cta.b64 _, [%0];" ::"r"(fullb + stage * 8) : "memory");
            if (++stage == NSTAGE) { stage = 0; phase ^= 1; }
          }
          continue;
        }
        int kit = type < 3 ? 9 : (type == 3 ? 32 : (type == 4 ? 72 : (type == 5 ? 64 : 8)));
        int k0 = 0;
        if (type == 7) { k0 = (n / 3) * 8; n = n % 3; type = 5; }
        if (type == 5) wait_cnt(&g_cnt[16 + m], 32);
        const CUtensorMap* ma = &p.mA[type < 3 ? 0 : type - 2];
        const CUtensorMap* mb = &p.mB[type];
        bool ta = (type == 3 || type == 4);
        if (type >= 4) {
          if (type == 4) wait_cnt(&g_cnt[0], 108);
          asm volatile("fence.proxy.async;" ::: "memory");
        }
        for (int k = k0; k < k0 + kit; k++) {
          mbar_wait_cl(emptyb + stage * 8, phase);
          uint32_t fb = fullb + stage * 8, a = sbase + stage * STAGE_BYTES, b = a + 16384;
          mbar_expect(fb, 16384 + bn * 128);
          if (ta) { tma2d(a, ma, row0, k * 64, fb); tma2d(a + 8192, ma, row0 + 64, k * 64, fb); }
          else tma2d(a, ma, k * 64, row0, fb);
          for (int i = 0; i < bn / 64; i++) tma2d_mc(b + i * 8192 + rank * 4096, mb, n * bn + i * 64, k * 64 + rank * 32, fb, (uint16_t)3);
          if (++stage == NSTAGE) { stage = 0; phase ^= 1; }
        }
      }
    }
    __syncwarp();
    if (p.wait_at_end) pdl_wait();
    cluster_sync();
  } else {
    asm volatile("setmaxnreg.inc.sync.aligned.u32 232;");
    const int cw = wg - 1, warp = __shfl_sync(~0u, (int)(threadIdx.x >> 5) & 3, 0);
    const uint32_t eb_l = mapa(emptyb, rank), eb_r = mapa(emptyb, rank ^ 1);
    const uint32_t stg = stg0 + (cw * 4 + warp) * 2048;
    const bool elect = (threadIdx.x & 127) == 0;
    const int g = lane >> 2, t = lane & 3;
    int stage = 0; uint32_t phase = 0;
    float d[128];
    for (int j = 0; j < p.stride; j++) {
      uint32_t job = jobs[j];
      if (job == 0xFFFF) break;
      int type = job >> 12, m = (job >> 6) & 63, n = job & 63;
      int row0 = m * 256 + rank * 128 + cw * 64 + warp * 16;
      if (type < 3) {
        gemm_mainloop<256, 0>(d, 9, sbase, fullb, eb_l, eb_r, cw, stage, phase, elect);
        bf16* dst = (type == 0 ? g_q : (type == 1 ? g_k : g_v)) + (size_t)row0 * HD_ + n * 256;
        store_tile<256>(d, stg, dst, HD_, lane, [](float a, float b, int, int) { return pack_bf16(a, b); });
        __threadfence();
        asm volatile("bar.sync %0, 256;" ::"r"(1) : "memory");
        if (threadIdx.x == 128) atomicAdd(&g_cnt[(type ? 8 : 40) + m], 1);
      } else if (type == 3) {
        gemm_mainloop<192, 1>(d, 32, sbase, fullb, eb_l, eb_r, cw, stage, phase, elect);
        float bb[2] = {__bfloat162float(p.b1[row0 + g]), __bfloat162float(p.b1[row0 + g + 8])};
        store_tile<192>(d, stg, g_ut + (size_t)row0 * D_ + n * 192, D_, lane,
                        [&](float a, float b, int h, int) { return pack_bf16(gelu_tanh(a + bb[h]), gelu_tanh(b + bb[h])); });
        __threadfence();
        asm volatile("fence.proxy.async;" ::: "memory");
        asm volatile("bar.sync %0, 256;" ::"r"(1) : "memory");
        if (threadIdx.x == 128) atomicAdd(&g_cnt[0], 1);
      } else if (type == 4) {
        gemm_mainloop<192, 1>(d, 72, sbase, fullb, eb_l, eb_r, cw, stage, phase, elect);
        float bb[2] = {__bfloat162float(p.b2[row0 + g]), __bfloat162float(p.b2[row0 + g + 8])};
#pragma unroll
        for (int i = 0; i < 24; i++)
#pragma unroll
          for (int h = 0; h < 2; h++) {
            size_t off = (size_t)(row0 + g + h * 8) * D_ + n * 192 + i * 8 + t * 2;
            float2 xv = unpack_bf16(*(const uint32_t*)(p.x + off));
            *(float2*)(g_yb + off) = make_float2(d[i * 4 + h * 2] + bb[h] + xv.x, d[i * 4 + h * 2 + 1] + bb[h] + xv.y);
          }
        __threadfence();
        asm volatile("bar.sync %0, 256;" ::"r"(1) : "memory");
        if (threadIdx.x == 128) atomicAdd(&g_cnt[24 + m], 1);
      } else if (type == 6) {
        const int st0 = stage;
        for (int k = 0; k < NSTAGE; k++) { mbar_wait(fullb + stage * 8, phase); if (++stage == NSTAGE) { stage = 0; phase ^= 1; } }
        const int seg = m * 8 + (n >> 1), w8 = cw * 4 + warp;
        const unsigned SEGT = p.kid == 2 ? 0u : 64u;
        if (lane == 0) { wait_cnt(&g_cnt[40 + m], 32); wait_cnt(&g_cnt[96 + seg], SEGT); }
        __syncwarp();
        attn_unit(seg, (n & 1) * 16 + rank * 8 + w8, smem_raw + (sbase - smem_u32(smem_raw)) + w8 * 12288, lane);
        __threadfence();
        asm volatile("fence.proxy.async;" ::: "memory");
        asm volatile("bar.sync %0, 256;" ::"r"(1) : "memory");
        if (elect) for (int k = 0; k < NSTAGE; k++) { mbar_arrive_remote(eb_l + k * 8); mbar_arrive_remote(eb_r + k * 8); }
        if (threadIdx.x == 128) atomicAdd(&g_cnt[16 + m], 1);
        (void)st0;
#pragma unroll
        for (int i = 0; i < 128; i++) d[i] = 0.f;
      } else if (type == 7) {
        const int nt = n % 3;
        gemm_mainloop<192, 0>(d, 8, sbase, fullb, eb_l, eb_r, cw, stage, phase, elect);
        if (lane == 0) wait_cnt(&g_cnt[24 + m], 6);
        __syncwarp();
#pragma unroll
        for (int i = 0; i < 24; i++)
#pragma unroll
          for (int h = 0; h < 2; h++)
            atomicAdd((float2*)(g_yb + (size_t)(row0 + g + h * 8) * D_ + nt * 192 + i * 8 + t * 2), make_float2(d[i * 4 + h * 2], d[i * 4 + h * 2 + 1]));
        __threadfence();
        asm volatile("bar.sync %0, 256;" ::"r"(1) : "memory");
        volatile uint32_t* lastf = (volatile uint32_t*)(smem_raw + (emptyb + 64 - smem_u32(smem_raw)));
        if (threadIdx.x == 128) { *lastf = atomicAdd(&g_cnt[48 + ((m - 4) * 3 + nt) * 2 + rank], 1); __threadfence(); }
        asm volatile("bar.sync %0, 256;" ::"r"(1) : "memory");
        if (*lastf == 7) {
          const int r0 = m * 256 + rank * 128;
          for (int i = threadIdx.x - 128; i < 128 * 48; i += 256) {
            int rr = i / 48, cc = (i - rr * 48) * 4;
            size_t off = (size_t)(r0 + rr) * D_ + nt * 192 + cc;
            float4 y = __ldcg((const float4*)(g_yb + off));
            *(uint2*)(p.out + off) = make_uint2(pack_bf16(y.x, y.y), pack_bf16(y.z, y.w));
          }
        }
        asm volatile("bar.sync %0, 256;" ::"r"(1) : "memory");
      } else {
        gemm_mainloop<192, 0>(d, 64, sbase, fullb, eb_l, eb_r, cw, stage, phase, elect);
        if (lane == 0) wait_cnt(&g_cnt[24 + m], 6);
        __syncwarp();
        const float* yb = g_yb + (size_t)(row0 + g) * D_ + n * 192 + t * 2;
        store_tile<192>(d, stg, p.out + (size_t)row0 * D_ + n * 192, D_, lane,
                        [&](float a, float b, int h, int c) { float2 y = *(const float2*)(yb + h * 8 * D_ + c); return pack_bf16(a + y.x, b + y.y); });
      }
    }
    if (blockIdx.x == 0 && threadIdx.x == 128) PT(2 + p.kid * 2);
    if (p.wait_at_end) pdl_wait();
    cluster_sync();
  }
}

constexpr int CH_WV = 0;
constexpr int CH_MEM = CH_WV + 73728;
constexpr int CH_KB = CH_MEM + 9216;
constexpr int CH_VB = CH_KB + 12288;
constexpr int CH_WO = CH_VB + 12288;
constexpr int CH_Q = CH_WO + 81920;
constexpr int CH_R1 = CH_Q + 1024;
constexpr int CH_SC = CH_R1 + 4096;
constexpr int CH_OF = CH_SC + 3584;
constexpr int CH_R2 = CH_OF + 8192;
constexpr int CH_BAR = CH_R2 + 12288;
constexpr int CHAIN_SMEM = CH_BAR + 64 + 1024;
#define POLL_DELAY 400
__device__ __forceinline__ void st_async1(uint32_t a, uint32_t v, uint32_t bar) { asm volatile("st.async.weak.shared::cluster.mbarrier::complete_tx::bytes.b32 [%0], %1, [%2];" ::"r"(a), "r"(v), "r"(bar) : "memory"); }
__device__ __forceinline__ void st_async2(uint32_t a, uint32_t v0, uint32_t v1, uint32_t bar) { asm volatile("st.async.weak.shared::cluster.mbarrier::complete_tx::bytes.v2.b32 [%0], {%1, %2}, [%3];" ::"r"(a), "r"(v0), "r"(v1), "r"(bar) : "memory"); }
__device__ __forceinline__ uint4 lds128(uint32_t a) { uint4 v; asm volatile("ld.shared.v4.u32 {%0,%1,%2,%3}, [%4];" : "=r"(v.x), "=r"(v.y), "=r"(v.z), "=r"(v.w) : "r"(a) : "memory"); return v; }
__device__ __forceinline__ void sts128f(uint32_t a, const float (&c)[4]) { asm volatile("st.shared.v4.f32 [%0], {%1,%2,%3,%4};" ::"r"(a), "f"(c[0]), "f"(c[1]), "f"(c[2]), "f"(c[3]) : "memory"); }
__device__ __forceinline__ void sts32(uint32_t a, uint32_t v) { asm volatile("st.shared.u32 [%0], %1;" ::"r"(a), "r"(v) : "memory"); }
__device__ __forceinline__ void mbar_wait_b(uint32_t b, uint32_t parity) {
  uint32_t ok; int n = 0;
  do { asm volatile("{\n.reg .pred p;\nmbarrier.try_wait.parity.shared::cta.b64 p, [%1], %2;\nselp.u32 %0, 1, 0, p;\n}" : "=r"(ok) : "r"(b), "r"(parity) : "memory"); } while (!ok && ++n < (1 << 20));
}
__device__ __forceinline__ uint32_t mapa_v(uint32_t a, uint32_t r) { uint32_t o; asm volatile("mapa.shared::cluster.u32 %0, %1, %2;" : "=r"(o) : "r"(a), "r"(r)); return o; }
__device__ __forceinline__ uint32_t tid_v() { uint32_t o; asm volatile("mov.u32 %0, %%tid.x;" : "=r"(o)); return o; }
template <int ACC>
__device__ __forceinline__ void wg_rs(float (&d)[4], const uint32_t (&a)[4], uint32_t dlo) {
  uint64_t db = ((uint64_t)16 << 32) | dlo;
  asm volatile("{\n.reg .pred p;\nsetp.ne.b32 p, %9, 0;\nwgmma.mma_async.sync.aligned.m64n8k16.f32.bf16.bf16 {%0,%1,%2,%3}, {%4,%5,%6,%7}, %8, p, 1, 1, 0;\n}"
               : "+f"(d[0]), "+f"(d[1]), "+f"(d[2]), "+f"(d[3]) : "r"(a[0]), "r"(a[1]), "r"(a[2]), "r"(a[3]), "l"(db), "n"(ACC));
}
template <int N>
__device__ __forceinline__ void wg_wait(float (&d)[N][4]) {
  asm volatile("wgmma.commit_group.sync.aligned;\nwgmma.wait_group.sync.aligned 0;" ::: "memory");
#pragma unroll
  for (int i = 0; i < N; i++) asm volatile("" : "+f"(d[i][0]), "+f"(d[i][1]), "+f"(d[i][2]), "+f"(d[i][3]) :: "memory");
}
#define BAR_ALL() asm volatile("bar.sync 0, 256;" ::: "memory")

__global__ void __launch_bounds__(256, 1) chain_kernel(const bf16* __restrict__ mem0, const bf16* __restrict__ Wq, const bf16* __restrict__ Wk,
                                                       const bf16* __restrict__ Wv, const bf16* __restrict__ Wo) {
  extern __shared__ uint8_t smem_raw[];
  const uint32_t sb = (smem_u32(smem_raw) + 1023) & ~1023u;
  const int tid = threadIdx.x, warp = __shfl_sync(~0u, tid >> 5, 0), wgi = __shfl_sync(~0u, tid >> 7, 0), lane = tid & 31, g = lane >> 2, t = lane & 3;
  const uint32_t r = cluster_rank();
  const int c = blockIdx.x >> 3, h = 4 * c + (r >> 1), j0 = h * 128 + (r & 1) * 64;
  const uint32_t bm = sb + CH_BAR, bs = bm + 8, bo = bm + 16;
  pdl_launch();
  if (blockIdx.x == 0 && tid == 0) PT(7);
  if (tid == 0) { mbar_init(bm, 1); mbar_init(bs, 1); mbar_init(bo, 1); asm volatile("fence.mbarrier_init.release.cluster;" ::: "memory"); }
  for (int i = tid; i < 576 + 1024; i += 256) {
    const bf16* a = i < 576 ? Wv + (size_t)i * HD_ + j0 : Wo + (size_t)(c * 512 + ((i - 576) >> 1)) * D_ + (((i - 576) & 1) ? 512 + (r >> 1) * 16 : r * 64);
    asm volatile("prefetch.global.L2 [%0];" ::"l"(a));
  }
  const int mi = lane >> 3, l7 = lane & 7;
  for (int i = tid; i < 576 * 8; i += 256) {
    int row = i >> 3, ch = i & 7;
    cp16(sb + CH_WV + row * 128 + ((ch ^ (row & 7)) * 16), Wq + (size_t)row * HD_ + j0 + ch * 8);
    cp16(sb + CH_WO + row * 128 + ((ch ^ (row & 7)) * 16), Wk + (size_t)row * HD_ + j0 + ch * 8);
  }
  asm volatile("cp.async.commit_group;\ncp.async.wait_group 0;" ::: "memory");
  BAR_ALL();
  uint32_t w1[36][4];
#pragma unroll
  for (int i = 0; i < 36; i++) {
    int row = i * 16 + (mi >> 1) * 8 + l7, ch = ((warp & 3) * 2 + (mi & 1)) ^ (row & 7);
    ldsm4t(w1[i], sb + (wgi ? CH_WO : CH_WV) + row * 128 + ch * 16);
  }
  BAR_ALL();
  for (int i = tid; i < 512 * 10; i += 256) {
    int row = i / 10, ch = i - row * 10;
    cp16(sb + CH_WV + row * 176 + ch * 16, Wo + (size_t)(c * 512 + row) * D_ + (ch < 8 ? r * 64 + ch * 8 : 512 + (r >> 1) * 16 + (ch - 8) * 8));
  }
  asm volatile("cp.async.commit_group;\ncp.async.wait_group 0;" ::: "memory");
  BAR_ALL();
  const int kperm = 2 * ((mi >> 1) * 2 + (l7 >> 2)) + (l7 & 1) + 8 * ((l7 >> 1) & 1);
  for (int i = 0; i < 16; i++) {
    uint32_t a[4];
    ldsm4t(a, sb + CH_WV + ((wgi * 16 + i) * 16 + kperm) * 176 + ((warp & 3) * 2 + (mi & 1)) * 16);
    asm volatile("st.shared.v4.u32 [%0], {%1,%2,%3,%4};" ::"r"(sb + CH_WO + 8192 + (warp * 16 + i) * 512 + lane * 16), "r"(a[0]), "r"(a[1]), "r"(a[2]), "r"(a[3]) : "memory");
  }
  for (int u = warp; u < 16; u += 8) {
    uint32_t a[4];
    ldsm4t(a, sb + CH_WV + (((r & 1) * 16 + u) * 16 + kperm) * 176 + (8 + (mi & 1)) * 16);
    asm volatile("st.shared.v4.u32 [%0], {%1,%2,%3,%4};" ::"r"(sb + CH_WO + u * 512 + lane * 16), "r"(a[0]), "r"(a[1]), "r"(a[2]), "r"(a[3]) : "memory");
  }
  BAR_ALL();
  for (int i = tid; i < 576 * 8; i += 256) {
    int row = i >> 3, ch = i & 7;
    cp16(sb + CH_WV + row * 128 + ((ch ^ (row & 7)) * 16), Wv + (size_t)row * HD_ + j0 + ch * 8);
  }
  for (int i = tid; i < 8 * 72; i += 256) {
    int row = i / 72, ch = i - row * 72;
    cp16(sb + CH_MEM + ch * 128 + row * 16, mem0 + row * D_ + ch * 8);
  }
  for (int i = tid; i < 4 * 64; i += 256) {
    int b = i >> 6, o = i & 63;
    asm volatile("st.shared.v4.u32 [%0], {%1,%1,%1,%1};" ::"r"(sb + CH_KB + b * 6144 + 40 * 128 + o * 16), "r"(0) : "memory");
  }
  auto prefetch_kv = [&](int s, int tid) {
    if ((s & 7) == 0) { if ((tid & 31) == 0) wait_cnt(&g_cnt[8 + (s >> 3)], 64); __syncwarp(); }
#pragma unroll
    for (int i = 0; i < 2; i++) {
      int u = tid + i * 256, which = u >> 8, row = (u & 255) >> 3, ch = u & 7;
      const bf16* src = (which ? g_v : g_k) + (size_t)(s * 32 + row) * HD_ + j0 + ch * 8;
      cp16(sb + (which ? CH_VB : CH_KB) + (s & 1) * 6144 + (row + 8) * 128 + ((ch ^ (row & 7)) * 16), src);
    }
    asm volatile("cp.async.commit_group;" ::: "memory");
  };
  prefetch_kv(0, tid);
  asm volatile("cp.async.wait_group 0;" ::: "memory");
  asm volatile("fence.proxy.async.shared::cta;" ::: "memory");
  BAR_ALL();
  cluster_sync();
  const uint32_t dsb = ((sb & 0x3FFFF) >> 4) | (8u << 16);
  if (blockIdx.x == 0 && tid == 0) PT(10);
#define CP(i) if (blockIdx.x == 0 && lane == 0 && warp == (((i) == 5 || (i) == 7) ? 4 : 0)) PC(64 + s * 16 + (i))
  for (int s = 0; s < NSEG; s++) {
    const int tid = tid_v(), lane = tid & 31, g = lane >> 2, t = lane & 3, mi = lane >> 3, l7 = lane & 7;
    CP(0);
    const uint32_t par = s & 1, kb = sb + CH_KB + par * 6144, vb = sb + CH_VB + par * 6144;
    if (s > 0) mbar_wait_b(bm, par ^ 1);
    CP(1);
    if (tid == 0 && s < NSEG - 1) { mbar_expect(bs, 2560); mbar_expect(bo, 8192); mbar_expect(bm, 9216); }
    auto phase1 = [&]() {
      float pa[3][4] = {};
#pragma unroll
      for (int i = 0; i < 36; i += 2) {
        uint32_t b[4];
        ldsm4(b, sb + CH_MEM + i * 256 + mi * 128 + l7 * 16);
        mma16816(pa[i % 3], w1[i], b[0], b[1]); mma16816(pa[(i + 1) % 3], w1[i + 1], b[2], b[3]);
      }
      CP(2);
      uint32_t b0 = movm(pack_bf16(pa[0][0] + pa[1][0] + pa[2][0], pa[0][1] + pa[1][1] + pa[2][1]));
      uint32_t b1 = movm(pack_bf16(pa[0][2] + pa[1][2] + pa[2][2], pa[0][3] + pa[1][3] + pa[2][3]));
      uint32_t dst = (wgi ? kb : sb + CH_Q) + g * 128 + t * 4;
      sts32(dst + ((((warp & 3) * 2) ^ g) * 16), b0); sts32(dst + ((((warp & 3) * 2 + 1) ^ g) * 16), b1);
      if (wgi) { uint32_t* gp = (uint32_t*)(g_km + ((size_t)s * 8 + g) * HD_ + j0 + (warp & 3) * 16 + t * 2); gp[0] = b0; gp[4] = b1; }
      asm volatile("cp.async.wait_group 0;" ::: "memory");
    };
    if (wgi == 0) {
      phase1();
      BAR_ALL();
      CP(4);
      if (s + 1 < NSEG) { prefetch_kv(s + 1, tid); asm volatile("bar.sync 6, 224;" ::: "memory"); }
      float va[4][4];
      asm volatile("wgmma.fence.sync.aligned;" ::: "memory");
      const uint32_t dwa = (((sb + CH_WV) & 0x3FFFF) >> 4) | ((8192u >> 4) << 16);
#pragma unroll
      for (int ks = 0; ks < 36; ks++) {
        uint64_t da = ((uint64_t)(0x40000000u | (1024 >> 4)) << 32) | (dwa + ks * 128), db = ((uint64_t)16 << 32) | (dsb + ((CH_MEM + ks * 256) >> 4));
        if (ks < 4)
          asm volatile("{\n.reg .pred p;\nsetp.ne.b32 p, 0, 0;\nwgmma.mma_async.sync.aligned.m64n8k16.f32.bf16.bf16 {%0,%1,%2,%3}, %4, %5, p, 1, 1, 1, 0;\n}"
                       : "=f"(va[ks & 3][0]), "=f"(va[ks & 3][1]), "=f"(va[ks & 3][2]), "=f"(va[ks & 3][3]) : "l"(da), "l"(db));
        else
          asm volatile("{\n.reg .pred p;\nsetp.ne.b32 p, 1, 0;\nwgmma.mma_async.sync.aligned.m64n8k16.f32.bf16.bf16 {%0,%1,%2,%3}, %4, %5, p, 1, 1, 1, 0;\n}"
                       : "+f"(va[ks & 3][0]), "+f"(va[ks & 3][1]), "+f"(va[ks & 3][2]), "+f"(va[ks & 3][3]) : "l"(da), "l"(db));
      }
      wg_wait(va);
      CP(6);
      uint32_t b0 = movm(pack_bf16(va[0][0] + va[1][0] + va[2][0] + va[3][0], va[0][1] + va[1][1] + va[2][1] + va[3][1]));
      uint32_t b1 = movm(pack_bf16(va[0][2] + va[1][2] + va[2][2] + va[3][2], va[0][3] + va[1][3] + va[2][3] + va[3][3]));
      sts32(vb + g * 128 + t * 4 + (((warp * 2) ^ g) * 16), b0); sts32(vb + g * 128 + t * 4 + (((warp * 2 + 1) ^ g) * 16), b1);
      uint32_t* gp = (uint32_t*)(g_vm + ((size_t)s * 8 + g) * HD_ + j0 + warp * 16 + t * 2); gp[0] = b0; gp[4] = b1;
      asm volatile("bar.arrive 7, 256;" ::: "memory");
    } else {
      phase1();
      BAR_ALL();
      if (warp == 7 && lane == 0 && s > 0) { __threadfence(); atomicAdd(&g_cnt[96 + s - 1], 1); }
      if (warp < 7 && s < NSEG - 1) {
        const int mt = warp - 4;
        const uint32_t sc_l = mapa_v(sb + CH_SC + (r & 1) * 1792, r), sc_r = mapa_v(sb + CH_SC + (r & 1) * 1792, r ^ 1), bs_l = mapa_v(bs, r), bs_r = mapa_v(bs, r ^ 1);
        float sa[4][4] = {};
#pragma unroll
        for (int kp = 0; kp < 2; kp++) {
          uint32_t b[4], a0[4], a1[4];
          ldsm4(b, sb + CH_Q + l7 * 128 + (((kp * 4 + mi) ^ l7) * 16));
          int row = mt * 16 + (mi & 1) * 8 + l7;
          ldsm4(a0, kb + row * 128 + (((kp * 4 + (mi >> 1)) ^ l7) * 16));
          ldsm4(a1, kb + row * 128 + (((kp * 4 + 2 + (mi >> 1)) ^ l7) * 16));
          mma16816(sa[2 * kp], a0, b[0], b[1]); mma16816(sa[2 * kp + 1], a1, b[2], b[3]);
        }
        asm volatile("bar.arrive 6, 224;" :: "f"(sa[0][0]), "f"(sa[1][0]), "f"(sa[2][0]), "f"(sa[3][0]) : "memory");
#pragma unroll
        for (int e = 0; e < 4; e++) {
          uint32_t off = ((2 * t + (e & 1)) * 56 + mt * 16 + (e >> 1) * 8 + g) * 4, v = __float_as_uint((sa[0][e] + sa[1][e]) + (sa[2][e] + sa[3][e]));
          if (mt < 2 || e < 2) { st_async1(sc_r + off, v, bs_r); st_async1(sc_l + off, v, bs_l); }
        }
        CP(5);
      }
      if (s < NSEG - 1) {
        prefetch_kv(s + 1, tid);
        const int w3 = warp & 3;
        uint32_t vt[3][4];
#pragma unroll
        for (int kk = 1; kk < 3; kk++) { int row = kk * 16 + (mi >> 1) * 8 + l7; ldsm4t(vt[kk], vb + row * 128 + (((w3 * 2 + (mi & 1)) ^ l7) * 16)); }
        mbar_wait_b(bs, par);
        CP(7);
        float z[10]; float mx = -INFINITY;
        const float scl = 0.08838834764831845f * 1.4426950408889634f;
#pragma unroll
        for (int i = 0; i < 5; i++) {
          float2 u0, u1; uint32_t a = sb + CH_SC + (g * 56 + i * 8 + 2 * t) * 4;
          asm volatile("ld.shared.v2.f32 {%0,%1}, [%2];" : "=f"(u0.x), "=f"(u0.y) : "r"(a) : "memory");
          asm volatile("ld.shared.v2.f32 {%0,%1}, [%2];" : "=f"(u1.x), "=f"(u1.y) : "r"(a + 1792) : "memory");
          z[2 * i] = (u0.x + u1.x) * scl; z[2 * i + 1] = (u0.y + u1.y) * scl;
        }
        mx = fmaxf(fmaxf(fmaxf(z[0], z[1]), fmaxf(z[2], z[3])), fmaxf(fmaxf(fmaxf(z[4], z[5]), fmaxf(z[6], z[7])), fmaxf(z[8], z[9])));
        mx = fmaxf(mx, __shfl_xor_sync(~0u, mx, 1)); mx = fmaxf(mx, __shfl_xor_sync(~0u, mx, 2));
        uint32_t pb[5];
#pragma unroll
        for (int i = 0; i < 5; i++) pb[i] = pack_bf16(exp2f(z[2 * i] - mx), exp2f(z[2 * i + 1] - mx));
        const uint32_t ones[4] = {0x3F803F80u, 0x3F803F80u, 0x3F803F80u, 0x3F803F80u};
        float o0[4] = {}, o1[4] = {}, o2[4] = {}, s0[4] = {}, s1[4] = {}, s2[4] = {};
        mma16816(s0, ones, pb[0], pb[1]);
        mma16816(o1, vt[1], pb[2], pb[3]); mma16816(s1, ones, pb[2], pb[3]);
        mma16816(o2, vt[2], pb[4], 0u); mma16816(s2, ones, pb[4], 0u);
        asm volatile("bar.sync 7, 256;" ::: "memory");
        ldsm4t(vt[0], vb + ((mi >> 1) * 8 + l7) * 128 + (((w3 * 2 + (mi & 1)) ^ l7) * 16));
        mma16816(o0, vt[0], pb[0], pb[1]);
        const float i0 = __fdividef(1.f, s0[0] + s1[0] + s2[0]), i1 = __fdividef(1.f, s0[1] + s1[1] + s2[1]);
        uint32_t f0 = movm(pack_bf16((o0[0] + o1[0] + o2[0]) * i0, (o0[1] + o1[1] + o2[1]) * i1));
        uint32_t f1 = movm(pack_bf16((o0[2] + o1[2] + o2[2]) * i0, (o0[3] + o1[3] + o2[3]) * i1));
        const int ks = r * 4 + w3;
        const uint32_t off = CH_OF + ks * 256 + (t >> 1) * 128 + g * 16 + (t & 1) * 8;
        const uint32_t cl0 = mapa_v(sb, 0), clstep = mapa_v(sb, 1) - cl0;
#pragma unroll
        for (int d = 0; d < 8; d++) st_async2(cl0 + d * clstep + off, f0, f1, cl0 + d * clstep + CH_BAR + 16);
      } else asm volatile("bar.sync 7, 256;" ::: "memory");
    }
    if (s == NSEG - 1) break;
    CP(8);
    uint32_t wo[16][4];
#pragma unroll
    for (int i = 0; i < 16; i++) { uint4 v = lds128(sb + CH_WO + 8192 + (warp * 16 + i) * 512 + lane * 16); wo[i][0] = v.x; wo[i][1] = v.y; wo[i][2] = v.z; wo[i][3] = v.w; }
    mbar_wait_b(bo, par);
    CP(9);
    const uint32_t tag = ((s >> 1) + 1) & 1;
    float* pbase = g_part + (size_t)par * 8 * 5120 + lane * 4;
    auto put = [&](int slot, const float (&a)[4]) {
      asm volatile("st.relaxed.gpu.global.v4.b32 [%0], {%1,%2,%3,%4};" ::"l"(pbase + c * 5120 + slot * 128), "r"((__float_as_uint(a[0]) & ~1u) | tag),
                   "r"((__float_as_uint(a[1]) & ~1u) | tag), "r"((__float_as_uint(a[2]) & ~1u) | tag), "r"((__float_as_uint(a[3]) & ~1u) | tag) : "memory");
    };
    {
      float acc[4][4];
      asm volatile("wgmma.fence.sync.aligned;" ::: "memory");
      const uint32_t dof = dsb + ((CH_OF >> 4) + wgi * 256);
#pragma unroll
      for (int i = 0; i < 16; i++) { if (i < 4) wg_rs<0>(acc[i & 3], wo[i], dof + i * 16); else wg_rs<1>(acc[i & 3], wo[i], dof + i * 16); }
      wg_wait(acc);
#pragma unroll
      for (int e = 0; e < 4; e++) acc[0][e] = (acc[0][e] + acc[1][e]) + (acc[2][e] + acc[3][e]);
      CP(10);
      const int w3 = warp & 3;
      if (wgi) {
        sts128f(sb + CH_R2 + w3 * 512 + lane * 16, acc[0]);
        asm volatile("bar.arrive %0, 64;" ::"r"(1 + w3) : "memory");
        if (w3 < 2) {
          float ex[2][4] = {};
#pragma unroll
          for (int i = 0; i < 8; i += 2) {
            uint32_t b[4]; ldsm4(b, sb + CH_OF + ((r & 1) * 16 + w3 * 8 + i) * 256 + mi * 128 + l7 * 16);
            uint4 v0 = lds128(sb + CH_WO + (w3 * 8 + i) * 512 + lane * 16), v1 = lds128(sb + CH_WO + (w3 * 8 + i + 1) * 512 + lane * 16);
            uint32_t a0[4] = {v0.x, v0.y, v0.z, v0.w}, a1[4] = {v1.x, v1.y, v1.z, v1.w};
            mma16816(ex[0], a0, b[0], b[1]); mma16816(ex[1], a1, b[2], b[3]);
          }
#pragma unroll
          for (int e = 0; e < 4; e++) ex[0][e] += ex[1][e];
          if (w3 == 1) { sts128f(sb + CH_R2 + 4 * 512 + lane * 16, ex[0]); asm volatile("bar.arrive 5, 64;" ::: "memory"); }
          else {
            asm volatile("bar.sync 5, 64;" ::: "memory");
            uint4 v = lds128(sb + CH_R2 + 4 * 512 + lane * 16);
            ex[0][0] += __uint_as_float(v.x); ex[0][1] += __uint_as_float(v.y); ex[0][2] += __uint_as_float(v.z); ex[0][3] += __uint_as_float(v.w);
            put(32 + r, ex[0]);
          }
        }
      } else {
        asm volatile("bar.sync %0, 64;" ::"r"(1 + w3) : "memory");
        uint4 v = lds128(sb + CH_R2 + w3 * 512 + lane * 16);
        acc[0][0] += __uint_as_float(v.x); acc[0][1] += __uint_as_float(v.y); acc[0][2] += __uint_as_float(v.z); acc[0][3] += __uint_as_float(v.w);
        put(r * 4 + w3, acc[0]);
      }
    }
    CP(11);
    if (warp < 4 || warp == 6) { long long t0 = clock64(); while (clock64() - t0 < POLL_DELAY) {} }
    if (warp < 4) {
      const float* pb = pbase + (r * 4 + warp) * 128;
      uint4 v[8]; int n = 0; uint32_t need = 0xFF;
#pragma unroll
      for (int i = 0; i < 8; i++) v[i] = make_uint4(0, 0, 0, 0);
      do {
#pragma unroll
        for (int i = 0; i < 8; i++)
          asm volatile("{\n.reg .pred p;\nsetp.ne.b32 p, %5, 0;\n@p ld.relaxed.gpu.global.v4.b32 {%0,%1,%2,%3}, [%4];\n}" : "+r"(v[i].x), "+r"(v[i].y), "+r"(v[i].z), "+r"(v[i].w) : "l"(pb + i * 5120), "r"(need & (1u << i)) : "memory");
#pragma unroll
        for (int i = 0; i < 8; i++) {
          bool ok = ((v[i].x & v[i].y & v[i].z & v[i].w & 1u) == tag) && (((v[i].x | v[i].y | v[i].z | v[i].w) & 1u) == tag);
          if (__all_sync(~0u, ok)) need &= ~(1u << i);
        }
      } while (need && ++n < (1 << 18));
      float m[4] = {};
#pragma unroll
      for (int i = 0; i < 8; i++) { m[0] += __uint_as_float(v[i].x); m[1] += __uint_as_float(v[i].y); m[2] += __uint_as_float(v[i].z); m[3] += __uint_as_float(v[i].w); }
      __syncwarp();
      CP(12);
      uint32_t b0 = movm(pack_bf16(m[0], m[1])), b1 = movm(pack_bf16(m[2], m[3]));
      const uint32_t off = CH_MEM + (r * 4 + warp) * 256 + g * 16 + t * 4;
      const uint32_t cl0 = mapa_v(sb, 0), clstep = mapa_v(sb, 1) - cl0;
#pragma unroll
      for (int d = 0; d < 8; d++) { st_async1(cl0 + d * clstep + off, b0, cl0 + d * clstep + CH_BAR); st_async1(cl0 + d * clstep + off + 128, b1, cl0 + d * clstep + CH_BAR); }
    } else if (warp == 6) {
      const float* pb = pbase - lane * 4 + (32 + (r & ~1u)) * 128 + lane * 4 + (r & 1) * 2;
      uint2 v[16]; int n = 0; uint32_t need = 0xFF;
#pragma unroll
      for (int i = 0; i < 16; i++) v[i] = make_uint2(0, 0);
      do {
#pragma unroll
        for (int i = 0; i < 16; i++)
          asm volatile("{\n.reg .pred p;\nsetp.ne.b32 p, %3, 0;\n@p ld.relaxed.gpu.global.v2.b32 {%0,%1}, [%2];\n}" : "+r"(v[i].x), "+r"(v[i].y) : "l"(pb + (i >> 1) * 5120 + (i & 1) * 128), "r"(need & (1u << (i >> 1))) : "memory");
#pragma unroll
        for (int i = 0; i < 16; i += 2) {
          bool ok = ((v[i].x & v[i].y & v[i + 1].x & v[i + 1].y & 1u) == tag) && (((v[i].x | v[i].y | v[i + 1].x | v[i + 1].y) & 1u) == tag);
          if (__all_sync(~0u, ok)) need &= ~(1u << (i >> 1));
        }
      } while (need && ++n < (1 << 18));
      float m0 = 0.f, m1 = 0.f;
#pragma unroll
      for (int i = 0; i < 16; i++) { m0 += __uint_as_float(v[i].x); m1 += __uint_as_float(v[i].y); }
      __syncwarp();
      uint32_t b0 = movm(pack_bf16(m0, m1));
      const uint32_t off = CH_MEM + (32 + (r >> 1)) * 256 + (r & 1) * 128 + g * 16 + t * 4;
      const uint32_t cl0 = mapa_v(sb, 0), clstep = mapa_v(sb, 1) - cl0;
#pragma unroll
      for (int d = 0; d < 8; d++) st_async1(cl0 + d * clstep + off, b0, cl0 + d * clstep + CH_BAR);
    }
  }
  if (blockIdx.x == 0 && tid == 0) PT(8);
  cluster_sync();
}
typedef CUresult (*EncodeFn)(CUtensorMap*, CUtensorMapDataType, cuuint32_t, void*, const cuuint64_t*, const cuuint64_t*, const cuuint32_t*, const cuuint32_t*,
                             CUtensorMapInterleave, CUtensorMapSwizzle, CUtensorMapL2promotion, CUtensorMapFloatOOBfill);
static EncodeFn g_enc;
static void mkmap(CUtensorMap* m, const void* ptr, int rows, int cols, int boxc, int boxr) {
  cuuint64_t dims[2] = {(cuuint64_t)cols, (cuuint64_t)rows}, strides[1] = {(cuuint64_t)cols * 2};
  cuuint32_t box[2] = {(cuuint32_t)boxc, (cuuint32_t)boxr}, es[2] = {1, 1};
  g_enc(m, CU_TENSOR_MAP_DATA_TYPE_BFLOAT16, 2, (void*)ptr, dims, strides, box, es, CU_TENSOR_MAP_INTERLEAVE_NONE, CU_TENSOR_MAP_SWIZZLE_128B,
        CU_TENSOR_MAP_L2_PROMOTION_L2_256B, CU_TENSOR_MAP_FLOAT_OOB_FILL_NONE);
}
#define URG 50.0
#define CHDT 3.6
constexpr double CH_T0 = 24.0, CH_DT = CHDT;
static inline uint16_t mkjob(int type, int m, int n) { return (uint16_t)(type << 12 | m << 6 | n); }
static void schedule_side(GemmParams& p, const uint16_t* base, int nb, int ncl) {
  static const double cost[8] = {7.6, 7.6, 7.6, 19.5, 56.0, 33.0, 12.5, 7.0};
  double t[66]; int cnt[66] = {};
  for (int c = 0; c < 66; c++) t[c] = 9.0;
  p.stride = 960 / ncl;
  for (int i = 0; i < 960; i++) p.job[i] = 0xFFFF;
  double g2_end = 0, q_end[8] = {}, g3_end[8] = {}, at_end[8] = {}; int qn[8] = {}, g3n[8] = {}, atn[8] = {};
  int bi = 0, ai = 0, gi = 0;
  while (bi < nb || ai < 96 || gi < 60) {
    int b = -1;
    for (int c = 0; c < ncl; c++) if (cnt[c] < p.stride && (b < 0 || t[c] < t[b] || (t[c] == t[b] && cnt[c] < cnt[b]))) b = c;
    const double inf = 1e30;
    int am = ai >> 4, gm = gi < 12 ? gi / 3 : 4 + (gi - 12) / 24;
    double ra = ai < 96 && qn[am] == 16 ? (q_end[am] > CH_T0 + CH_DT * (am * 8 + ((ai & 15) >> 1) + 2) ? q_end[am] : CH_T0 + CH_DT * (am * 8 + ((ai & 15) >> 1) + 2)) : inf;
    double rg = gi < 60 && atn[gm] == 16 && g3n[gm] == 3 ? (at_end[gm] > g3_end[gm] - 30 ? at_end[gm] : g3_end[gm] - 30) : inf;
    bool urgent = bi < nb && (base[bi] >> 12) >= 1 && (base[bi] >> 12) <= 2 && CH_T0 + CH_DT * 8 * ((base[bi] >> 6) & 63) - t[b] < URG;
    uint16_t job; double start = t[b];
    if (urgent) job = base[bi++];
    else if (rg <= t[b] || (bi >= nb && rg < inf && (rg <= ra || (gi < 60 && ai >= 96)))) { job = gi < 12 ? mkjob(5, gm, gi % 3) : mkjob(7, gm, (gi - 12) % 24); gi++; if (rg > start) start = rg; }
    else if (ra <= t[b] || bi >= nb) { job = mkjob(6, am, ai & 15); ai++; if (ra > start) start = ra; }
    else job = base[bi++];
    int ty = job >> 12, m = (job >> 6) & 63;
    if (ty == 4 && start < g2_end) start = g2_end;
    t[b] = start + cost[ty];
    if (ty == 3 && t[b] > g2_end) g2_end = t[b];
    if (ty == 0) { qn[m]++; if (t[b] > q_end[m]) q_end[m] = t[b]; }
    if (ty == 4) { g3n[m]++; if (t[b] > g3_end[m]) g3_end[m] = t[b]; }
    if (ty == 6) { atn[m]++; if (t[b] > at_end[m]) at_end[m] = t[b]; }
    p.job[b * p.stride + cnt[b]++] = job;
  }
}
template <class... A>
static void launch(void (*k)(A...), int grid, int block, int smem, int cluster, bool pdl, A... a) {
  cudaLaunchConfig_t c = {};
  c.gridDim = grid; c.blockDim = block; c.dynamicSmemBytes = smem; c.stream = cudaStreamPerThread;
  cudaLaunchAttribute at[2]; int n = 0;
  if (cluster > 1) { at[n].id = cudaLaunchAttributeClusterDimension; at[n].val.clusterDim.x = cluster; at[n].val.clusterDim.y = 1; at[n].val.clusterDim.z = 1; n++; }
  if (pdl) { at[n].id = cudaLaunchAttributeProgrammaticStreamSerialization; at[n].val.programmaticStreamSerializationAllowed = 1; n++; }
  c.attrs = at; c.numAttrs = n;
  cudaLaunchKernelEx(&c, k, a...);
}

extern "C" void kernel_launch(void* const* d_in, const int* in_sizes, int n_in, void* d_out, int out_size) {
  const bf16 *x = (const bf16*)d_in[0], *mem0 = (const bf16*)d_in[1], *Wq = (const bf16*)d_in[2], *Wk = (const bf16*)d_in[3], *Wv = (const bf16*)d_in[4],
             *Wo = (const bf16*)d_in[5], *w1 = (const bf16*)d_in[8], *b1 = (const bf16*)d_in[9], *w2 = (const bf16*)d_in[10], *b2 = (const bf16*)d_in[11];
  static bool init = false;
  static GemmParams side, post;
  if (!init) {
    init = true;
    cudaDriverEntryPointQueryResult qr;
    cudaGetDriverEntryPoint("cuTensorMapEncodeTiled", (void**)&g_enc, cudaEnableDefault, &qr);
    void *xn, *h2, *o, *ut;
    cudaGetSymbolAddress(&xn, g_xn); cudaGetSymbolAddress(&h2, g_h2); cudaGetSymbolAddress(&o, g_o); cudaGetSymbolAddress(&ut, g_ut);
    GemmParams b = {};
    mkmap(&b.mA[0], xn, S_, D_, 64, 128); mkmap(&b.mA[1], w1, S_, F_, 64, 64); mkmap(&b.mA[2], w2, F_, S_, 64, 64); mkmap(&b.mA[3], o, S_, HD_, 64, 128);
    mkmap(&b.mB[0], Wq, D_, HD_, 64, 32); mkmap(&b.mB[1], Wk, D_, HD_, 64, 32); mkmap(&b.mB[2], Wv, D_, HD_, 64, 32);
    mkmap(&b.mB[3], h2, S_, D_, 64, 32); mkmap(&b.mB[4], ut, F_, D_, 64, 32); mkmap(&b.mB[5], Wo, HD_, D_, 64, 32);
    b.x = x; b.b1 = b1; b.b2 = b2; b.out = (bf16*)d_out;
    side = b; post = b; side.kid = 1; post.kid = 2;
    static uint16_t jl[1024]; int n = 0;
    auto kv = [&](int m) { for (int j = 0; j < 16; j++) { jl[n++] = mkjob(1, m, j); jl[n++] = mkjob(2, m, j); } };
    auto qq = [&](int m) { for (int j = 0; j < 16; j++) jl[n++] = mkjob(0, m, j); };
    kv(0); kv(1);
    for (int m = 0; m < 18; m++) for (int j = 0; j < 3; j++) jl[n++] = mkjob(3, m, j);
    kv(2); qq(0); kv(3); qq(1);
    for (int m = 0; m < 8; m++) for (int j = 0; j < 3; j++) jl[n++] = mkjob(4, m, j);
    for (int m = 4; m < 8; m++) { kv(m); qq(m - 2); }
    qq(6); qq(7);
    schedule_side(side, jl, n, 34);
    side.wait_at_end = 1;
    post.stride = 2;
    for (int i = 0; i < 960; i++) post.job[i] = 0xFFFF;
    for (int i = 0; i < 48; i++) {
      if (i >= 16) { post.job[i * 2] = mkjob(6, 6 + ((i - 16) >> 4), (i - 16) & 15); post.job[i * 2 + 1] = mkjob(7, 6 + i / 24, i % 24); }
      else post.job[i * 2] = mkjob(7, 6 + i / 24, i % 24);
    }
    cudaFuncSetAttribute(gemm_kernel, cudaFuncAttributeMaxDynamicSharedMemorySize, GEMM_SMEM);
    cudaFuncSetAttribute(chain_kernel, cudaFuncAttributeMaxDynamicSharedMemorySize, CHAIN_SMEM);
  }
  launch(ln_kernel, 256, 256, 0, 1, false, x);
  launch(chain_kernel, 64, 256, CHAIN_SMEM, 8, false, mem0, Wq, Wk, Wv, Wo);
  launch(gemm_kernel, 68, 384, GEMM_SMEM, 2, true, side);
  launch(gemm_kernel, 96, 384, GEMM_SMEM, 2, false, post);
}
```

```cpp
#include <cuda_runtime.h>
#include <cuda_bf16.h>
#include <cuda.h>
#include <stdint.h>

typedef __nv_bfloat16 bf16;
constexpr int S_ = 2048, D_ = 576, HD_ = 4096, F_ = 4608, NSEG = 64;

__device__ bf16 g_xn[S_ * D_];
__device__ bf16 g_h2[S_ * D_];
__device__ bf16 g_q[S_ * HD_];
__device__ bf16 g_k[S_ * HD_];
__device__ bf16 g_v[S_ * HD_];
__device__ bf16 g_o[S_ * HD_];
__device__ bf16 g_km[NSEG * 8 * HD_];
__device__ bf16 g_vm[NSEG * 8 * HD_];
__device__ bf16 g_ut[F_ * D_];
__device__ float g_yb[S_ * D_];
__device__ float g_part[2 * 8 * 8 * 5 * 32 * 4];
__device__ unsigned int g_cnt[192];

#define PT(i)
#define PC(i)
__device__ __forceinline__ uint32_t smem_u32(const void* p) { return (uint32_t)__cvta_generic_to_shared(p); }
__device__ __forceinline__ void mbar_init(uint32_t b, uint32_t c) { asm volatile("mbarrier.init.shared::cta.b64 [%0], %1;" ::"r"(b), "r"(c)); }
__device__ __forceinline__ void mbar_expect(uint32_t b, uint32_t bytes) { asm volatile("mbarrier.arrive.expect_tx.shared::cta.b64 _, [%0], %1;" ::"r"(b), "r"(bytes) : "memory"); }
__device__ __forceinline__ void mbar_wait(uint32_t b, uint32_t parity) {
  uint32_t ok;
  do { asm volatile("{\n.reg .pred p;\nmbarrier.try_wait.parity.shared::cta.b64 p, [%1], %2;\nselp.u32 %0, 1, 0, p;\n}" : "=r"(ok) : "r"(b), "r"(parity) : "memory"); } while (!ok);
}
__device__ __forceinline__ void mbar_wait_cl(uint32_t b, uint32_t parity) {
  uint32_t ok;
  do { asm volatile("{\n.reg .pred p;\nmbarrier.try_wait.parity.shared::cta.b64 p, [%1], %2;\nselp.u32 %0, 1, 0, p;\n}" : "=r"(ok) : "r"(b), "r"(parity) : "memory"); } while (!ok);
}
__device__ __forceinline__ uint32_t mapa(uint32_t a, uint32_t r) { uint32_t o; asm("mapa.shared::cluster.u32 %0, %1, %2;" : "=r"(o) : "r"(a), "r"(r)); return o; }
__device__ __forceinline__ void mbar_arrive_remote(uint32_t remote_b) { asm volatile("mbarrier.arrive.shared::cluster.b64 _, [%0];" ::"r"(remote_b) : "memory"); }
__device__ __forceinline__ uint32_t cluster_rank() { uint32_t r; asm("mov.u32 %0, %%cluster_ctarank;" : "=r"(r)); return r; }
__device__ __forceinline__ void cluster_sync() { asm volatile("barrier.cluster.arrive.release.aligned;\nbarrier.cluster.wait.acquire.aligned;" ::: "memory"); }
__device__ __forceinline__ void tma2d(uint32_t dst, const CUtensorMap* m, int c0, int c1, uint32_t bar) {
  asm volatile("cp.async.bulk.tensor.2d.shared::cluster.global.mbarrier::complete_tx::bytes [%0], [%1, {%3, %4}], [%2];"
               ::"r"(dst), "l"(m), "r"(bar), "r"(c0), "r"(c1) : "memory");
}
__device__ __forceinline__ void tma2d_mc(uint32_t dst, const CUtensorMap* m, int c0, int c1, uint32_t bar, uint16_t mask) {
  asm volatile("cp.async.bulk.tensor.2d.shared::cluster.global.mbarrier::complete_tx::bytes.multicast::cluster [%0], [%1, {%3, %4}], [%2], %5;"
               ::"r"(dst), "l"(m), "r"(bar), "r"(c0), "r"(c1), "h"(mask) : "memory");
}
__device__ __forceinline__ uint32_t pack_bf16(float a, float b) { __nv_bfloat162 t = __floats2bfloat162_rn(a, b); return *(uint32_t*)&t; }
__device__ __forceinline__ float2 unpack_bf16(uint32_t u) { return __bfloat1622float2(*(__nv_bfloat162*)&u); }
__device__ __forceinline__ void mma16816(float (&c)[4], const uint32_t (&a)[4], uint32_t b0, uint32_t b1) {
  asm volatile("mma.sync.aligned.m16n8k16.row.col.f32.bf16.bf16.f32 {%0,%1,%2,%3},{%4,%5,%6,%7},{%8,%9},{%0,%1,%2,%3};"
               : "+f"(c[0]), "+f"(c[1]), "+f"(c[2]), "+f"(c[3]) : "r"(a[0]), "r"(a[1]), "r"(a[2]), "r"(a[3]), "r"(b0), "r"(b1));
}
__device__ __forceinline__ void ldsm4(uint32_t (&r)[4], uint32_t a) { asm volatile("ldmatrix.sync.aligned.m8n8.x4.shared.b16 {%0,%1,%2,%3},[%4];" : "=r"(r[0]), "=r"(r[1]), "=r"(r[2]), "=r"(r[3]) : "r"(a) : "memory"); }
__device__ __forceinline__ void ldsm4t(uint32_t (&r)[4], uint32_t a) { asm volatile("ldmatrix.sync.aligned.m8n8.x4.trans.shared.b16 {%0,%1,%2,%3},[%4];" : "=r"(r[0]), "=r"(r[1]), "=r"(r[2]), "=r"(r[3]) : "r"(a) : "memory"); }
__device__ __forceinline__ uint32_t movm(uint32_t a) { uint32_t o; asm volatile("movmatrix.sync.aligned.m8n8.trans.b16 %0, %1;" : "=r"(o) : "r"(a)); return o; }
__device__ __forceinline__ void cp16(uint32_t dst, const void* src) { asm volatile("cp.async.cg.shared.global [%0], [%1], 16;" ::"r"(dst), "l"(src) : "memory"); }
__device__ __forceinline__ void pdl_wait() { asm volatile("griddepcontrol.wait;" ::: "memory"); }
__device__ __forceinline__ void pdl_launch() { asm volatile("griddepcontrol.launch_dependents;" ::: "memory"); }

__device__ __forceinline__ void wait_cnt(const unsigned int* c, unsigned int target) {
  uint32_t v; int n = 0;
  do { asm volatile("ld.acquire.gpu.global.u32 %0, [%1];" : "=r"(v) : "l"(c) : "memory"); if (v >= target) break; __nanosleep(64); } while (++n < (1 << 22));
}
__global__ void __launch_bounds__(256) ln_kernel(const bf16* __restrict__ x) {
  int row = blockIdx.x * 8 + (threadIdx.x >> 5), lane = threadIdx.x & 31;
  if (blockIdx.x == 0 && threadIdx.x < 192) { g_cnt[threadIdx.x] = 0; if (threadIdx.x == 0) PT(0); }
  for (int i = blockIdx.x * 256 + threadIdx.x; i < 2 * 64 * 640; i += 256 * 256) g_part[i] = 0.f;
  const uint32_t* xr = (const uint32_t*)(x + (size_t)row * D_);
  float v[18]; float s = 0.f;
#pragma unroll
  for (int i = 0; i < 9; i++) { float2 f = unpack_bf16(xr[lane + 32 * i]); v[2 * i] = f.x; v[2 * i + 1] = f.y; s += f.x + f.y; }
#pragma unroll
  for (int pass = 0; pass < 2; pass++) {
#pragma unroll
    for (int o = 16; o; o >>= 1) s += __shfl_xor_sync(~0u, s, o);
    float m = s * (1.f / D_), q = 0.f;
#pragma unroll
    for (int i = 0; i < 18; i++) { v[i] -= m; q += v[i] * v[i]; }
#pragma unroll
    for (int o = 16; o; o >>= 1) q += __shfl_xor_sync(~0u, q, o);
    float r = 1.f / sqrtf(q * (1.f / D_) + 1e-5f);
    uint32_t* dst = (uint32_t*)((pass == 0 ? g_xn : g_h2) + (size_t)row * D_);
    s = 0.f;
#pragma unroll
    for (int i = 0; i < 9; i++) {
      uint32_t p = pack_bf16(v[2 * i] * r, v[2 * i + 1] * r);
      dst[lane + 32 * i] = p;
      float2 f = unpack_bf16(p); v[2 * i] = f.x; v[2 * i + 1] = f.y; s += f.x + f.y;
    }
  }
}

template<int TA> __device__ __forceinline__ void wgmma_n256(float (&d)[128], uint64_t da, uint64_t db, int sc) {
  asm volatile("{\n.reg .pred p;\nsetp.ne.b32 p, %130, 0;\n"
    "wgmma.mma_async.sync.aligned.m64n256k16.f32.bf16.bf16 {%0, %1, %2, %3, %4, %5, %6, %7, %8, %9, %10, %11, %12, %13, %14, %15, %16, %17, %18, %19, %20, %21, %22, %23, %24, %25, %26, %27, %28, %29, %30, %31, %32, %33, %34, %35, %36, %37, %38, %39, %40, %41, %42, %43, %44, %45, %46, %47, %48, %49, %50, %51, %52, %53, %54, %55, %56, %57, %58, %59, %60, %61, %62, %63, %64, %65, %66, %67, %68, %69, %70, %71, %72, %73, %74, %75, %76, %77, %78, %79, %80, %81, %82, %83, %84, %85, %86, %87, %88, %89, %90, %91, %92, %93, %94, %95, %96, %97, %98, %99, %100, %101, %102, %103, %104, %105, %106, %107, %108, %109, %110, %111, %112, %113, %114, %115, %116, %117, %118, %119, %120, %121, %122, %123, %124, %125, %126, %127}, %128, %129, p, 1, 1, %131, 1;\n}\n"
    : "+f"(d[0]), "+f"(d[1]), "+f"(d[2]), "+f"(d[3]), "+f"(d[4]), "+f"(d[5]), "+f"(d[6]), "+f"(d[7]), "+f"(d[8]), "+f"(d[9]), "+f"(d[10]), "+f"(d[11]), "+f"(d[12]), "+f"(d[13]), "+f"(d[14]), "+f"(d[15]), "+f"(d[16]), "+f"(d[17]), "+f"(d[18]), "+f"(d[19]), "+f"(d[20]), "+f"(d[21]), "+f"(d[22]), "+f"(d[23]), "+f"(d[24]), "+f"(d[25]), "+f"(d[26]), "+f"(d[27]), "+f"(d[28]), "+f"(d[29]), "+f"(d[30]), "+f"(d[31]), "+f"(d[32]), "+f"(d[33]), "+f"(d[34]), "+f"(d[35]), "+f"(d[36]), "+f"(d[37]), "+f"(d[38]), "+f"(d[39]), "+f"(d[40]), "+f"(d[41]), "+f"(d[42]), "+f"(d[43]), "+f"(d[44]), "+f"(d[45]), "+f"(d[46]), "+f"(d[47]), "+f"(d[48]), "+f"(d[49]), "+f"(d[50]), "+f"(d[51]), "+f"(d[52]), "+f"(d[53]), "+f"(d[54]), "+f"(d[55]), "+f"(d[56]), "+f"(d[57]), "+f"(d[58]), "+f"(d[59]), "+f"(d[60]), "+f"(d[61]), "+f"(d[62]), "+f"(d[63]), "+f"(d[64]), "+f"(d[65]), "+f"(d[66]), "+f"(d[67]), "+f"(d[68]), "+f"(d[69]), "+f"(d[70]), "+f"(d[71]), "+f"(d[72]), "+f"(d[73]), "+f"(d[74]), "+f"(d[75]), "+f"(d[76]), "+f"(d[77]), "+f"(d[78]), "+f"(d[79]), "+f"(d[80]), "+f"(d[81]), "+f"(d[82]), "+f"(d[83]), "+f"(d[84]), "+f"(d[85]), "+f"(d[86]), "+f"(d[87]), "+f"(d[88]), "+f"(d[89]), "+f"(d[90]), "+f"(d[91]), "+f"(d[92]), "+f"(d[93]), "+f"(d[94]), "+f"(d[95]), "+f"(d[96]), "+f"(d[97]), "+f"(d[98]), "+f"(d[99]), "+f"(d[100]), "+f"(d[101]), "+f"(d[102]), "+f"(d[103]), "+f"(d[104]), "+f"(d[105]), "+f"(d[106]), "+f"(d[107]), "+f"(d[108]), "+f"(d[109]), "+f"(d[110]), "+f"(d[111]), "+f"(d[112]), "+f"(d[113]), "+f"(d[114]), "+f"(d[115]), "+f"(d[116]), "+f"(d[117]), "+f"(d[118]), "+f"(d[119]), "+f"(d[120]), "+f"(d[121]), "+f"(d[122]), "+f"(d[123]), "+f"(d[124]), "+f"(d[125]), "+f"(d[126]), "+f"(d[127])
    : "l"(da), "l"(db), "r"(sc), "n"(TA));
}

template<int TA> __device__ __forceinline__ void wgmma_n192(float (&d)[128], uint64_t da, uint64_t db, int sc) {
  asm volatile("{\n.reg .pred p;\nsetp.ne.b32 p, %98, 0;\n"
    "wgmma.mma_async.sync.aligned.m64n192k16.f32.bf16.bf16 {%0, %1, %2, %3, %4, %5, %6, %7, %8, %9, %10, %11, %12, %13, %14, %15, %16, %17, %18, %19, %20, %21, %22, %23, %24, %25, %26, %27, %28, %29, %30, %31, %32, %33, %34, %35, %36, %37, %38, %39, %40, %41, %42, %43, %44, %45, %46, %47, %48, %49, %50, %51, %52, %53, %54, %55, %56, %57, %58, %59, %60, %61, %62, %63, %64, %65, %66, %67, %68, %69, %70, %71, %72, %73, %74, %75, %76, %77, %78, %79, %80, %81, %82, %83, %84, %85, %86, %87, %88, %89, %90, %91, %92, %93, %94, %95}, %96, %97, p, 1, 1, %99, 1;\n}\n"
    : "+f"(d[0]), "+f"(d[1]), "+f"(d[2]), "+f"(d[3]), "+f"(d[4]), "+f"(d[5]), "+f"(d[6]), "+f"(d[7]), "+f"(d[8]), "+f"(d[9]), "+f"(d[10]), "+f"(d[11]), "+f"(d[12]), "+f"(d[13]), "+f"(d[14]), "+f"(d[15]), "+f"(d[16]), "+f"(d[17]), "+f"(d[18]), "+f"(d[19]), "+f"(d[20]), "+f"(d[21]), "+f"(d[22]), "+f"(d[23]), "+f"(d[24]), "+f"(d[25]), "+f"(d[26]), "+f"(d[27]), "+f"(d[28]), "+f"(d[29]), "+f"(d[30]), "+f"(d[31]), "+f"(d[32]), "+f"(d[33]), "+f"(d[34]), "+f"(d[35]), "+f"(d[36]), "+f"(d[37]), "+f"(d[38]), "+f"(d[39]), "+f"(d[40]), "+f"(d[41]), "+f"(d[42]), "+f"(d[43]), "+f"(d[44]), "+f"(d[45]), "+f"(d[46]), "+f"(d[47]), "+f"(d[48]), "+f"(d[49]), "+f"(d[50]), "+f"(d[51]), "+f"(d[52]), "+f"(d[53]), "+f"(d[54]), "+f"(d[55]), "+f"(d[56]), "+f"(d[57]), "+f"(d[58]), "+f"(d[59]), "+f"(d[60]), "+f"(d[61]), "+f"(d[62]), "+f"(d[63]), "+f"(d[64]), "+f"(d[65]), "+f"(d[66]), "+f"(d[67]), "+f"(d[68]), "+f"(d[69]), "+f"(d[70]), "+f"(d[71]), "+f"(d[72]), "+f"(d[73]), "+f"(d[74]), "+f"(d[75]), "+f"(d[76]), "+f"(d[77]), "+f"(d[78]), "+f"(d[79]), "+f"(d[80]), "+f"(d[81]), "+f"(d[82]), "+f"(d[83]), "+f"(d[84]), "+f"(d[85]), "+f"(d[86]), "+f"(d[87]), "+f"(d[88]), "+f"(d[89]), "+f"(d[90]), "+f"(d[91]), "+f"(d[92]), "+f"(d[93]), "+f"(d[94]), "+f"(d[95])
    : "l"(da), "l"(db), "r"(sc), "n"(TA));
}

struct GemmParams {
  CUtensorMap mA[4];
  CUtensorMap mB[6];
  const bf16* x; const bf16* b1; const bf16* b2; bf16* out;
  int stride, kid;
  int wait_at_end;
  uint16_t job[960];
};
constexpr int NSTAGE = 4, STAGE_BYTES = 49152;
constexpr int GEMM_SMEM = NSTAGE * STAGE_BYTES + 8 * 2048 + 256 + 1024;

__device__ __forceinline__ uint64_t mkdesc(uint32_t addr, uint32_t lbo, uint32_t sbo) {
  return (uint64_t)((addr & 0x3FFFF) >> 4) | ((uint64_t)(lbo >> 4) << 16) | ((uint64_t)(sbo >> 4) << 32) | (1ull << 62);
}
__device__ __forceinline__ float gelu_tanh(float u) {
  float z = 0.7978845608028654f * (u + 0.044715f * u * u * u);
  float e = __expf(2.f * z);
  float th = 1.f - __fdividef(2.f, e + 1.f);
  return 0.5f * u * (1.f + th);
}
template <int BN, int TA>
__device__ __forceinline__ void gemm_mainloop(float (&d)[128], int kiters, uint32_t sbase, uint32_t fullb, uint32_t emptyb_l, uint32_t emptyb_r,
                                              int wg, int& stage, uint32_t& phase, bool elect) {
  int prev = -1;
  for (int k = 0; k < kiters; k++) {
    mbar_wait(fullb + stage * 8, phase);
    uint32_t a = sbase + stage * STAGE_BYTES + wg * 8192, b = sbase + stage * STAGE_BYTES + 16384;
    asm volatile("wgmma.fence.sync.aligned;" ::: "memory");
#pragma unroll
    for (int kk = 0; kk < 4; kk++) {
      uint64_t da = TA ? mkdesc(a + kk * 2048, 8192, 1024) : mkdesc(a + kk * 32, 16, 1024);
      uint64_t db = mkdesc(b + kk * 2048, 8192, 1024);
      if constexpr (BN == 256) wgmma_n256<TA>(d, da, db, (k | kk) != 0); else wgmma_n192<TA>(d, da, db, (k | kk) != 0);
    }
    asm volatile("wgmma.commit_group.sync.aligned;" ::: "memory");
    asm volatile("wgmma.wait_group.sync.aligned 1;" ::: "memory");
    if (prev >= 0 && elect) { mbar_arrive_remote(emptyb_l + prev * 8); mbar_arrive_remote(emptyb_r + prev * 8); }
    prev = stage;
    if (++stage == NSTAGE) { stage = 0; phase ^= 1; }
  }
  asm volatile("wgmma.wait_group.sync.aligned 0;" ::: "memory");
  if (elect) { mbar_arrive_remote(emptyb_l + prev * 8); mbar_arrive_remote(emptyb_r + prev * 8); }
}
template <int BN, class F>
__device__ __forceinline__ void store_tile(const float (&d)[128], uint32_t stg, bf16* dst, int ld, int lane, F f) {
#pragma unroll
  for (int c = 0; c < BN / 64; c++) {
#pragma unroll
    for (int i = 0; i < 8; i += 2) {
      const int o = c * 32 + i * 4;
      uint32_t r0 = f(d[o], d[o + 1], 0, c * 64 + i * 8), r1 = f(d[o + 2], d[o + 3], 1, c * 64 + i * 8);
      uint32_t r2 = f(d[o + 4], d[o + 5], 0, c * 64 + i * 8 + 8), r3 = f(d[o + 6], d[o + 7], 1, c * 64 + i * 8 + 8);
      int m = lane >> 3, row = (m & 1) * 8 + (lane & 7), ch = (i + (m >> 1)) ^ (row & 7);
      asm volatile("stmatrix.sync.aligned.m8n8.x4.shared.b16 [%0], {%1,%2,%3,%4};" ::"r"(stg + row * 128 + ch * 16), "r"(r0), "r"(r1), "r"(r2), "r"(r3) : "memory");
    }
    __syncwarp();
#pragma unroll
    for (int j = 0; j < 4; j++) {
      int idx = lane + 32 * j, row = idx >> 3, ch = idx & 7;
      uint4 v;
      asm volatile("ld.shared.v4.u32 {%0,%1,%2,%3}, [%4];" : "=r"(v.x), "=r"(v.y), "=r"(v.z), "=r"(v.w) : "r"(stg + row * 128 + ((ch ^ (row & 7)) * 16)));
      *(uint4*)(dst + (size_t)row * ld + c * 64 + ch * 8) = v;
    }
    __syncwarp();
  }
}

__device__ __forceinline__ void attn_unit(int seg, int h, uint8_t* sm, int lane) {
  const int g = lane >> 2, t = lane & 3;
  const uint32_t sv = smem_u32(sm);
  const size_t tok0 = (size_t)seg * 32;
  for (int i = lane; i < 40 * 16; i += 32) {
    int r = i >> 4, c = i & 15;
    const bf16* src = (r < 8 ? g_vm + ((size_t)seg * 8 + r) * HD_ : g_v + (tok0 + r - 8) * HD_) + h * 128 + c * 8;
    cp16(sv + r * 256 + ((c ^ (r & 7)) * 16), src);
  }
  for (int i = lane; i < 8 * 16; i += 32) *(uint4*)(sm + 40 * 256 + i * 16) = make_uint4(0, 0, 0, 0);
  asm volatile("cp.async.commit_group;" ::: "memory");
  float s[2][5][4];
#pragma unroll
  for (int m = 0; m < 2; m++)
#pragma unroll
    for (int n = 0; n < 5; n++) { s[m][n][0] = s[m][n][1] = s[m][n][2] = s[m][n][3] = 0.f; }
#pragma unroll
  for (int j = 0; j < 4; j++) {
    uint4 qa[2][2], kb[5];
#pragma unroll
    for (int m = 0; m < 2; m++)
#pragma unroll
      for (int hh = 0; hh < 2; hh++) qa[m][hh] = *(const uint4*)(g_q + (tok0 + m * 16 + hh * 8 + g) * HD_ + h * 128 + j * 32 + t * 8);
#pragma unroll
    for (int n = 0; n < 5; n++)
      kb[n] = *(const uint4*)((n == 0 ? g_km + ((size_t)seg * 8 + g) * HD_ : g_k + (tok0 + (n - 1) * 8 + g) * HD_) + h * 128 + j * 32 + t * 8);
#pragma unroll
    for (int m = 0; m < 2; m++) {
      uint32_t a0[4] = {qa[m][0].x, qa[m][1].x, qa[m][0].y, qa[m][1].y}, a1[4] = {qa[m][0].z, qa[m][1].z, qa[m][0].w, qa[m][1].w};
#pragma unroll
      for (int n = 0; n < 5; n++) { mma16816(s[m][n], a0, kb[n].x, kb[n].y); mma16816(s[m][n], a1, kb[n].z, kb[n].w); }
    }
  }
  const float sc = 0.08838834764831845f * 1.4426950408889634f;
  uint32_t pa[2][3][4];
#pragma unroll
  for (int m = 0; m < 2; m++) {
    float inv[2];
#pragma unroll
    for (int hh = 0; hh < 2; hh++) {
      int qi = 8 + m * 16 + hh * 8 + g;
      float mx = -INFINITY;
#pragma unroll
      for (int n = 0; n < 5; n++)
#pragma unroll
        for (int e = 0; e < 2; e++) { float& z = s[m][n][hh * 2 + e]; z = (n * 8 + t * 2 + e <= qi) ? z * sc : -INFINITY; mx = fmaxf(mx, z); }
      mx = fmaxf(mx, __shfl_xor_sync(~0u, mx, 1)); mx = fmaxf(mx, __shfl_xor_sync(~0u, mx, 2));
      float sum = 0.f;
#pragma unroll
      for (int n = 0; n < 5; n++)
#pragma unroll
        for (int e = 0; e < 2; e++) { float& z = s[m][n][hh * 2 + e]; z = exp2f(z - mx); sum += z; }
      sum += __shfl_xor_sync(~0u, sum, 1); sum += __shfl_xor_sync(~0u, sum, 2);
      inv[hh] = 1.f / sum;
    }
#pragma unroll
    for (int kk = 0; kk < 3; kk++) {
      pa[m][kk][0] = pack_bf16(s[m][2 * kk][0] * inv[0], s[m][2 * kk][1] * inv[0]);
      pa[m][kk][1] = pack_bf16(s[m][2 * kk][2] * inv[1], s[m][2 * kk][3] * inv[1]);
      if (kk < 2) {
        pa[m][kk][2] = pack_bf16(s[m][2 * kk + 1][0] * inv[0], s[m][2 * kk + 1][1] * inv[0]);
        pa[m][kk][3] = pack_bf16(s[m][2 * kk + 1][2] * inv[1], s[m][2 * kk + 1][3] * inv[1]);
      } else { pa[m][kk][2] = 0; pa[m][kk][3] = 0; }
    }
  }
  asm volatile("cp.async.wait_group 0;" ::: "memory");
  __syncwarp();
  uint32_t ov[2][16][2];
#pragma unroll
  for (int np = 0; np < 8; np++) {
    float o[2][2][4] = {};
#pragma unroll
    for (int kk = 0; kk < 3; kk++) {
      uint32_t b[4];
      int mi = lane >> 3, r = kk * 16 + (mi & 1) * 8 + (lane & 7), c = np * 2 + (mi >> 1);
      ldsm4t(b, sv + r * 256 + ((c ^ (r & 7)) * 16));
#pragma unroll
      for (int m = 0; m < 2; m++) { mma16816(o[m][0], pa[m][kk], b[0], b[1]); mma16816(o[m][1], pa[m][kk], b[2], b[3]); }
    }
#pragma unroll
    for (int m = 0; m < 2; m++)
#pragma unroll
      for (int q = 0; q < 2; q++) { ov[m][np * 2 + q][0] = pack_bf16(o[m][q][0], o[m][q][1]); ov[m][np * 2 + q][1] = pack_bf16(o[m][q][2], o[m][q][3]); }
  }
  __syncwarp();
#pragma unroll
  for (int m = 0; m < 2; m++)
#pragma unroll
    for (int n = 0; n < 16; n++)
#pragma unroll
      for (int hh = 0; hh < 2; hh++) {
        int r = m * 16 + hh * 8 + g;
        *(uint32_t*)(sm + r * 256 + ((n ^ (r & 7)) * 16) + t * 4) = ov[m][n][hh];
      }
  __syncwarp();
#pragma unroll
  for (int i = 0; i < 16; i++) {
    int idx = lane + 32 * i, r = idx >> 4, c = idx & 15;
    *(uint4*)(g_o + (tok0 + r) * HD_ + h * 128 + c * 8) = *(const uint4*)(sm + r * 256 + ((c ^ (r & 7)) * 16));
  }
}

__global__ void __launch_bounds__(384, 1) gemm_kernel(const __grid_constant__ GemmParams p) {
  extern __shared__ uint8_t smem_raw[];
  const uint32_t sbase = (smem_u32(smem_raw) + 1023) & ~1023u;
  const uint32_t stg0 = sbase + NSTAGE * STAGE_BYTES, fullb = stg0 + 8 * 2048, emptyb = fullb + 64;
  const uint32_t rank = cluster_rank();
  const int wg = __shfl_sync(~0u, (int)(threadIdx.x >> 7), 0), lane = threadIdx.x & 31;
  const int cl = blockIdx.x >> 1;
  if (threadIdx.x == 0) {
    for (int i = 0; i < NSTAGE; i++) { mbar_init(fullb + i * 8, 1); mbar_init(emptyb + i * 8, 4); }
    asm volatile("fence.mbarrier_init.release.cluster;" ::: "memory");
  }
  cluster_sync();
  pdl_launch();
  if (blockIdx.x == 0 && threadIdx.x == 0) PT(1 + p.kid * 2);
  const uint16_t* jobs = p.job + cl * p.stride;
  if (wg == 0) {
    asm volatile("setmaxnreg.dec.sync.aligned.u32 40;");
    if (threadIdx.x == 0) {
      int stage = 0; uint32_t phase = 1;
      for (int j = 0; j < p.stride; j++) {
        uint32_t job = jobs[j];
        if (job == 0xFFFF) break;
        int type = job >> 12, m = (job >> 6) & 63, n = job & 63;
        int row0 = m * 256 + rank * 128;
        int bn = type < 3 ? 256 : 192;
        if (type == 6) {
          for (int k = 0; k < NSTAGE; k++) {
            mbar_wait_cl(emptyb + stage * 8, phase);
            asm volatile("mbarrier.arrive.shared::cta.b64 _, [%0];" ::"r"(fullb + stage * 8) : "memory");
            if (++stage == NSTAGE) { stage = 0; phase ^= 1; }
          }
          continue;
        }
        int kit = type < 3 ? 9 : (type == 3 ? 32 : (type == 4 ? 72 : (type == 5 ? 64 : 8)));
        int k0 = 0;
        if (type == 7) { k0 = (n / 3) * 8; n = n % 3; type = 5; }
        if (type == 5) wait_cnt(&g_cnt[16 + m], 32);
        const CUtensorMap* ma = &p.mA[type < 3 ? 0 : type - 2];
        const CUtensorMap* mb = &p.mB[type];
        bool ta = (type == 3 || type == 4);
        if (type >= 4) {
          if (type == 4) wait_cnt(&g_cnt[0], 108);
          asm volatile("fence.proxy.async;" ::: "memory");
        }
        for (int k = k0; k < k0 + kit; k++) {
          mbar_wait_cl(emptyb + stage * 8, phase);
          uint32_t fb = fullb + stage * 8, a = sbase + stage * STAGE_BYTES, b = a + 16384;
          mbar_expect(fb, 16384 + bn * 128);
          if (ta) { tma2d(a, ma, row0, k * 64, fb); tma2d(a + 8192, ma, row0 + 64, k * 64, fb); }
          else tma2d(a, ma, k * 64, row0, fb);
          for (int i = 0; i < bn / 64; i++) tma2d_mc(b + i * 8192 + rank * 4096, mb, n * bn + i * 64, k * 64 + rank * 32, fb, (uint16_t)3);
          if (++stage == NSTAGE) { stage = 0; phase ^= 1; }
        }
      }
    }
    __syncwarp();
    if (p.wait_at_end) pdl_wait();
    cluster_sync();
  } else {
    asm volatile("setmaxnreg.inc.sync.aligned.u32 232;");
    const int cw = wg - 1, warp = __shfl_sync(~0u, (int)(threadIdx.x >> 5) & 3, 0);
    const uint32_t eb_l = mapa(emptyb, rank), eb_r = mapa(emptyb, rank ^ 1);
    const uint32_t stg = stg0 + (cw * 4 + warp) * 2048;
    const bool elect = (threadIdx.x & 127) == 0;
    const int g = lane >> 2, t = lane & 3;
    int stage = 0; uint32_t phase = 0;
    float d[128];
    for (int j = 0; j < p.stride; j++) {
      uint32_t job = jobs[j];
      if (job == 0xFFFF) break;
      int type = job >> 12, m = (job >> 6) & 63, n = job & 63;
      int row0 = m * 256 + rank * 128 + cw * 64 + warp * 16;
      if (type < 3) {
        gemm_mainloop<256, 0>(d, 9, sbase, fullb, eb_l, eb_r, cw, stage, phase, elect);
        bf16* dst = (type == 0 ? g_q : (type == 1 ? g_k : g_v)) + (size_t)row0 * HD_ + n * 256;
        store_tile<256>(d, stg, dst, HD_, lane, [](float a, float b, int, int) { return pack_bf16(a, b); });
        __threadfence();
        asm volatile("bar.sync %0, 256;" ::"r"(1) : "memory");
        if (threadIdx.x == 128) atomicAdd(&g_cnt[(type ? 8 : 40) + m], 1);
      } else if (type == 3) {
        gemm_mainloop<192, 1>(d, 32, sbase, fullb, eb_l, eb_r, cw, stage, phase, elect);
        float bb[2] = {__bfloat162float(p.b1[row0 + g]), __bfloat162float(p.b1[row0 + g + 8])};
        store_tile<192>(d, stg, g_ut + (size_t)row0 * D_ + n * 192, D_, lane,
                        [&](float a, float b, int h, int) { return pack_bf16(gelu_tanh(a + bb[h]), gelu_tanh(b + bb[h])); });
        __threadfence();
        asm volatile("fence.proxy.async;" ::: "memory");
        asm volatile("bar.sync %0, 256;" ::"r"(1) : "memory");
        if (threadIdx.x == 128) atomicAdd(&g_cnt[0], 1);
      } else if (type == 4) {
        gemm_mainloop<192, 1>(d, 72, sbase, fullb, eb_l, eb_r, cw, stage, phase, elect);
        float bb[2] = {__bfloat162float(p.b2[row0 + g]), __bfloat162float(p.b2[row0 + g + 8])};
#pragma unroll
        for (int i = 0; i < 24; i++)
#pragma unroll
          for (int h = 0; h < 2; h++) {
            size_t off = (size_t)(row0 + g + h * 8) * D_ + n * 192 + i * 8 + t * 2;
            float2 xv = unpack_bf16(*(const uint32_t*)(p.x + off));
            *(float2*)(g_yb + off) = make_float2(d[i * 4 + h * 2] + bb[h] + xv.x, d[i * 4 + h * 2 + 1] + bb[h] + xv.y);
          }
        __threadfence();
        asm volatile("bar.sync %0, 256;" ::"r"(1) : "memory");
        if (threadIdx.x == 128) atomicAdd(&g_cnt[24 + m], 1);
      } else if (type == 6) {
        const int st0 = stage;
        for (int k = 0; k < NSTAGE; k++) { mbar_wait(fullb + stage * 8, phase); if (++stage == NSTAGE) { stage = 0; phase ^= 1; } }
        const int seg = m * 8 + (n >> 1), w8 = cw * 4 + warp;
        const unsigned SEGT = 64u;
        if (lane == 0) { wait_cnt(&g_cnt[40 + m], 32); wait_cnt(&g_cnt[96 + seg], SEGT); }
        __syncwarp();
        attn_unit(seg, (n & 1) * 16 + rank * 8 + w8, smem_raw + (sbase - smem_u32(smem_raw)) + w8 * 12288, lane);
        __threadfence();
        asm volatile("fence.proxy.async;" ::: "memory");
        asm volatile("bar.sync %0, 256;" ::"r"(1) : "memory");
        if (elect) for (int k = 0; k < NSTAGE; k++) { mbar_arrive_remote(eb_l + k * 8); mbar_arrive_remote(eb_r + k * 8); }
        if (threadIdx.x == 128) atomicAdd(&g_cnt[16 + m], 1);
        (void)st0;
#pragma unroll
        for (int i = 0; i < 128; i++) d[i] = 0.f;
      } else if (type == 7) {
        const int nt = n % 3;
        gemm_mainloop<192, 0>(d, 8, sbase, fullb, eb_l, eb_r, cw, stage, phase, elect);
        if (lane == 0) wait_cnt(&g_cnt[24 + m], 6);
        __syncwarp();
#pragma unroll
        for (int i = 0; i < 24; i++)
#pragma unroll
          for (int h = 0; h < 2; h++)
            atomicAdd((float2*)(g_yb + (size_t)(row0 + g + h * 8) * D_ + nt * 192 + i * 8 + t * 2), make_float2(d[i * 4 + h * 2], d[i * 4 + h * 2 + 1]));
        __threadfence();
        asm volatile("bar.sync %0, 256;" ::"r"(1) : "memory");
        volatile uint32_t* lastf = (volatile uint32_t*)(smem_raw + (emptyb + 64 - smem_u32(smem_raw)));
        if (threadIdx.x == 128) { *lastf = atomicAdd(&g_cnt[48 + ((m - 4) * 3 + nt) * 2 + rank], 1); __threadfence(); }
        asm volatile("bar.sync %0, 256;" ::"r"(1) : "memory");
        if (*lastf == 7) {
          const int r0 = m * 256 + rank * 128;
          for (int i = threadIdx.x - 128; i < 128 * 48; i += 256) {
            int rr = i / 48, cc = (i - rr * 48) * 4;
            size_t off = (size_t)(r0 + rr) * D_ + nt * 192 + cc;
            float4 y = __ldcg((const float4*)(g_yb + off));
            *(uint2*)(p.out + off) = make_uint2(pack_bf16(y.x, y.y), pack_bf16(y.z, y.w));
          }
        }
        asm volatile("bar.sync %0, 256;" ::"r"(1) : "memory");
      } else {
        gemm_mainloop<192, 0>(d, 64, sbase, fullb, eb_l, eb_r, cw, stage, phase, elect);
        if (lane == 0) wait_cnt(&g_cnt[24 + m], 6);
        __syncwarp();
        const float* yb = g_yb + (size_t)(row0 + g) * D_ + n * 192 + t * 2;
        store_tile<192>(d, stg, p.out + (size_t)row0 * D_ + n * 192, D_, lane,
                        [&](float a, float b, int h, int c) { float2 y = *(const float2*)(yb + h * 8 * D_ + c); return pack_bf16(a + y.x, b + y.y); });
      }
    }
    if (blockIdx.x == 0 && threadIdx.x == 128) PT(2 + p.kid * 2);
    if (p.wait_at_end) pdl_wait();
    cluster_sync();
  }
}

constexpr int CH_WV = 0;
constexpr int CH_MEM = CH_WV + 73728;
constexpr int CH_KB = CH_MEM + 9216;
constexpr int CH_VB = CH_KB + 12288;
constexpr int CH_WO = CH_VB + 12288;
constexpr int CH_Q = CH_WO + 81920;
constexpr int CH_R1 = CH_Q + 1024;
constexpr int CH_SC = CH_R1 + 4096;
constexpr int CH_OF = CH_SC + 3584;
constexpr int CH_R2 = CH_OF + 8192;
constexpr int CH_BAR = CH_R2 + 12288;
constexpr int CHAIN_SMEM = CH_BAR + 64 + 1024;
#define POLL_DELAY 400
__device__ __forceinline__ void st_async1(uint32_t a, uint32_t v, uint32_t bar) { asm volatile("st.async.weak.shared::cluster.mbarrier::complete_tx::bytes.b32 [%0], %1, [%2];" ::"r"(a), "r"(v), "r"(bar) : "memory"); }
__device__ __forceinline__ void st_async2(uint32_t a, uint32_t v0, uint32_t v1, uint32_t bar) { asm volatile("st.async.weak.shared::cluster.mbarrier::complete_tx::bytes.v2.b32 [%0], {%1, %2}, [%3];" ::"r"(a), "r"(v0), "r"(v1), "r"(bar) : "memory"); }
__device__ __forceinline__ uint4 lds128(uint32_t a) { uint4 v; asm volatile("ld.shared.v4.u32 {%0,%1,%2,%3}, [%4];" : "=r"(v.x), "=r"(v.y), "=r"(v.z), "=r"(v.w) : "r"(a) : "memory"); return v; }
__device__ __forceinline__ void sts128f(uint32_t a, const float (&c)[4]) { asm volatile("st.shared.v4.f32 [%0], {%1,%2,%3,%4};" ::"r"(a), "f"(c[0]), "f"(c[1]), "f"(c[2]), "f"(c[3]) : "memory"); }
__device__ __forceinline__ void sts32(uint32_t a, uint32_t v) { asm volatile("st.shared.u32 [%0], %1;" ::"r"(a), "r"(v) : "memory"); }
__device__ __forceinline__ void mbar_wait_b(uint32_t b, uint32_t parity) {
  uint32_t ok; int n = 0;
  do { asm volatile("{\n.reg .pred p;\nmbarrier.try_wait.parity.shared::cta.b64 p, [%1], %2;\nselp.u32 %0, 1, 0, p;\n}" : "=r"(ok) : "r"(b), "r"(parity) : "memory"); } while (!ok && ++n < (1 << 20));
}
__device__ __forceinline__ uint32_t mapa_v(uint32_t a, uint32_t r) { uint32_t o; asm volatile("mapa.shared::cluster.u32 %0, %1, %2;" : "=r"(o) : "r"(a), "r"(r)); return o; }
__device__ __forceinline__ uint32_t tid_v() { uint32_t o; asm volatile("mov.u32 %0, %%tid.x;" : "=r"(o)); return o; }
template <int ACC>
__device__ __forceinline__ void wg_rs(float (&d)[4], const uint32_t (&a)[4], uint32_t dlo) {
  uint64_t db = ((uint64_t)16 << 32) | dlo;
  asm volatile("{\n.reg .pred p;\nsetp.ne.b32 p, %9, 0;\nwgmma.mma_async.sync.aligned.m64n8k16.f32.bf16.bf16 {%0,%1,%2,%3}, {%4,%5,%6,%7}, %8, p, 1, 1, 0;\n}"
               : "+f"(d[0]), "+f"(d[1]), "+f"(d[2]), "+f"(d[3]) : "r"(a[0]), "r"(a[1]), "r"(a[2]), "r"(a[3]), "l"(db), "n"(ACC));
}
template <int N>
__device__ __forceinline__ void wg_wait(float (&d)[N][4]) {
  asm volatile("wgmma.commit_group.sync.aligned;\nwgmma.wait_group.sync.aligned 0;" ::: "memory");
#pragma unroll
  for (int i = 0; i < N; i++) asm volatile("" : "+f"(d[i][0]), "+f"(d[i][1]), "+f"(d[i][2]), "+f"(d[i][3]) :: "memory");
}
#define BAR_ALL() asm volatile("bar.sync 0, 256;" ::: "memory")

__global__ void __launch_bounds__(256, 1) chain_kernel(const bf16* __restrict__ mem0, const bf16* __restrict__ Wq, const bf16* __restrict__ Wk,
                                                       const bf16* __restrict__ Wv, const bf16* __restrict__ Wo) {
  extern __shared__ uint8_t smem_raw[];
  const uint32_t sb = (smem_u32(smem_raw) + 1023) & ~1023u;
  const int tid = threadIdx.x, warp = __shfl_sync(~0u, tid >> 5, 0), wgi = __shfl_sync(~0u, tid >> 7, 0), lane = tid & 31, g = lane >> 2, t = lane & 3;
  const uint32_t r = cluster_rank();
  const int c = blockIdx.x >> 3, h = 4 * c + (r >> 1), j0 = h * 128 + (r & 1) * 64;
  const uint32_t bm = sb + CH_BAR, bs = bm + 8, bo = bm + 16;
  pdl_launch();
  if (blockIdx.x == 0 && tid == 0) PT(7);
  if (tid == 0) { mbar_init(bm, 1); mbar_init(bs, 1); mbar_init(bo, 1); asm volatile("fence.mbarrier_init.release.cluster;" ::: "memory"); }
  for (int i = tid; i < 576 + 1024; i += 256) {
    const bf16* a = i < 576 ? Wv + (size_t)i * HD_ + j0 : Wo + (size_t)(c * 512 + ((i - 576) >> 1)) * D_ + (((i - 576) & 1) ? 512 + (r >> 1) * 16 : r * 64);
    asm volatile("prefetch.global.L2 [%0];" ::"l"(a));
  }
  const int mi = lane >> 3, l7 = lane & 7;
  for (int i = tid; i < 576 * 8; i += 256) {
    int row = i >> 3, ch = i & 7;
    cp16(sb + CH_WV + row * 128 + ((ch ^ (row & 7)) * 16), Wq + (size_t)row * HD_ + j0 + ch * 8);
    cp16(sb + CH_WO + row * 128 + ((ch ^ (row & 7)) * 16), Wk + (size_t)row * HD_ + j0 + ch * 8);
  }
  asm volatile("cp.async.commit_group;\ncp.async.wait_group 0;" ::: "memory");
  BAR_ALL();
  uint32_t w1[36][4];
#pragma unroll
  for (int i = 0; i < 36; i++) {
    int row = i * 16 + (mi >> 1) * 8 + l7, ch = ((warp & 3) * 2 + (mi & 1)) ^ (row & 7);
    ldsm4t(w1[i], sb + (wgi ? CH_WO : CH_WV) + row * 128 + ch * 16);
  }
  BAR_ALL();
  for (int i = tid; i < 512 * 10; i += 256) {
    int row = i / 10, ch = i - row * 10;
    cp16(sb + CH_WV + row * 176 + ch * 16, Wo + (size_t)(c * 512 + row) * D_ + (ch < 8 ? r * 64 + ch * 8 : 512 + (r >> 1) * 16 + (ch - 8) * 8));
  }
  asm volatile("cp.async.commit_group;\ncp.async.wait_group 0;" ::: "memory");
  BAR_ALL();
  const int kperm = 2 * ((mi >> 1) * 2 + (l7 >> 2)) + (l7 & 1) + 8 * ((l7 >> 1) & 1);
  for (int i = 0; i < 16; i++) {
    uint32_t a[4];
    ldsm4t(a, sb + CH_WV + ((wgi * 16 + i) * 16 + kperm) * 176 + ((warp & 3) * 2 + (mi & 1)) * 16);
    asm volatile("st.shared.v4.u32 [%0], {%1,%2,%3,%4};" ::"r"(sb + CH_WO + 8192 + (warp * 16 + i) * 512 + lane * 16), "r"(a[0]), "r"(a[1]), "r"(a[2]), "r"(a[3]) : "memory");
  }
  for (int u = warp; u < 16; u += 8) {
    uint32_t a[4];
    ldsm4t(a, sb + CH_WV + (((r & 1) * 16 + u) * 16 + kperm) * 176 + (8 + (mi & 1)) * 16);
    asm volatile("st.shared.v4.u32 [%0], {%1,%2,%3,%4};" ::"r"(sb + CH_WO + u * 512 + lane * 16), "r"(a[0]), "r"(a[1]), "r"(a[2]), "r"(a[3]) : "memory");
  }
  BAR_ALL();
  for (int i = tid; i < 576 * 8; i += 256) {
    int row = i >> 3, ch = i & 7;
    cp16(sb + CH_WV + row * 128 + ((ch ^ (row & 7)) * 16), Wv + (size_t)row * HD_ + j0 + ch * 8);
  }
  for (int i = tid; i < 8 * 72; i += 256) {
    int row = i / 72, ch = i - row * 72;
    cp16(sb + CH_MEM + ch * 128 + row * 16, mem0 + row * D_ + ch * 8);
  }
  for (int i = tid; i < 4 * 64; i += 256) {
    int b = i >> 6, o = i & 63;
    asm volatile("st.shared.v4.u32 [%0], {%1,%1,%1,%1};" ::"r"(sb + CH_KB + b * 6144 + 40 * 128 + o * 16), "r"(0) : "memory");
  }
  auto prefetch_kv = [&](int s, int tid) {
    if ((s & 7) == 0) { if ((tid & 31) == 0) wait_cnt(&g_cnt[8 + (s >> 3)], 64); __syncwarp(); }
#pragma unroll
    for (int i = 0; i < 2; i++) {
      int u = tid + i * 256, which = u >> 8, row = (u & 255) >> 3, ch = u & 7;
      const bf16* src = (which ? g_v : g_k) + (size_t)(s * 32 + row) * HD_ + j0 + ch * 8;
      cp16(sb + (which ? CH_VB : CH_KB) + (s & 1) * 6144 + (row + 8) * 128 + ((ch ^ (row & 7)) * 16), src);
    }
    asm volatile("cp.async.commit_group;" ::: "memory");
  };
  prefetch_kv(0, tid);
  asm volatile("cp.async.wait_group 0;" ::: "memory");
  asm volatile("fence.proxy.async.shared::cta;" ::: "memory");
  BAR_ALL();
  cluster_sync();
  const uint32_t dsb = ((sb & 0x3FFFF) >> 4) | (8u << 16);
  if (blockIdx.x == 0 && tid == 0) PT(10);
#define CP(i) if (blockIdx.x == 0 && lane == 0 && warp == (((i) == 5 || (i) == 7) ? 4 : 0)) PC(64 + s * 16 + (i))
  for (int s = 0; s < NSEG; s++) {
    const int tid = tid_v(), lane = tid & 31, g = lane >> 2, t = lane & 3, mi = lane >> 3, l7 = lane & 7;
    CP(0);
    const uint32_t par = s & 1, kb = sb + CH_KB + par * 6144, vb = sb + CH_VB + par * 6144;
    if (s > 0) mbar_wait_b(bm, par ^ 1);
    CP(1);
    if (tid == 0 && s < NSEG - 1) { mbar_expect(bs, 2560); mbar_expect(bo, 8192); mbar_expect(bm, 9216); }
    auto phase1 = [&]() {
      float pa[3][4] = {};
#pragma unroll
      for (int i = 0; i < 36; i += 2) {
        uint32_t b[4];
        ldsm4(b, sb + CH_MEM + i * 256 + mi * 128 + l7 * 16);
        mma16816(pa[i % 3], w1[i], b[0], b[1]); mma16816(pa[(i + 1) % 3], w1[i + 1], b[2], b[3]);
      }
      CP(2);
      uint32_t b0 = movm(pack_bf16(pa[0][0] + pa[1][0] + pa[2][0], pa[0][1] + pa[1][1] + pa[2][1]));
      uint32_t b1 = movm(pack_bf16(pa[0][2] + pa[1][2] + pa[2][2], pa[0][3] + pa[1][3] + pa[2][3]));
      uint32_t dst = (wgi ? kb : sb + CH_Q) + g * 128 + t * 4;
      sts32(dst + ((((warp & 3) * 2) ^ g) * 16), b0); sts32(dst + ((((warp & 3) * 2 + 1) ^ g) * 16), b1);
      if (wgi) { uint32_t* gp = (uint32_t*)(g_km + ((size_t)s * 8 + g) * HD_ + j0 + (warp & 3) * 16 + t * 2); gp[0] = b0; gp[4] = b1; }
      asm volatile("cp.async.wait_group 0;" ::: "memory");
    };
    if (wgi == 0) {
      phase1();
      BAR_ALL();
      CP(4);
      if (s + 1 < NSEG) { prefetch_kv(s + 1, tid); asm volatile("bar.sync 6, 224;" ::: "memory"); }
      float va[4][4];
      asm volatile("wgmma.fence.sync.aligned;" ::: "memory");
      const uint32_t dwa = (((sb + CH_WV) & 0x3FFFF) >> 4) | ((8192u >> 4) << 16);
#pragma unroll
      for (int ks = 0; ks < 36; ks++) {
        uint64_t da = ((uint64_t)(0x40000000u | (1024 >> 4)) << 32) | (dwa + ks * 128), db = ((uint64_t)16 << 32) | (dsb + ((CH_MEM + ks * 256) >> 4));
        if (ks < 4)
          asm volatile("{\n.reg .pred p;\nsetp.ne.b32 p, 0, 0;\nwgmma.mma_async.sync.aligned.m64n8k16.f32.bf16.bf16 {%0,%1,%2,%3}, %4, %5, p, 1, 1, 1, 0;\n}"
                       : "=f"(va[ks & 3][0]), "=f"(va[ks & 3][1]), "=f"(va[ks & 3][2]), "=f"(va[ks & 3][3]) : "l"(da), "l"(db));
        else
          asm volatile("{\n.reg .pred p;\nsetp.ne.b32 p, 1, 0;\nwgmma.mma_async.sync.aligned.m64n8k16.f32.bf16.bf16 {%0,%1,%2,%3}, %4, %5, p, 1, 1, 1, 0;\n}"
                       : "+f"(va[ks & 3][0]), "+f"(va[ks & 3][1]), "+f"(va[ks & 3][2]), "+f"(va[ks & 3][3]) : "l"(da), "l"(db));
      }
      wg_wait(va);
      CP(6);
      uint32_t b0 = movm(pack_bf16(va[0][0] + va[1][0] + va[2][0] + va[3][0], va[0][1] + va[1][1] + va[2][1] + va[3][1]));
      uint32_t b1 = movm(pack_bf16(va[0][2] + va[1][2] + va[2][2] + va[3][2], va[0][3] + va[1][3] + va[2][3] + va[3][3]));
      sts32(vb + g * 128 + t * 4 + (((warp * 2) ^ g) * 16), b0); sts32(vb + g * 128 + t * 4 + (((warp * 2 + 1) ^ g) * 16), b1);
      uint32_t* gp = (uint32_t*)(g_vm + ((size_t)s * 8 + g) * HD_ + j0 + warp * 16 + t * 2); gp[0] = b0; gp[4] = b1;
      asm volatile("bar.arrive 7, 256;" ::: "memory");
    } else {
      phase1();
      BAR_ALL();
      if (warp == 7 && lane == 0 && s > 0) { __threadfence(); atomicAdd(&g_cnt[96 + s - 1], 1); }
      if (warp < 7 && s < NSEG - 1) {
        const int mt = warp - 4;
        const uint32_t sc_l = mapa_v(sb + CH_SC + (r & 1) * 1792, r), sc_r = mapa_v(sb + CH_SC + (r & 1) * 1792, r ^ 1), bs_l = mapa_v(bs, r), bs_r = mapa_v(bs, r ^ 1);
        float sa[4][4] = {};
#pragma unroll
        for (int kp = 0; kp < 2; kp++) {
          uint32_t b[4], a0[4], a1[4];
          ldsm4(b, sb + CH_Q + l7 * 128 + (((kp * 4 + mi) ^ l7) * 16));
          int row = mt * 16 + (mi & 1) * 8 + l7;
          ldsm4(a0, kb + row * 128 + (((kp * 4 + (mi >> 1)) ^ l7) * 16));
          ldsm4(a1, kb + row * 128 + (((kp * 4 + 2 + (mi >> 1)) ^ l7) * 16));
          mma16816(sa[2 * kp], a0, b[0], b[1]); mma16816(sa[2 * kp + 1], a1, b[2], b[3]);
        }
        asm volatile("bar.arrive 6, 224;" :: "f"(sa[0][0]), "f"(sa[1][0]), "f"(sa[2][0]), "f"(sa[3][0]) : "memory");
#pragma unroll
        for (int e = 0; e < 4; e++) {
          uint32_t off = ((2 * t + (e & 1)) * 56 + mt * 16 + (e >> 1) * 8 + g) * 4, v = __float_as_uint((sa[0][e] + sa[1][e]) + (sa[2][e] + sa[3][e]));
          if (mt < 2 || e < 2) { st_async1(sc_r + off, v, bs_r); st_async1(sc_l + off, v, bs_l); }
        }
        CP(5);
      }
      if (s < NSEG - 1) {
        prefetch_kv(s + 1, tid);
        const int w3 = warp & 3;
        uint32_t vt[3][4];
#pragma unroll
        for (int kk = 1; kk < 3; kk++) { int row = kk * 16 + (mi >> 1) * 8 + l7; ldsm4t(vt[kk], vb + row * 128 + (((w3 * 2 + (mi & 1)) ^ l7) * 16)); }
        mbar_wait_b(bs, par);
        CP(7);
        float z[10]; float mx = -INFINITY;
        const float scl = 0.08838834764831845f * 1.4426950408889634f;
#pragma unroll
        for (int i = 0; i < 5; i++) {
          float2 u0, u1; uint32_t a = sb + CH_SC + (g * 56 + i * 8 + 2 * t) * 4;
          asm volatile("ld.shared.v2.f32 {%0,%1}, [%2];" : "=f"(u0.x), "=f"(u0.y) : "r"(a) : "memory");
          asm volatile("ld.shared.v2.f32 {%0,%1}, [%2];" : "=f"(u1.x), "=f"(u1.y) : "r"(a + 1792) : "memory");
          z[2 * i] = (u0.x + u1.x) * scl; z[2 * i + 1] = (u0.y + u1.y) * scl;
        }
        mx = fmaxf(fmaxf(fmaxf(z[0], z[1]), fmaxf(z[2], z[3])), fmaxf(fmaxf(fmaxf(z[4], z[5]), fmaxf(z[6], z[7])), fmaxf(z[8], z[9])));
        mx = fmaxf(mx, __shfl_xor_sync(~0u, mx, 1)); mx = fmaxf(mx, __shfl_xor_sync(~0u, mx, 2));
        uint32_t pb[5];
#pragma unroll
        for (int i = 0; i < 5; i++) pb[i] = pack_bf16(exp2f(z[2 * i] - mx), exp2f(z[2 * i + 1] - mx));
        const uint32_t ones[4] = {0x3F803F80u, 0x3F803F80u, 0x3F803F80u, 0x3F803F80u};
        float o0[4] = {}, o1[4] = {}, o2[4] = {}, s0[4] = {}, s1[4] = {}, s2[4] = {};
        mma16816(s0, ones, pb[0], pb[1]);
        mma16816(o1, vt[1], pb[2], pb[3]); mma16816(s1, ones, pb[2], pb[3]);
        mma16816(o2, vt[2], pb[4], 0u); mma16816(s2, ones, pb[4], 0u);
        asm volatile("bar.sync 7, 256;" ::: "memory");
        ldsm4t(vt[0], vb + ((mi >> 1) * 8 + l7) * 128 + (((w3 * 2 + (mi & 1)) ^ l7) * 16));
        mma16816(o0, vt[0], pb[0], pb[1]);
        const float i0 = __fdividef(1.f, s0[0] + s1[0] + s2[0]), i1 = __fdividef(1.f, s0[1] + s1[1] + s2[1]);
        uint32_t f0 = movm(pack_bf16((o0[0] + o1[0] + o2[0]) * i0, (o0[1] + o1[1] + o2[1]) * i1));
        uint32_t f1 = movm(pack_bf16((o0[2] + o1[2] + o2[2]) * i0, (o0[3] + o1[3] + o2[3]) * i1));
        const int ks = r * 4 + w3;
        const uint32_t off = CH_OF + ks * 256 + (t >> 1) * 128 + g * 16 + (t & 1) * 8;
        const uint32_t cl0 = mapa_v(sb, 0), clstep = mapa_v(sb, 1) - cl0;
#pragma unroll
        for (int d = 0; d < 8; d++) st_async2(cl0 + d * clstep + off, f0, f1, cl0 + d * clstep + CH_BAR + 16);
      } else asm volatile("bar.sync 7, 256;" ::: "memory");
    }
    if (s == NSEG - 1) break;
    CP(8);
    uint32_t wo[16][4];
#pragma unroll
    for (int i = 0; i < 16; i++) { uint4 v = lds128(sb + CH_WO + 8192 + (warp * 16 + i) * 512 + lane * 16); wo[i][0] = v.x; wo[i][1] = v.y; wo[i][2] = v.z; wo[i][3] = v.w; }
    mbar_wait_b(bo, par);
    CP(9);
    const uint32_t tag = ((s >> 1) + 1) & 1;
    float* pbase = g_part + (size_t)par * 8 * 5120 + lane * 4;
    auto put = [&](int slot, const float (&a)[4]) {
      asm volatile("st.relaxed.gpu.global.v4.b32 [%0], {%1,%2,%3,%4};" ::"l"(pbase + c * 5120 + slot * 128), "r"((__float_as_uint(a[0]) & ~1u) | tag),
                   "r"((__float_as_uint(a[1]) & ~1u) | tag), "r"((__float_as_uint(a[2]) & ~1u) | tag), "r"((__float_as_uint(a[3]) & ~1u) | tag) : "memory");
    };
    {
      float acc[4][4];
      asm volatile("wgmma.fence.sync.aligned;" ::: "memory");
      const uint32_t dof = dsb + ((CH_OF >> 4) + wgi * 256);
#pragma unroll
      for (int i = 0; i < 16; i++) { if (i < 4) wg_rs<0>(acc[i & 3], wo[i], dof + i * 16); else wg_rs<1>(acc[i & 3], wo[i], dof + i * 16); }
      wg_wait(acc);
#pragma unroll
      for (int e = 0; e < 4; e++) acc[0][e] = (acc[0][e] + acc[1][e]) + (acc[2][e] + acc[3][e]);
      CP(10);
      const int w3 = warp & 3;
      if (wgi) {
        sts128f(sb + CH_R2 + w3 * 512 + lane * 16, acc[0]);
        asm volatile("bar.arrive %0, 64;" ::"r"(1 + w3) : "memory");
        if (w3 < 2) {
          float ex[2][4] = {};
#pragma unroll
          for (int i = 0; i < 8; i += 2) {
            uint32_t b[4]; ldsm4(b, sb + CH_OF + ((r & 1) * 16 + w3 * 8 + i) * 256 + mi * 128 + l7 * 16);
            uint4 v0 = lds128(sb + CH_WO + (w3 * 8 + i) * 512 + lane * 16), v1 = lds128(sb + CH_WO + (w3 * 8 + i + 1) * 512 + lane * 16);
            uint32_t a0[4] = {v0.x, v0.y, v0.z, v0.w}, a1[4] = {v1.x, v1.y, v1.z, v1.w};
            mma16816(ex[0], a0, b[0], b[1]); mma16816(ex[1], a1, b[2], b[3]);
          }
#pragma unroll
          for (int e = 0; e < 4; e++) ex[0][e] += ex[1][e];
          if (w3 == 1) { sts128f(sb + CH_R2 + 4 * 512 + lane * 16, ex[0]); asm volatile("bar.arrive 5, 64;" ::: "memory"); }
          else {
            asm volatile("bar.sync 5, 64;" ::: "memory");
            uint4 v = lds128(sb + CH_R2 + 4 * 512 + lane * 16);
            ex[0][0] += __uint_as_float(v.x); ex[0][1] += __uint_as_float(v.y); ex[0][2] += __uint_as_float(v.z); ex[0][3] += __uint_as_float(v.w);
            put(32 + r, ex[0]);
          }
        }
      } else {
        asm volatile("bar.sync %0, 64;" ::"r"(1 + w3) : "memory");
        uint4 v = lds128(sb + CH_R2 + w3 * 512 + lane * 16);
        acc[0][0] += __uint_as_float(v.x); acc[0][1] += __uint_as_float(v.y); acc[0][2] += __uint_as_float(v.z); acc[0][3] += __uint_as_float(v.w);
        put(r * 4 + w3, acc[0]);
      }
    }
    CP(11);
    if (warp < 4 || warp == 6) { long long t0 = clock64(); while (clock64() - t0 < POLL_DELAY) {} }
    if (warp < 4) {
      const float* pb = pbase + (r * 4 + warp) * 128;
      uint4 v[8]; int n = 0; uint32_t need = 0xFF;
#pragma unroll
      for (int i = 0; i < 8; i++) v[i] = make_uint4(0, 0, 0, 0);
      do {
#pragma unroll
        for (int i = 0; i < 8; i++)
          asm volatile("{\n.reg .pred p;\nsetp.ne.b32 p, %5, 0;\n@p ld.relaxed.gpu.global.v4.b32 {%0,%1,%2,%3}, [%4];\n}" : "+r"(v[i].x), "+r"(v[i].y), "+r"(v[i].z), "+r"(v[i].w) : "l"(pb + i * 5120), "r"(need & (1u << i)) : "memory");
#pragma unroll
        for (int i = 0; i < 8; i++) {
          bool ok = ((v[i].x & v[i].y & v[i].z & v[i].w & 1u) == tag) && (((v[i].x | v[i].y | v[i].z | v[i].w) & 1u) == tag);
          if (__all_sync(~0u, ok)) need &= ~(1u << i);
        }
      } while (need && ++n < (1 << 18));
      float m[4] = {};
#pragma unroll
      for (int i = 0; i < 8; i++) { m[0] += __uint_as_float(v[i].x); m[1] += __uint_as_float(v[i].y); m[2] += __uint_as_float(v[i].z); m[3] += __uint_as_float(v[i].w); }
      __syncwarp();
      CP(12);
      uint32_t b0 = movm(pack_bf16(m[0], m[1])), b1 = movm(pack_bf16(m[2], m[3]));
      const uint32_t off = CH_MEM + (r * 4 + warp) * 256 + g * 16 + t * 4;
      const uint32_t cl0 = mapa_v(sb, 0), clstep = mapa_v(sb, 1) - cl0;
#pragma unroll
      for (int d = 0; d < 8; d++) { st_async1(cl0 + d * clstep + off, b0, cl0 + d * clstep + CH_BAR); st_async1(cl0 + d * clstep + off + 128, b1, cl0 + d * clstep + CH_BAR); }
    } else if (warp == 6) {
      const float* pb = pbase - lane * 4 + (32 + (r & ~1u)) * 128 + lane * 4 + (r & 1) * 2;
      uint2 v[16]; int n = 0; uint32_t need = 0xFF;
#pragma unroll
      for (int i = 0; i < 16; i++) v[i] = make_uint2(0, 0);
      do {
#pragma unroll
        for (int i = 0; i < 16; i++)
          asm volatile("{\n.reg .pred p;\nsetp.ne.b32 p, %3, 0;\n@p ld.relaxed.gpu.global.v2.b32 {%0,%1}, [%2];\n}" : "+r"(v[i].x), "+r"(v[i].y) : "l"(pb + (i >> 1) * 5120 + (i & 1) * 128), "r"(need & (1u << (i >> 1))) : "memory");
#pragma unroll
        for (int i = 0; i < 16; i += 2) {
          bool ok = ((v[i].x & v[i].y & v[i + 1].x & v[i + 1].y & 1u) == tag) && (((v[i].x | v[i].y | v[i + 1].x | v[i + 1].y) & 1u) == tag);
          if (__all_sync(~0u, ok)) need &= ~(1u << (i >> 1));
        }
      } while (need && ++n < (1 << 18));
      float m0 = 0.f, m1 = 0.f;
#pragma unroll
      for (int i = 0; i < 16; i++) { m0 += __uint_as_float(v[i].x); m1 += __uint_as_float(v[i].y); }
      __syncwarp();
      uint32_t b0 = movm(pack_bf16(m0, m1));
      const uint32_t off = CH_MEM + (32 + (r >> 1)) * 256 + (r & 1) * 128 + g * 16 + t * 4;
      const uint32_t cl0 = mapa_v(sb, 0), clstep = mapa_v(sb, 1) - cl0;
#pragma unroll
      for (int d = 0; d < 8; d++) st_async1(cl0 + d * clstep + off, b0, cl0 + d * clstep + CH_BAR);
    }
  }
  BAR_ALL();
  if (tid == 0) { __threadfence(); atomicAdd(&g_cnt[96 + NSEG - 1], 1); }
  if (blockIdx.x == 0 && tid == 0) PT(8);
  cluster_sync();
}
typedef CUresult (*EncodeFn)(CUtensorMap*, CUtensorMapDataType, cuuint32_t, void*, const cuuint64_t*, const cuuint64_t*, const cuuint32_t*, const cuuint32_t*,
                             CUtensorMapInterleave, CUtensorMapSwizzle, CUtensorMapL2promotion, CUtensorMapFloatOOBfill);
static EncodeFn g_enc;
static void mkmap(CUtensorMap* m, const void* ptr, int rows, int cols, int boxc, int boxr) {
  cuuint64_t dims[2] = {(cuuint64_t)cols, (cuuint64_t)rows}, strides[1] = {(cuuint64_t)cols * 2};
  cuuint32_t box[2] = {(cuuint32_t)boxc, (cuuint32_t)boxr}, es[2] = {1, 1};
  g_enc(m, CU_TENSOR_MAP_DATA_TYPE_BFLOAT16, 2, (void*)ptr, dims, strides, box, es, CU_TENSOR_MAP_INTERLEAVE_NONE, CU_TENSOR_MAP_SWIZZLE_128B,
        CU_TENSOR_MAP_L2_PROMOTION_L2_256B, CU_TENSOR_MAP_FLOAT_OOB_FILL_NONE);
}
#define URG 50.0
#define CHDT 3.6
constexpr double CH_T0 = 24.0, CH_DT = CHDT;
static inline uint16_t mkjob(int type, int m, int n) { return (uint16_t)(type << 12 | m << 6 | n); }
static void schedule_side(GemmParams& p, const uint16_t* base, int nb, int ncl) {
  static const double cost[8] = {7.6, 7.6, 7.6, 19.5, 56.0, 33.0, 12.5, 7.0};
  double t[66]; int cnt[66] = {};
  for (int c = 0; c < 66; c++) t[c] = 9.0;
  p.stride = 960 / ncl;
  for (int i = 0; i < 960; i++) p.job[i] = 0xFFFF;
  double g2_end = 0, q_end[8] = {}, g3_end[8] = {}, at_end[8] = {}; int qn[8] = {}, g3n[8] = {}, atn[8] = {};
  int bi = 0, ai = 0, gi = 0;
  while (bi < nb || ai < 96 || gi < 60) {
    int b = -1;
    for (int c = 0; c < ncl; c++) if (cnt[c] < p.stride && (b < 0 || t[c] < t[b] || (t[c] == t[b] && cnt[c] < cnt[b]))) b = c;
    const double inf = 1e30;
    int am = ai >> 4, gm = gi < 12 ? gi / 3 : 4 + (gi - 12) / 24;
    double ra = ai < 96 && qn[am] == 16 ? (q_end[am] > CH_T0 + CH_DT * (am * 8 + ((ai & 15) >> 1) + 2) ? q_end[am] : CH_T0 + CH_DT * (am * 8 + ((ai & 15) >> 1) + 2)) : inf;
    double rg = gi < 60 && atn[gm] == 16 && g3n[gm] == 3 ? (at_end[gm] > g3_end[gm] - 30 ? at_end[gm] : g3_end[gm] - 30) : inf;
    bool urgent = bi < nb && (base[bi] >> 12) >= 1 && (base[bi] >> 12) <= 2 && CH_T0 + CH_DT * 8 * ((base[bi] >> 6) & 63) - t[b] < URG;
    uint16_t job; double start = t[b];
    if (urgent) job = base[bi++];
    else if (rg <= t[b] || (bi >= nb && rg < inf && (rg <= ra || (gi < 60 && ai >= 96)))) { job = gi < 12 ? mkjob(5, gm, gi % 3) : mkjob(7, gm, (gi - 12) % 24); gi++; if (rg > start) start = rg; }
    else if (ra <= t[b] || bi >= nb) { job = mkjob(6, am, ai & 15); ai++; if (ra > start) start = ra; }
    else job = base[bi++];
    int ty = job >> 12, m = (job >> 6) & 63;
    if (ty == 4 && start < g2_end) start = g2_end;
    t[b] = start + cost[ty];
    if (ty == 3 && t[b] > g2_end) g2_end = t[b];
    if (ty == 0) { qn[m]++; if (t[b] > q_end[m]) q_end[m] = t[b]; }
    if (ty == 4) { g3n[m]++; if (t[b] > g3_end[m]) g3_end[m] = t[b]; }
    if (ty == 6) { atn[m]++; if (t[b] > at_end[m]) at_end[m] = t[b]; }
    p.job[b * p.stride + cnt[b]++] = job;
  }
}
template <class... A>
static void launch(void (*k)(A...), int grid, int block, int smem, int cluster, bool pdl, A... a) {
  cudaLaunchConfig_t c = {};
  c.gridDim = grid; c.blockDim = block; c.dynamicSmemBytes = smem; c.stream = cudaStreamPerThread;
  cudaLaunchAttribute at[2]; int n = 0;
  if (cluster > 1) { at[n].id = cudaLaunchAttributeClusterDimension; at[n].val.clusterDim.x = cluster; at[n].val.clusterDim.y = 1; at[n].val.clusterDim.z = 1; n++; }
  if (pdl) { at[n].id = cudaLaunchAttributeProgrammaticStreamSerialization; at[n].val.programmaticStreamSerializationAllowed = 1; n++; }
  c.attrs = at; c.numAttrs = n;
  cudaLaunchKernelEx(&c, k, a...);
}

extern "C" void kernel_launch(void* const* d_in, const int* in_sizes, int n_in, void* d_out, int out_size) {
  const bf16 *x = (const bf16*)d_in[0], *mem0 = (const bf16*)d_in[1], *Wq = (const bf16*)d_in[2], *Wk = (const bf16*)d_in[3], *Wv = (const bf16*)d_in[4],
             *Wo = (const bf16*)d_in[5], *w1 = (const bf16*)d_in[8], *b1 = (const bf16*)d_in[9], *w2 = (const bf16*)d_in[10], *b2 = (const bf16*)d_in[11];
  static bool init = false;
  static GemmParams side, post;
  if (!init) {
    init = true;
    cudaDriverEntryPointQueryResult qr;
    cudaGetDriverEntryPoint("cuTensorMapEncodeTiled", (void**)&g_enc, cudaEnableDefault, &qr);
    void *xn, *h2, *o, *ut;
    cudaGetSymbolAddress(&xn, g_xn); cudaGetSymbolAddress(&h2, g_h2); cudaGetSymbolAddress(&o, g_o); cudaGetSymbolAddress(&ut, g_ut);
    GemmParams b = {};
    mkmap(&b.mA[0], xn, S_, D_, 64, 128); mkmap(&b.mA[1], w1, S_, F_, 64, 64); mkmap(&b.mA[2], w2, F_, S_, 64, 64); mkmap(&b.mA[3], o, S_, HD_, 64, 128);
    mkmap(&b.mB[0], Wq, D_, HD_, 64, 32); mkmap(&b.mB[1], Wk, D_, HD_, 64, 32); mkmap(&b.mB[2], Wv, D_, HD_, 64, 32);
    mkmap(&b.mB[3], h2, S_, D_, 64, 32); mkmap(&b.mB[4], ut, F_, D_, 64, 32); mkmap(&b.mB[5], Wo, HD_, D_, 64, 32);
    b.x = x; b.b1 = b1; b.b2 = b2; b.out = (bf16*)d_out;
    side = b; post = b; side.kid = 1; post.kid = 2;
    static uint16_t jl[1024]; int n = 0;
    auto kv = [&](int m) { for (int j = 0; j < 16; j++) { jl[n++] = mkjob(1, m, j); jl[n++] = mkjob(2, m, j); } };
    auto qq = [&](int m) { for (int j = 0; j < 16; j++) jl[n++] = mkjob(0, m, j); };
    kv(0); kv(1);
    for (int m = 0; m < 18; m++) for (int j = 0; j < 3; j++) jl[n++] = mkjob(3, m, j);
    kv(2); qq(0); kv(3); qq(1);
    for (int m = 0; m < 8; m++) for (int j = 0; j < 3; j++) jl[n++] = mkjob(4, m, j);
    for (int m = 4; m < 8; m++) { kv(m); qq(m - 2); }
    qq(6); qq(7);
    schedule_side(side, jl, n, 34);
    side.wait_at_end = 0;
    post.stride = 2;
    for (int i = 0; i < 960; i++) post.job[i] = 0xFFFF;
    for (int i = 0; i < 48; i++) {
      if (i < 32) { post.job[i * 2] = mkjob(6, 6 + (i >> 4), i & 15); post.job[i * 2 + 1] = mkjob(7, 6 + i / 24, i % 24); }
      else post.job[i * 2] = mkjob(7, 6 + i / 24, i % 24);
    }
    cudaFuncSetAttribute(gemm_kernel, cudaFuncAttributeMaxDynamicSharedMemorySize, GEMM_SMEM);
    cudaFuncSetAttribute(chain_kernel, cudaFuncAttributeMaxDynamicSharedMemorySize, CHAIN_SMEM);
  }
  launch(ln_kernel, 256, 256, 0, 1, false, x);
  launch(chain_kernel, 64, 256, CHAIN_SMEM, 8, false, mem0, Wq, Wk, Wv, Wo);
  launch(gemm_kernel, 68, 384, GEMM_SMEM, 2, true, side);
  launch(gemm_kernel, 96, 384, GEMM_SMEM, 2, true, post);
}
```

```cpp
#include <cuda_runtime.h>
#include <cuda_bf16.h>
#include <cuda.h>
#include <stdint.h>

typedef __nv_bfloat16 bf16;
constexpr int S_ = 2048, D_ = 576, HD_ = 4096, F_ = 4608, NSEG = 64;

__device__ bf16 g_xn[S_ * D_];
__device__ bf16 g_h2[S_ * D_];
__device__ bf16 g_q[S_ * HD_];
__device__ bf16 g_k[S_ * HD_];
__device__ bf16 g_v[S_ * HD_];
__device__ bf16 g_o[S_ * HD_];
__device__ bf16 g_km[NSEG * 8 * HD_];
__device__ bf16 g_vm[NSEG * 8 * HD_];
__device__ bf16 g_ut[F_ * D_];
__device__ float g_yb[S_ * D_];
__device__ float g_pk[8 * 512 * D_];
__device__ float g_part[2 * 8 * 8 * 5 * 32 * 4];
__device__ unsigned int g_cnt[192];

#define PT(i)
#define PC(i)
__device__ __forceinline__ uint32_t smem_u32(const void* p) { return (uint32_t)__cvta_generic_to_shared(p); }
__device__ __forceinline__ void mbar_init(uint32_t b, uint32_t c) { asm volatile("mbarrier.init.shared::cta.b64 [%0], %1;" ::"r"(b), "r"(c)); }
__device__ __forceinline__ void mbar_expect(uint32_t b, uint32_t bytes) { asm volatile("mbarrier.arrive.expect_tx.shared::cta.b64 _, [%0], %1;" ::"r"(b), "r"(bytes) : "memory"); }
__device__ __forceinline__ void mbar_wait(uint32_t b, uint32_t parity) {
  uint32_t ok;
  do { asm volatile("{\n.reg .pred p;\nmbarrier.try_wait.parity.shared::cta.b64 p, [%1], %2;\nselp.u32 %0, 1, 0, p;\n}" : "=r"(ok) : "r"(b), "r"(parity) : "memory"); } while (!ok);
}
__device__ __forceinline__ void mbar_wait_cl(uint32_t b, uint32_t parity) {
  uint32_t ok;
  do { asm volatile("{\n.reg .pred p;\nmbarrier.try_wait.parity.shared::cta.b64 p, [%1], %2;\nselp.u32 %0, 1, 0, p;\n}" : "=r"(ok) : "r"(b), "r"(parity) : "memory"); } while (!ok);
}
__device__ __forceinline__ uint32_t mapa(uint32_t a, uint32_t r) { uint32_t o; asm("mapa.shared::cluster.u32 %0, %1, %2;" : "=r"(o) : "r"(a), "r"(r)); return o; }
__device__ __forceinline__ void mbar_arrive_remote(uint32_t remote_b) { asm volatile("mbarrier.arrive.shared::cluster.b64 _, [%0];" ::"r"(remote_b) : "memory"); }
__device__ __forceinline__ uint32_t cluster_rank() { uint32_t r; asm("mov.u32 %0, %%cluster_ctarank;" : "=r"(r)); return r; }
__device__ __forceinline__ void cluster_sync() { asm volatile("barrier.cluster.arrive.release.aligned;\nbarrier.cluster.wait.acquire.aligned;" ::: "memory"); }
__device__ __forceinline__ void tma2d(uint32_t dst, const CUtensorMap* m, int c0, int c1, uint32_t bar) {
  asm volatile("cp.async.bulk.tensor.2d.shared::cluster.global.mbarrier::complete_tx::bytes [%0], [%1, {%3, %4}], [%2];"
               ::"r"(dst), "l"(m), "r"(bar), "r"(c0), "r"(c1) : "memory");
}
__device__ __forceinline__ void tma2d_mc(uint32_t dst, const CUtensorMap* m, int c0, int c1, uint32_t bar, uint16_t mask) {
  asm volatile("cp.async.bulk.tensor.2d.shared::cluster.global.mbarrier::complete_tx::bytes.multicast::cluster [%0], [%1, {%3, %4}], [%2], %5;"
               ::"r"(dst), "l"(m), "r"(bar), "r"(c0), "r"(c1), "h"(mask) : "memory");
}
__device__ __forceinline__ uint32_t pack_bf16(float a, float b) { __nv_bfloat162 t = __floats2bfloat162_rn(a, b); return *(uint32_t*)&t; }
__device__ __forceinline__ float2 unpack_bf16(uint32_t u) { return __bfloat1622float2(*(__nv_bfloat162*)&u); }
__device__ __forceinline__ void mma16816(float (&c)[4], const uint32_t (&a)[4], uint32_t b0, uint32_t b1) {
  asm volatile("mma.sync.aligned.m16n8k16.row.col.f32.bf16.bf16.f32 {%0,%1,%2,%3},{%4,%5,%6,%7},{%8,%9},{%0,%1,%2,%3};"
               : "+f"(c[0]), "+f"(c[1]), "+f"(c[2]), "+f"(c[3]) : "r"(a[0]), "r"(a[1]), "r"(a[2]), "r"(a[3]), "r"(b0), "r"(b1));
}
__device__ __forceinline__ void ldsm4(uint32_t (&r)[4], uint32_t a) { asm volatile("ldmatrix.sync.aligned.m8n8.x4.shared.b16 {%0,%1,%2,%3},[%4];" : "=r"(r[0]), "=r"(r[1]), "=r"(r[2]), "=r"(r[3]) : "r"(a) : "memory"); }
__device__ __forceinline__ void ldsm4t(uint32_t (&r)[4], uint32_t a) { asm volatile("ldmatrix.sync.aligned.m8n8.x4.trans.shared.b16 {%0,%1,%2,%3},[%4];" : "=r"(r[0]), "=r"(r[1]), "=r"(r[2]), "=r"(r[3]) : "r"(a) : "memory"); }
__device__ __forceinline__ uint32_t movm(uint32_t a) { uint32_t o; asm volatile("movmatrix.sync.aligned.m8n8.trans.b16 %0, %1;" : "=r"(o) : "r"(a)); return o; }
__device__ __forceinline__ void cp16(uint32_t dst, const void* src) { asm volatile("cp.async.cg.shared.global [%0], [%1], 16;" ::"r"(dst), "l"(src) : "memory"); }
__device__ __forceinline__ void pdl_wait() { asm volatile("griddepcontrol.wait;" ::: "memory"); }
__device__ __forceinline__ void pdl_launch() { asm volatile("griddepcontrol.launch_dependents;" ::: "memory"); }

__device__ __forceinline__ void wait_cnt(const unsigned int* c, unsigned int target) {
  uint32_t v; int n = 0;
  do { asm volatile("ld.acquire.gpu.global.u32 %0, [%1];" : "=r"(v) : "l"(c) : "memory"); if (v >= target) break; __nanosleep(64); } while (++n < (1 << 22));
}
__global__ void __launch_bounds__(256) ln_kernel(const bf16* __restrict__ x) {
  int row = blockIdx.x * 8 + (threadIdx.x >> 5), lane = threadIdx.x & 31;
  if (blockIdx.x == 0 && threadIdx.x < 192) { g_cnt[threadIdx.x] = 0; if (threadIdx.x == 0) PT(0); }
  for (int i = blockIdx.x * 256 + threadIdx.x; i < 2 * 64 * 640; i += 256 * 256) g_part[i] = 0.f;
  const uint32_t* xr = (const uint32_t*)(x + (size_t)row * D_);
  float v[18]; float s = 0.f;
#pragma unroll
  for (int i = 0; i < 9; i++) { float2 f = unpack_bf16(xr[lane + 32 * i]); v[2 * i] = f.x; v[2 * i + 1] = f.y; s += f.x + f.y; }
#pragma unroll
  for (int pass = 0; pass < 2; pass++) {
#pragma unroll
    for (int o = 16; o; o >>= 1) s += __shfl_xor_sync(~0u, s, o);
    float m = s * (1.f / D_), q = 0.f;
#pragma unroll
    for (int i = 0; i < 18; i++) { v[i] -= m; q += v[i] * v[i]; }
#pragma unroll
    for (int o = 16; o; o >>= 1) q += __shfl_xor_sync(~0u, q, o);
    float r = 1.f / sqrtf(q * (1.f / D_) + 1e-5f);
    uint32_t* dst = (uint32_t*)((pass == 0 ? g_xn : g_h2) + (size_t)row * D_);
    s = 0.f;
#pragma unroll
    for (int i = 0; i < 9; i++) {
      uint32_t p = pack_bf16(v[2 * i] * r, v[2 * i + 1] * r);
      dst[lane + 32 * i] = p;
      float2 f = unpack_bf16(p); v[2 * i] = f.x; v[2 * i + 1] = f.y; s += f.x + f.y;
    }
  }
}

template<int TA> __device__ __forceinline__ void wgmma_n256(float (&d)[128], uint64_t da, uint64_t db, int sc) {
  asm volatile("{\n.reg .pred p;\nsetp.ne.b32 p, %130, 0;\n"
    "wgmma.mma_async.sync.aligned.m64n256k16.f32.bf16.bf16 {%0, %1, %2, %3, %4, %5, %6, %7, %8, %9, %10, %11, %12, %13, %14, %15, %16, %17, %18, %19, %20, %21, %22, %23, %24, %25, %26, %27, %28, %29, %30, %31, %32, %33, %34, %35, %36, %37, %38, %39, %40, %41, %42, %43, %44, %45, %46, %47, %48, %49, %50, %51, %52, %53, %54, %55, %56, %57, %58, %59, %60, %61, %62, %63, %64, %65, %66, %67, %68, %69, %70, %71, %72, %73, %74, %75, %76, %77, %78, %79, %80, %81, %82, %83, %84, %85, %86, %87, %88, %89, %90, %91, %92, %93, %94, %95, %96, %97, %98, %99, %100, %101, %102, %103, %104, %105, %106, %107, %108, %109, %110, %111, %112, %113, %114, %115, %116, %117, %118, %119, %120, %121, %122, %123, %124, %125, %126, %127}, %128, %129, p, 1, 1, %131, 1;\n}\n"
    : "+f"(d[0]), "+f"(d[1]), "+f"(d[2]), "+f"(d[3]), "+f"(d[4]), "+f"(d[5]), "+f"(d[6]), "+f"(d[7]), "+f"(d[8]), "+f"(d[9]), "+f"(d[10]), "+f"(d[11]), "+f"(d[12]), "+f"(d[13]), "+f"(d[14]), "+f"(d[15]), "+f"(d[16]), "+f"(d[17]), "+f"(d[18]), "+f"(d[19]), "+f"(d[20]), "+f"(d[21]), "+f"(d[22]), "+f"(d[23]), "+f"(d[24]), "+f"(d[25]), "+f"(d[26]), "+f"(d[27]), "+f"(d[28]), "+f"(d[29]), "+f"(d[30]), "+f"(d[31]), "+f"(d[32]), "+f"(d[33]), "+f"(d[34]), "+f"(d[35]), "+f"(d[36]), "+f"(d[37]), "+f"(d[38]), "+f"(d[39]), "+f"(d[40]), "+f"(d[41]), "+f"(d[42]), "+f"(d[43]), "+f"(d[44]), "+f"(d[45]), "+f"(d[46]), "+f"(d[47]), "+f"(d[48]), "+f"(d[49]), "+f"(d[50]), "+f"(d[51]), "+f"(d[52]), "+f"(d[53]), "+f"(d[54]), "+f"(d[55]), "+f"(d[56]), "+f"(d[57]), "+f"(d[58]), "+f"(d[59]), "+f"(d[60]), "+f"(d[61]), "+f"(d[62]), "+f"(d[63]), "+f"(d[64]), "+f"(d[65]), "+f"(d[66]), "+f"(d[67]), "+f"(d[68]), "+f"(d[69]), "+f"(d[70]), "+f"(d[71]), "+f"(d[72]), "+f"(d[73]), "+f"(d[74]), "+f"(d[75]), "+f"(d[76]), "+f"(d[77]), "+f"(d[78]), "+f"(d[79]), "+f"(d[80]), "+f"(d[81]), "+f"(d[82]), "+f"(d[83]), "+f"(d[84]), "+f"(d[85]), "+f"(d[86]), "+f"(d[87]), "+f"(d[88]), "+f"(d[89]), "+f"(d[90]), "+f"(d[91]), "+f"(d[92]), "+f"(d[93]), "+f"(d[94]), "+f"(d[95]), "+f"(d[96]), "+f"(d[97]), "+f"(d[98]), "+f"(d[99]), "+f"(d[100]), "+f"(d[101]), "+f"(d[102]), "+f"(d[103]), "+f"(d[104]), "+f"(d[105]), "+f"(d[106]), "+f"(d[107]), "+f"(d[108]), "+f"(d[109]), "+f"(d[110]), "+f"(d[111]), "+f"(d[112]), "+f"(d[113]), "+f"(d[114]), "+f"(d[115]), "+f"(d[116]), "+f"(d[117]), "+f"(d[118]), "+f"(d[119]), "+f"(d[120]), "+f"(d[121]), "+f"(d[122]), "+f"(d[123]), "+f"(d[124]), "+f"(d[125]), "+f"(d[126]), "+f"(d[127])
    : "l"(da), "l"(db), "r"(sc), "n"(TA));
}

template<int TA> __device__ __forceinline__ void wgmma_n192(float (&d)[128], uint64_t da, uint64_t db, int sc) {
  asm volatile("{\n.reg .pred p;\nsetp.ne.b32 p, %98, 0;\n"
    "wgmma.mma_async.sync.aligned.m64n192k16.f32.bf16.bf16 {%0, %1, %2, %3, %4, %5, %6, %7, %8, %9, %10, %11, %12, %13, %14, %15, %16, %17, %18, %19, %20, %21, %22, %23, %24, %25, %26, %27, %28, %29, %30, %31, %32, %33, %34, %35, %36, %37, %38, %39, %40, %41, %42, %43, %44, %45, %46, %47, %48, %49, %50, %51, %52, %53, %54, %55, %56, %57, %58, %59, %60, %61, %62, %63, %64, %65, %66, %67, %68, %69, %70, %71, %72, %73, %74, %75, %76, %77, %78, %79, %80, %81, %82, %83, %84, %85, %86, %87, %88, %89, %90, %91, %92, %93, %94, %95}, %96, %97, p, 1, 1, %99, 1;\n}\n"
    : "+f"(d[0]), "+f"(d[1]), "+f"(d[2]), "+f"(d[3]), "+f"(d[4]), "+f"(d[5]), "+f"(d[6]), "+f"(d[7]), "+f"(d[8]), "+f"(d[9]), "+f"(d[10]), "+f"(d[11]), "+f"(d[12]), "+f"(d[13]), "+f"(d[14]), "+f"(d[15]), "+f"(d[16]), "+f"(d[17]), "+f"(d[18]), "+f"(d[19]), "+f"(d[20]), "+f"(d[21]), "+f"(d[22]), "+f"(d[23]), "+f"(d[24]), "+f"(d[25]), "+f"(d[26]), "+f"(d[27]), "+f"(d[28]), "+f"(d[29]), "+f"(d[30]), "+f"(d[31]), "+f"(d[32]), "+f"(d[33]), "+f"(d[34]), "+f"(d[35]), "+f"(d[36]), "+f"(d[37]), "+f"(d[38]), "+f"(d[39]), "+f"(d[40]), "+f"(d[41]), "+f"(d[42]), "+f"(d[43]), "+f"(d[44]), "+f"(d[45]), "+f"(d[46]), "+f"(d[47]), "+f"(d[48]), "+f"(d[49]), "+f"(d[50]), "+f"(d[51]), "+f"(d[52]), "+f"(d[53]), "+f"(d[54]), "+f"(d[55]), "+f"(d[56]), "+f"(d[57]), "+f"(d[58]), "+f"(d[59]), "+f"(d[60]), "+f"(d[61]), "+f"(d[62]), "+f"(d[63]), "+f"(d[64]), "+f"(d[65]), "+f"(d[66]), "+f"(d[67]), "+f"(d[68]), "+f"(d[69]), "+f"(d[70]), "+f"(d[71]), "+f"(d[72]), "+f"(d[73]), "+f"(d[74]), "+f"(d[75]), "+f"(d[76]), "+f"(d[77]), "+f"(d[78]), "+f"(d[79]), "+f"(d[80]), "+f"(d[81]), "+f"(d[82]), "+f"(d[83]), "+f"(d[84]), "+f"(d[85]), "+f"(d[86]), "+f"(d[87]), "+f"(d[88]), "+f"(d[89]), "+f"(d[90]), "+f"(d[91]), "+f"(d[92]), "+f"(d[93]), "+f"(d[94]), "+f"(d[95])
    : "l"(da), "l"(db), "r"(sc), "n"(TA));
}

struct GemmParams {
  CUtensorMap mA[4];
  CUtensorMap mB[6];
  const bf16* x; const bf16* b1; const bf16* b2; bf16* out;
  int stride, kid;
  int wait_at_end;
  uint16_t job[960];
};
constexpr int NSTAGE = 4, STAGE_BYTES = 49152;
constexpr int GEMM_SMEM = NSTAGE * STAGE_BYTES + 8 * 2048 + 256 + 1024;

__device__ __forceinline__ uint64_t mkdesc(uint32_t addr, uint32_t lbo, uint32_t sbo) {
  return (uint64_t)((addr & 0x3FFFF) >> 4) | ((uint64_t)(lbo >> 4) << 16) | ((uint64_t)(sbo >> 4) << 32) | (1ull << 62);
}
__device__ __forceinline__ float gelu_tanh(float u) {
  float z = 0.7978845608028654f * (u + 0.044715f * u * u * u);
  float e = __expf(2.f * z);
  float th = 1.f - __fdividef(2.f, e + 1.f);
  return 0.5f * u * (1.f + th);
}
template <int BN, int TA>
__device__ __forceinline__ void gemm_mainloop(float (&d)[128], int kiters, uint32_t sbase, uint32_t fullb, uint32_t emptyb_l, uint32_t emptyb_r,
                                              int wg, int& stage, uint32_t& phase, bool elect) {
  int prev = -1;
  for (int k = 0; k < kiters; k++) {
    mbar_wait(fullb + stage * 8, phase);
    uint32_t a = sbase + stage * STAGE_BYTES + wg * 8192, b = sbase + stage * STAGE_BYTES + 16384;
    asm volatile("wgmma.fence.sync.aligned;" ::: "memory");
#pragma unroll
    for (int kk = 0; kk < 4; kk++) {
      uint64_t da = TA ? mkdesc(a + kk * 2048, 8192, 1024) : mkdesc(a + kk * 32, 16, 1024);
      uint64_t db = mkdesc(b + kk * 2048, 8192, 1024);
      if constexpr (BN == 256) wgmma_n256<TA>(d, da, db, (k | kk) != 0); else wgmma_n192<TA>(d, da, db, (k | kk) != 0);
    }
    asm volatile("wgmma.commit_group.sync.aligned;" ::: "memory");
    asm volatile("wgmma.wait_group.sync.aligned 1;" ::: "memory");
    if (prev >= 0 && elect) { mbar_arrive_remote(emptyb_l + prev * 8); mbar_arrive_remote(emptyb_r + prev * 8); }
    prev = stage;
    if (++stage == NSTAGE) { stage = 0; phase ^= 1; }
  }
  asm volatile("wgmma.wait_group.sync.aligned 0;" ::: "memory");
  if (elect) { mbar_arrive_remote(emptyb_l + prev * 8); mbar_arrive_remote(emptyb_r + prev * 8); }
}
template <int BN, class F>
__device__ __forceinline__ void store_tile(const float (&d)[128], uint32_t stg, bf16* dst, int ld, int lane, F f) {
#pragma unroll
  for (int c = 0; c < BN / 64; c++) {
#pragma unroll
    for (int i = 0; i < 8; i += 2) {
      const int o = c * 32 + i * 4;
      uint32_t r0 = f(d[o], d[o + 1], 0, c * 64 + i * 8), r1 = f(d[o + 2], d[o + 3], 1, c * 64 + i * 8);
      uint32_t r2 = f(d[o + 4], d[o + 5], 0, c * 64 + i * 8 + 8), r3 = f(d[o + 6], d[o + 7], 1, c * 64 + i * 8 + 8);
      int m = lane >> 3, row = (m & 1) * 8 + (lane & 7), ch = (i + (m >> 1)) ^ (row & 7);
      asm volatile("stmatrix.sync.aligned.m8n8.x4.shared.b16 [%0], {%1,%2,%3,%4};" ::"r"(stg + row * 128 + ch * 16), "r"(r0), "r"(r1), "r"(r2), "r"(r3) : "memory");
    }
    __syncwarp();
#pragma unroll
    for (int j = 0; j < 4; j++) {
      int idx = lane + 32 * j, row = idx >> 3, ch = idx & 7;
      uint4 v;
      asm volatile("ld.shared.v4.u32 {%0,%1,%2,%3}, [%4];" : "=r"(v.x), "=r"(v.y), "=r"(v.z), "=r"(v.w) : "r"(stg + row * 128 + ((ch ^ (row & 7)) * 16)));
      *(uint4*)(dst + (size_t)row * ld + c * 64 + ch * 8) = v;
    }
    __syncwarp();
  }
}

__device__ __forceinline__ void attn_unit(int seg, int h, uint8_t* sm, int lane) {
  const int g = lane >> 2, t = lane & 3;
  const uint32_t sv = smem_u32(sm);
  const size_t tok0 = (size_t)seg * 32;
  for (int i = lane; i < 40 * 16; i += 32) {
    int r = i >> 4, c = i & 15;
    const bf16* src = (r < 8 ? g_vm + ((size_t)seg * 8 + r) * HD_ : g_v + (tok0 + r - 8) * HD_) + h * 128 + c * 8;
    cp16(sv + r * 256 + ((c ^ (r & 7)) * 16), src);
  }
  for (int i = lane; i < 8 * 16; i += 32) *(uint4*)(sm + 40 * 256 + i * 16) = make_uint4(0, 0, 0, 0);
  asm volatile("cp.async.commit_group;" ::: "memory");
  float s[2][5][4];
#pragma unroll
  for (int m = 0; m < 2; m++)
#pragma unroll
    for (int n = 0; n < 5; n++) { s[m][n][0] = s[m][n][1] = s[m][n][2] = s[m][n][3] = 0.f; }
#pragma unroll
  for (int j = 0; j < 4; j++) {
    uint4 qa[2][2], kb[5];
#pragma unroll
    for (int m = 0; m < 2; m++)
#pragma unroll
      for (int hh = 0; hh < 2; hh++) qa[m][hh] = *(const uint4*)(g_q + (tok0 + m * 16 + hh * 8 + g) * HD_ + h * 128 + j * 32 + t * 8);
#pragma unroll
    for (int n = 0; n < 5; n++)
      kb[n] = *(const uint4*)((n == 0 ? g_km + ((size_t)seg * 8 + g) * HD_ : g_k + (tok0 + (n - 1) * 8 + g) * HD_) + h * 128 + j * 32 + t * 8);
#pragma unroll
    for (int m = 0; m < 2; m++) {
      uint32_t a0[4] = {qa[m][0].x, qa[m][1].x, qa[m][0].y, qa[m][1].y}, a1[4] = {qa[m][0].z, qa[m][1].z, qa[m][0].w, qa[m][1].w};
#pragma unroll
      for (int n = 0; n < 5; n++) { mma16816(s[m][n], a0, kb[n].x, kb[n].y); mma16816(s[m][n], a1, kb[n].z, kb[n].w); }
    }
  }
  const float sc = 0.08838834764831845f * 1.4426950408889634f;
  uint32_t pa[2][3][4];
#pragma unroll
  for (int m = 0; m < 2; m++) {
    float inv[2];
#pragma unroll
    for (int hh = 0; hh < 2; hh++) {
      int qi = 8 + m * 16 + hh * 8 + g;
      float mx = -INFINITY;
#pragma unroll
      for (int n = 0; n < 5; n++)
#pragma unroll
        for (int e = 0; e < 2; e++) { float& z = s[m][n][hh * 2 + e]; z = (n * 8 + t * 2 + e <= qi) ? z * sc : -INFINITY; mx = fmaxf(mx, z); }
      mx = fmaxf(mx, __shfl_xor_sync(~0u, mx, 1)); mx = fmaxf(mx, __shfl_xor_sync(~0u, mx, 2));
      float sum = 0.f;
#pragma unroll
      for (int n = 0; n < 5; n++)
#pragma unroll
        for (int e = 0; e < 2; e++) { float& z = s[m][n][hh * 2 + e]; z = exp2f(z - mx); sum += z; }
      sum += __shfl_xor_sync(~0u, sum, 1); sum += __shfl_xor_sync(~0u, sum, 2);
      inv[hh] = 1.f / sum;
    }
#pragma unroll
    for (int kk = 0; kk < 3; kk++) {
      pa[m][kk][0] = pack_bf16(s[m][2 * kk][0] * inv[0], s[m][2 * kk][1] * inv[0]);
      pa[m][kk][1] = pack_bf16(s[m][2 * kk][2] * inv[1], s[m][2 * kk][3] * inv[1]);
      if (kk < 2) {
        pa[m][kk][2] = pack_bf16(s[m][2 * kk + 1][0] * inv[0], s[m][2 * kk + 1][1] * inv[0]);
        pa[m][kk][3] = pack_bf16(s[m][2 * kk + 1][2] * inv[1], s[m][2 * kk + 1][3] * inv[1]);
      } else { pa[m][kk][2] = 0; pa[m][kk][3] = 0; }
    }
  }
  asm volatile("cp.async.wait_group 0;" ::: "memory");
  __syncwarp();
  uint32_t ov[2][16][2];
#pragma unroll
  for (int np = 0; np < 8; np++) {
    float o[2][2][4] = {};
#pragma unroll
    for (int kk = 0; kk < 3; kk++) {
      uint32_t b[4];
      int mi = lane >> 3, r = kk * 16 + (mi & 1) * 8 + (lane & 7), c = np * 2 + (mi >> 1);
      ldsm4t(b, sv + r * 256 + ((c ^ (r & 7)) * 16));
#pragma unroll
      for (int m = 0; m < 2; m++) { mma16816(o[m][0], pa[m][kk], b[0], b[1]); mma16816(o[m][1], pa[m][kk], b[2], b[3]); }
    }
#pragma unroll
    for (int m = 0; m < 2; m++)
#pragma unroll
      for (int q = 0; q < 2; q++) { ov[m][np * 2 + q][0] = pack_bf16(o[m][q][0], o[m][q][1]); ov[m][np * 2 + q][1] = pack_bf16(o[m][q][2], o[m][q][3]); }
  }
  __syncwarp();
#pragma unroll
  for (int m = 0; m < 2; m++)
#pragma unroll
    for (int n = 0; n < 16; n++)
#pragma unroll
      for (int hh = 0; hh < 2; hh++) {
        int r = m * 16 + hh * 8 + g;
        *(uint32_t*)(sm + r * 256 + ((n ^ (r & 7)) * 16) + t * 4) = ov[m][n][hh];
      }
  __syncwarp();
#pragma unroll
  for (int i = 0; i < 16; i++) {
    int idx = lane + 32 * i, r = idx >> 4, c = idx & 15;
    *(uint4*)(g_o + (tok0 + r) * HD_ + h * 128 + c * 8) = *(const uint4*)(sm + r * 256 + ((c ^ (r & 7)) * 16));
  }
}

__global__ void __launch_bounds__(384, 1) gemm_kernel(const __grid_constant__ GemmParams p) {
  extern __shared__ uint8_t smem_raw[];
  const uint32_t sbase = (smem_u32(smem_raw) + 1023) & ~1023u;
  const uint32_t stg0 = sbase + NSTAGE * STAGE_BYTES, fullb = stg0 + 8 * 2048, emptyb = fullb + 64;
  const uint32_t rank = cluster_rank();
  const int wg = __shfl_sync(~0u, (int)(threadIdx.x >> 7), 0), lane = threadIdx.x & 31;
  const int cl = blockIdx.x >> 1;
  if (threadIdx.x == 0) {
    for (int i = 0; i < NSTAGE; i++) { mbar_init(fullb + i * 8, 1); mbar_init(emptyb + i * 8, 4); }
    asm volatile("fence.mbarrier_init.release.cluster;" ::: "memory");
  }
  cluster_sync();
  pdl_launch();
  if (blockIdx.x == 0 && threadIdx.x == 0) PT(1 + p.kid * 2);
  const uint16_t* jobs = p.job + cl * p.stride;
  if (wg == 0) {
    asm volatile("setmaxnreg.dec.sync.aligned.u32 40;");
    if (threadIdx.x == 0) {
      int stage = 0; uint32_t phase = 1;
      for (int j = 0; j < p.stride; j++) {
        uint32_t job = jobs[j];
        if (job == 0xFFFF) break;
        int type = job >> 12, m = (job >> 6) & 63, n = job & 63;
        int row0 = m * 256 + rank * 128;
        int bn = type < 3 ? 256 : 192;
        if (type == 6) {
          for (int k = 0; k < NSTAGE; k++) {
            mbar_wait_cl(emptyb + stage * 8, phase);
            asm volatile("mbarrier.arrive.shared::cta.b64 _, [%0];" ::"r"(fullb + stage * 8) : "memory");
            if (++stage == NSTAGE) { stage = 0; phase ^= 1; }
          }
          continue;
        }
        int kit = type < 3 ? 9 : (type == 3 ? 32 : (type == 4 ? 72 : (type == 5 ? 64 : 8)));
        int k0 = 0;
        if (type == 7) { k0 = (n / 3) * 8; n = n % 3; type = 5; }
        if (type == 5) wait_cnt(&g_cnt[16 + m], 32);
        const CUtensorMap* ma = &p.mA[type < 3 ? 0 : type - 2];
        const CUtensorMap* mb = &p.mB[type];
        bool ta = (type == 3 || type == 4);
        if (type >= 4) {
          if (type == 4) wait_cnt(&g_cnt[0], 108);
          asm volatile("fence.proxy.async;" ::: "memory");
        }
        for (int k = k0; k < k0 + kit; k++) {
          mbar_wait_cl(emptyb + stage * 8, phase);
          uint32_t fb = fullb + stage * 8, a = sbase + stage * STAGE_BYTES, b = a + 16384;
          mbar_expect(fb, 16384 + bn * 128);
          if (ta) { tma2d(a, ma, row0, k * 64, fb); tma2d(a + 8192, ma, row0 + 64, k * 64, fb); }
          else tma2d(a, ma, k * 64, row0, fb);
          for (int i = 0; i < bn / 64; i++) tma2d_mc(b + i * 8192 + rank * 4096, mb, n * bn + i * 64, k * 64 + rank * 32, fb, (uint16_t)3);
          if (++stage == NSTAGE) { stage = 0; phase ^= 1; }
        }
      }
    }
    __syncwarp();
    if (p.wait_at_end) pdl_wait();
    cluster_sync();
  } else {
    asm volatile("setmaxnreg.inc.sync.aligned.u32 232;");
    const int cw = wg - 1, warp = __shfl_sync(~0u, (int)(threadIdx.x >> 5) & 3, 0);
    const uint32_t eb_l = mapa(emptyb, rank), eb_r = mapa(emptyb, rank ^ 1);
    const uint32_t stg = stg0 + (cw * 4 + warp) * 2048;
    const bool elect = (threadIdx.x & 127) == 0;
    const int g = lane >> 2, t = lane & 3;
    int stage = 0; uint32_t phase = 0;
    float d[128];
    for (int j = 0; j < p.stride; j++) {
      uint32_t job = jobs[j];
      if (job == 0xFFFF) break;
      int type = job >> 12, m = (job >> 6) & 63, n = job & 63;
      int row0 = m * 256 + rank * 128 + cw * 64 + warp * 16;
      if (type < 3) {
        gemm_mainloop<256, 0>(d, 9, sbase, fullb, eb_l, eb_r, cw, stage, phase, elect);
        bf16* dst = (type == 0 ? g_q : (type == 1 ? g_k : g_v)) + (size_t)row0 * HD_ + n * 256;
        store_tile<256>(d, stg, dst, HD_, lane, [](float a, float b, int, int) { return pack_bf16(a, b); });
        __threadfence();
        asm volatile("bar.sync %0, 256;" ::"r"(1) : "memory");
        if (threadIdx.x == 128) atomicAdd(&g_cnt[(type ? 8 : 40) + m], 1);
      } else if (type == 3) {
        gemm_mainloop<192, 1>(d, 32, sbase, fullb, eb_l, eb_r, cw, stage, phase, elect);
        float bb[2] = {__bfloat162float(p.b1[row0 + g]), __bfloat162float(p.b1[row0 + g + 8])};
        store_tile<192>(d, stg, g_ut + (size_t)row0 * D_ + n * 192, D_, lane,
                        [&](float a, float b, int h, int) { return pack_bf16(gelu_tanh(a + bb[h]), gelu_tanh(b + bb[h])); });
        __threadfence();
        asm volatile("fence.proxy.async;" ::: "memory");
        asm volatile("bar.sync %0, 256;" ::"r"(1) : "memory");
        if (threadIdx.x == 128) atomicAdd(&g_cnt[0], 1);
      } else if (type == 4) {
        gemm_mainloop<192, 1>(d, 72, sbase, fullb, eb_l, eb_r, cw, stage, phase, elect);
        float bb[2] = {__bfloat162float(p.b2[row0 + g]), __bfloat162float(p.b2[row0 + g + 8])};
#pragma unroll
        for (int i = 0; i < 24; i++)
#pragma unroll
          for (int h = 0; h < 2; h++) {
            size_t off = (size_t)(row0 + g + h * 8) * D_ + n * 192 + i * 8 + t * 2;
            float2 xv = unpack_bf16(*(const uint32_t*)(p.x + off));
            *(float2*)(g_yb + off) = make_float2(d[i * 4 + h * 2] + bb[h] + xv.x, d[i * 4 + h * 2 + 1] + bb[h] + xv.y);
          }
        __threadfence();
        asm volatile("bar.sync %0, 256;" ::"r"(1) : "memory");
        if (threadIdx.x == 128) atomicAdd(&g_cnt[24 + m], 1);
      } else if (type == 6) {
        const int st0 = stage;
        for (int k = 0; k < NSTAGE; k++) { mbar_wait(fullb + stage * 8, phase); if (++stage == NSTAGE) { stage = 0; phase ^= 1; } }
        const int seg = m * 8 + (n >> 1), w8 = cw * 4 + warp;
        const unsigned SEGT = 64u;
        if (lane == 0) wait_cnt(&g_cnt[40 + m], 32);
        __syncwarp();
        {
          const size_t o = ((size_t)seg * 32 + lane) * HD_ + ((n & 1) * 16 + rank * 8 + w8) * 128;
#pragma unroll
          for (int i = 0; i < 2; i++) {
            asm volatile("prefetch.global.L2 [%0];" ::"l"(g_q + o + i * 64)); asm volatile("prefetch.global.L2 [%0];" ::"l"(g_k + o + i * 64));
            asm volatile("prefetch.global.L2 [%0];" ::"l"(g_v + o + i * 64));
          }
        }
        if (lane == 0) { wait_cnt(&g_cnt[96 + seg], SEGT); }
        __syncwarp();
        attn_unit(seg, (n & 1) * 16 + rank * 8 + w8, smem_raw + (sbase - smem_u32(smem_raw)) + w8 * 12288, lane);
        __threadfence();
        asm volatile("fence.proxy.async;" ::: "memory");
        asm volatile("bar.sync %0, 256;" ::"r"(1) : "memory");
        if (elect) for (int k = 0; k < NSTAGE; k++) { mbar_arrive_remote(eb_l + k * 8); mbar_arrive_remote(eb_r + k * 8); }
        if (threadIdx.x == 128) atomicAdd(&g_cnt[16 + m], 1);
        (void)st0;
#pragma unroll
        for (int i = 0; i < 128; i++) d[i] = 0.f;
      } else if (type == 7) {
        const int nt = n % 3;
        gemm_mainloop<192, 0>(d, 8, sbase, fullb, eb_l, eb_r, cw, stage, phase, elect);
        if (lane == 0) wait_cnt(&g_cnt[24 + m], 6);
        __syncwarp();
        if (p.kid == 2) {
          const int ks = n / 3;
          float* pk = g_pk + ((size_t)ks * 512 + row0 - 1536 + g) * D_ + nt * 192 + t * 2;
#pragma unroll
          for (int i = 0; i < 24; i++)
#pragma unroll
            for (int h = 0; h < 2; h++) *(float2*)(pk + h * 8 * D_ + i * 8) = make_float2(d[i * 4 + h * 2], d[i * 4 + h * 2 + 1]);
          __threadfence();
          asm volatile("bar.sync %0, 256;" ::"r"(1) : "memory");
          unsigned int* cn = &g_cnt[48 + ((m - 4) * 3 + nt) * 2 + rank];
          if (threadIdx.x == 128) atomicAdd(cn, 1);
          if (lane == 0) wait_cnt(cn, 8);
          __syncwarp();
          const int r0 = m * 256 + rank * 128 + ks * 16;
#pragma unroll
          for (int it = 0; it < 3; it++) {
            int i = threadIdx.x - 128 + it * 256, rr = i / 48, cc = (i - rr * 48) * 4;
            size_t off = (size_t)(r0 + rr) * D_ + nt * 192 + cc;
            float4 y = __ldcg((const float4*)(g_yb + off)), q[8];
#pragma unroll
            for (int k = 0; k < 8; k++) q[k] = __ldcg((const float4*)(g_pk + (size_t)k * 512 * D_ + off - (size_t)1536 * D_));
#pragma unroll
            for (int k = 0; k < 8; k++) { y.x += q[k].x; y.y += q[k].y; y.z += q[k].z; y.w += q[k].w; }
            *(uint2*)(p.out + off) = make_uint2(pack_bf16(y.x, y.y), pack_bf16(y.z, y.w));
          }
          continue;
        }
#pragma unroll
        for (int i = 0; i < 24; i++)
#pragma unroll
          for (int h = 0; h < 2; h++)
            atomicAdd((float2*)(g_yb + (size_t)(row0 + g + h * 8) * D_ + nt * 192 + i * 8 + t * 2), make_float2(d[i * 4 + h * 2], d[i * 4 + h * 2 + 1]));
        __threadfence();
        asm volatile("bar.sync %0, 256;" ::"r"(1) : "memory");
        volatile uint32_t* lastf = (volatile uint32_t*)(smem_raw + (emptyb + 64 - smem_u32(smem_raw)));
        if (threadIdx.x == 128) { *lastf = atomicAdd(&g_cnt[48 + ((m - 4) * 3 + nt) * 2 + rank], 1); __threadfence(); }
        asm volatile("bar.sync %0, 256;" ::"r"(1) : "memory");
        if (*lastf == 7) {
          const int r0 = m * 256 + rank * 128;
#pragma unroll 8
          for (int i = threadIdx.x - 128; i < 128 * 48; i += 256) {
            int rr = i / 48, cc = (i - rr * 48) * 4;
            size_t off = (size_t)(r0 + rr) * D_ + nt * 192 + cc;
            float4 y = __ldcg((const float4*)(g_yb + off));
            *(uint2*)(p.out + off) = make_uint2(pack_bf16(y.x, y.y), pack_bf16(y.z, y.w));
          }
        }
        asm volatile("bar.sync %0, 256;" ::"r"(1) : "memory");
      } else {
        gemm_mainloop<192, 0>(d, 64, sbase, fullb, eb_l, eb_r, cw, stage, phase, elect);
        if (lane == 0) wait_cnt(&g_cnt[24 + m], 6);
        __syncwarp();
        const float* yb = g_yb + (size_t)(row0 + g) * D_ + n * 192 + t * 2;
        store_tile<192>(d, stg, p.out + (size_t)row0 * D_ + n * 192, D_, lane,
                        [&](float a, float b, int h, int c) { float2 y = *(const float2*)(yb + h * 8 * D_ + c); return pack_bf16(a + y.x, b + y.y); });
      }
    }
    if (blockIdx.x == 0 && threadIdx.x == 128) PT(2 + p.kid * 2);
    if (p.wait_at_end) pdl_wait();
    cluster_sync();
  }
}

constexpr int CH_WV = 0;
constexpr int CH_MEM = CH_WV + 73728;
constexpr int CH_KB = CH_MEM + 9216;
constexpr int CH_VB = CH_KB + 12288;
constexpr int CH_WO = CH_VB + 12288;
constexpr int CH_Q = CH_WO + 81920;
constexpr int CH_R1 = CH_Q + 1024;
constexpr int CH_SC = CH_R1 + 4096;
constexpr int CH_OF = CH_SC + 3584;
constexpr int CH_R2 = CH_OF + 8192;
constexpr int CH_BAR = CH_R2 + 12288;
constexpr int CHAIN_SMEM = CH_BAR + 64 + 1024;
#define POLL_DELAY 400
__device__ __forceinline__ void st_async1(uint32_t a, uint32_t v, uint32_t bar) { asm volatile("st.async.weak.shared::cluster.mbarrier::complete_tx::bytes.b32 [%0], %1, [%2];" ::"r"(a), "r"(v), "r"(bar) : "memory"); }
__device__ __forceinline__ void st_async2(uint32_t a, uint32_t v0, uint32_t v1, uint32_t bar) { asm volatile("st.async.weak.shared::cluster.mbarrier::complete_tx::bytes.v2.b32 [%0], {%1, %2}, [%3];" ::"r"(a), "r"(v0), "r"(v1), "r"(bar) : "memory"); }
__device__ __forceinline__ uint4 lds128(uint32_t a) { uint4 v; asm volatile("ld.shared.v4.u32 {%0,%1,%2,%3}, [%4];" : "=r"(v.x), "=r"(v.y), "=r"(v.z), "=r"(v.w) : "r"(a) : "memory"); return v; }
__device__ __forceinline__ void sts128f(uint32_t a, const float (&c)[4]) { asm volatile("st.shared.v4.f32 [%0], {%1,%2,%3,%4};" ::"r"(a), "f"(c[0]), "f"(c[1]), "f"(c[2]), "f"(c[3]) : "memory"); }
__device__ __forceinline__ void sts32(uint32_t a, uint32_t v) { asm volatile("st.shared.u32 [%0], %1;" ::"r"(a), "r"(v) : "memory"); }
__device__ __forceinline__ void mbar_wait_b(uint32_t b, uint32_t parity) {
  uint32_t ok; int n = 0;
  do { asm volatile("{\n.reg .pred p;\nmbarrier.try_wait.parity.shared::cta.b64 p, [%1], %2;\nselp.u32 %0, 1, 0, p;\n}" : "=r"(ok) : "r"(b), "r"(parity) : "memory"); } while (!ok && ++n < (1 << 20));
}
__device__ __forceinline__ uint32_t mapa_v(uint32_t a, uint32_t r) { uint32_t o; asm volatile("mapa.shared::cluster.u32 %0, %1, %2;" : "=r"(o) : "r"(a), "r"(r)); return o; }
__device__ __forceinline__ uint32_t tid_v() { uint32_t o; asm volatile("mov.u32 %0, %%tid.x;" : "=r"(o)); return o; }
template <int ACC>
__device__ __forceinline__ void wg_rs(float (&d)[4], const uint32_t (&a)[4], uint32_t dlo) {
  uint64_t db = ((uint64_t)16 << 32) | dlo;
  asm volatile("{\n.reg .pred p;\nsetp.ne.b32 p, %9, 0;\nwgmma.mma_async.sync.aligned.m64n8k16.f32.bf16.bf16 {%0,%1,%2,%3}, {%4,%5,%6,%7}, %8, p, 1, 1, 0;\n}"
               : "+f"(d[0]), "+f"(d[1]), "+f"(d[2]), "+f"(d[3]) : "r"(a[0]), "r"(a[1]), "r"(a[2]), "r"(a[3]), "l"(db), "n"(ACC));
}
template <int N>
__device__ __forceinline__ void wg_wait(float (&d)[N][4]) {
  asm volatile("wgmma.commit_group.sync.aligned;\nwgmma.wait_group.sync.aligned 0;" ::: "memory");
#pragma unroll
  for (int i = 0; i < N; i++) asm volatile("" : "+f"(d[i][0]), "+f"(d[i][1]), "+f"(d[i][2]), "+f"(d[i][3]) :: "memory");
}
#define BAR_ALL() asm volatile("bar.sync 0, 256;" ::: "memory")

__global__ void __launch_bounds__(256, 1) chain_kernel(const bf16* __restrict__ mem0, const bf16* __restrict__ Wq, const bf16* __restrict__ Wk,
                                                       const bf16* __restrict__ Wv, const bf16* __restrict__ Wo) {
  extern __shared__ uint8_t smem_raw[];
  const uint32_t sb = (smem_u32(smem_raw) + 1023) & ~1023u;
  const int tid = threadIdx.x, warp = __shfl_sync(~0u, tid >> 5, 0), wgi = __shfl_sync(~0u, tid >> 7, 0), lane = tid & 31, g = lane >> 2, t = lane & 3;
  const uint32_t r = cluster_rank();
  const int c = blockIdx.x >> 3, h = 4 * c + (r >> 1), j0 = h * 128 + (r & 1) * 64;
  const uint32_t bm = sb + CH_BAR, bs = bm + 8, bo = bm + 16;
  pdl_launch();
  if (blockIdx.x == 0 && tid == 0) PT(7);
  if (tid == 0) { mbar_init(bm, 1); mbar_init(bs, 1); mbar_init(bo, 1); asm volatile("fence.mbarrier_init.release.cluster;" ::: "memory"); }
  for (int i = tid; i < 576 + 1024; i += 256) {
    const bf16* a = i < 576 ? Wv + (size_t)i * HD_ + j0 : Wo + (size_t)(c * 512 + ((i - 576) >> 1)) * D_ + (((i - 576) & 1) ? 512 + (r >> 1) * 16 : r * 64);
    asm volatile("prefetch.global.L2 [%0];" ::"l"(a));
  }
  const int mi = lane >> 3, l7 = lane & 7;
  for (int i = tid; i < 576 * 8; i += 256) {
    int row = i >> 3, ch = i & 7;
    cp16(sb + CH_WV + row * 128 + ((ch ^ (row & 7)) * 16), Wq + (size_t)row * HD_ + j0 + ch * 8);
    cp16(sb + CH_WO + row * 128 + ((ch ^ (row & 7)) * 16), Wk + (size_t)row * HD_ + j0 + ch * 8);
  }
  asm volatile("cp.async.commit_group;\ncp.async.wait_group 0;" ::: "memory");
  BAR_ALL();
  uint32_t w1[36][4];
#pragma unroll
  for (int i = 0; i < 36; i++) {
    int row = i * 16 + (mi >> 1) * 8 + l7, ch = ((warp & 3) * 2 + (mi & 1)) ^ (row & 7);
    ldsm4t(w1[i], sb + (wgi ? CH_WO : CH_WV) + row * 128 + ch * 16);
  }
  BAR_ALL();
  for (int i = tid; i < 512 * 10; i += 256) {
    int row = i / 10, ch = i - row * 10;
    cp16(sb + CH_WV + row * 176 + ch * 16, Wo + (size_t)(c * 512 + row) * D_ + (ch < 8 ? r * 64 + ch * 8 : 512 + (r >> 1) * 16 + (ch - 8) * 8));
  }
  asm volatile("cp.async.commit_group;\ncp.async.wait_group 0;" ::: "memory");
  BAR_ALL();
  const int kperm = 2 * ((mi >> 1) * 2 + (l7 >> 2)) + (l7 & 1) + 8 * ((l7 >> 1) & 1);
  for (int i = 0; i < 16; i++) {
    uint32_t a[4];
    ldsm4t(a, sb + CH_WV + ((wgi * 16 + i) * 16 + kperm) * 176 + ((warp & 3) * 2 + (mi & 1)) * 16);
    asm volatile("st.shared.v4.u32 [%0], {%1,%2,%3,%4};" ::"r"(sb + CH_WO + 8192 + (warp * 16 + i) * 512 + lane * 16), "r"(a[0]), "r"(a[1]), "r"(a[2]), "r"(a[3]) : "memory");
  }
  for (int u = warp; u < 16; u += 8) {
    uint32_t a[4];
    ldsm4t(a, sb + CH_WV + (((r & 1) * 16 + u) * 16 + kperm) * 176 + (8 + (mi & 1)) * 16);
    asm volatile("st.shared.v4.u32 [%0], {%1,%2,%3,%4};" ::"r"(sb + CH_WO + u * 512 + lane * 16), "r"(a[0]), "r"(a[1]), "r"(a[2]), "r"(a[3]) : "memory");
  }
  BAR_ALL();
  for (int i = tid; i < 576 * 8; i += 256) {
    int row = i >> 3, ch = i & 7;
    cp16(sb + CH_WV + row * 128 + ((ch ^ (row & 7)) * 16), Wv + (size_t)row * HD_ + j0 + ch * 8);
  }
  for (int i = tid; i < 8 * 72; i += 256) {
    int row = i / 72, ch = i - row * 72;
    cp16(sb + CH_MEM + ch * 128 + row * 16, mem0 + row * D_ + ch * 8);
  }
  for (int i = tid; i < 4 * 64; i += 256) {
    int b = i >> 6, o = i & 63;
    asm volatile("st.shared.v4.u32 [%0], {%1,%1,%1,%1};" ::"r"(sb + CH_KB + b * 6144 + 40 * 128 + o * 16), "r"(0) : "memory");
  }
  auto prefetch_kv = [&](int s, int tid) {
    if ((s & 7) == 0) { if ((tid & 31) == 0) wait_cnt(&g_cnt[8 + (s >> 3)], 64); __syncwarp(); }
#pragma unroll
    for (int i = 0; i < 2; i++) {
      int u = tid + i * 256, which = u >> 8, row = (u & 255) >> 3, ch = u & 7;
      const bf16* src = (which ? g_v : g_k) + (size_t)(s * 32 + row) * HD_ + j0 + ch * 8;
      cp16(sb + (which ? CH_VB : CH_KB) + (s & 1) * 6144 + (row + 8) * 128 + ((ch ^ (row & 7)) * 16), src);
    }
    asm volatile("cp.async.commit_group;" ::: "memory");
  };
  prefetch_kv(0, tid);
  asm volatile("cp.async.wait_group 0;" ::: "memory");
  asm volatile("fence.proxy.async.shared::cta;" ::: "memory");
  BAR_ALL();
  cluster_sync();
  const uint32_t dsb = ((sb & 0x3FFFF) >> 4) | (8u << 16);
  if (blockIdx.x == 0 && tid == 0) PT(10);
#define CP(i) if (blockIdx.x == 0 && lane == 0 && warp == (((i) == 5 || (i) == 7) ? 4 : 0)) PC(64 + s * 16 + (i))
  for (int s = 0; s < NSEG; s++) {
    const int tid = tid_v(), lane = tid & 31, g = lane >> 2, t = lane & 3, mi = lane >> 3, l7 = lane & 7;
    CP(0);
    const uint32_t par = s & 1, kb = sb + CH_KB + par * 6144, vb = sb + CH_VB + par * 6144;
    if (s > 0) mbar_wait_b(bm, par ^ 1);
    CP(1);
    if (tid == 0 && s < NSEG - 1) { mbar_expect(bs, 2560); mbar_expect(bo, 8192); mbar_expect(bm, 9216); }
    auto phase1 = [&]() {
      float pa[3][4] = {};
#pragma unroll
      for (int i = 0; i < 36; i += 2) {
        uint32_t b[4];
        ldsm4(b, sb + CH_MEM + i * 256 + mi * 128 + l7 * 16);
        mma16816(pa[i % 3], w1[i], b[0], b[1]); mma16816(pa[(i + 1) % 3], w1[i + 1], b[2], b[3]);
      }
      CP(2);
      uint32_t b0 = movm(pack_bf16(pa[0][0] + pa[1][0] + pa[2][0], pa[0][1] + pa[1][1] + pa[2][1]));
      uint32_t b1 = movm(pack_bf16(pa[0][2] + pa[1][2] + pa[2][2], pa[0][3] + pa[1][3] + pa[2][3]));
      uint32_t dst = (wgi ? kb : sb + CH_Q) + g * 128 + t * 4;
      sts32(dst + ((((warp & 3) * 2) ^ g) * 16), b0); sts32(dst + ((((warp & 3) * 2 + 1) ^ g) * 16), b1);
      if (wgi) { uint32_t* gp = (uint32_t*)(g_km + ((size_t)s * 8 + g) * HD_ + j0 + (warp & 3) * 16 + t * 2); gp[0] = b0; gp[4] = b1; }
      asm volatile("cp.async.wait_group 0;" ::: "memory");
    };
    if (wgi == 0) {
      phase1();
      BAR_ALL();
      CP(4);
      if (s + 1 < NSEG) { prefetch_kv(s + 1, tid); asm volatile("bar.sync 6, 224;" ::: "memory"); }
      float va[4][4];
      asm volatile("wgmma.fence.sync.aligned;" ::: "memory");
      const uint32_t dwa = (((sb + CH_WV) & 0x3FFFF) >> 4) | ((8192u >> 4) << 16);
#pragma unroll
      for (int ks = 0; ks < 36; ks++) {
        uint64_t da = ((uint64_t)(0x40000000u | (1024 >> 4)) << 32) | (dwa + ks * 128), db = ((uint64_t)16 << 32) | (dsb + ((CH_MEM + ks * 256) >> 4));
        if (ks < 4)
          asm volatile("{\n.reg .pred p;\nsetp.ne.b32 p, 0, 0;\nwgmma.mma_async.sync.aligned.m64n8k16.f32.bf16.bf16 {%0,%1,%2,%3}, %4, %5, p, 1, 1, 1, 0;\n}"
                       : "=f"(va[ks & 3][0]), "=f"(va[ks & 3][1]), "=f"(va[ks & 3][2]), "=f"(va[ks & 3][3]) : "l"(da), "l"(db));
        else
          asm volatile("{\n.reg .pred p;\nsetp.ne.b32 p, 1, 0;\nwgmma.mma_async.sync.aligned.m64n8k16.f32.bf16.bf16 {%0,%1,%2,%3}, %4, %5, p, 1, 1, 1, 0;\n}"
                       : "+f"(va[ks & 3][0]), "+f"(va[ks & 3][1]), "+f"(va[ks & 3][2]), "+f"(va[ks & 3][3]) : "l"(da), "l"(db));
      }
      wg_wait(va);
      CP(6);
      uint32_t b0 = movm(pack_bf16(va[0][0] + va[1][0] + va[2][0] + va[3][0], va[0][1] + va[1][1] + va[2][1] + va[3][1]));
      uint32_t b1 = movm(pack_bf16(va[0][2] + va[1][2] + va[2][2] + va[3][2], va[0][3] + va[1][3] + va[2][3] + va[3][3]));
      sts32(vb + g * 128 + t * 4 + (((warp * 2) ^ g) * 16), b0); sts32(vb + g * 128 + t * 4 + (((warp * 2 + 1) ^ g) * 16), b1);
      uint32_t* gp = (uint32_t*)(g_vm + ((size_t)s * 8 + g) * HD_ + j0 + warp * 16 + t * 2); gp[0] = b0; gp[4] = b1;
      asm volatile("bar.arrive 7, 256;" ::: "memory");
    } else {
      phase1();
      BAR_ALL();
      if (warp == 7 && lane == 0 && s > 0) { __threadfence(); atomicAdd(&g_cnt[96 + s - 1], 1); }
      if (warp < 7 && s < NSEG - 1) {
        const int mt = warp - 4;
        const uint32_t sc_l = mapa_v(sb + CH_SC + (r & 1) * 1792, r), sc_r = mapa_v(sb + CH_SC + (r & 1) * 1792, r ^ 1), bs_l = mapa_v(bs, r), bs_r = mapa_v(bs, r ^ 1);
        float sa[4][4] = {};
#pragma unroll
        for (int kp = 0; kp < 2; kp++) {
          uint32_t b[4], a0[4], a1[4];
          ldsm4(b, sb + CH_Q + l7 * 128 + (((kp * 4 + mi) ^ l7) * 16));
          int row = mt * 16 + (mi & 1) * 8 + l7;
          ldsm4(a0, kb + row * 128 + (((kp * 4 + (mi >> 1)) ^ l7) * 16));
          ldsm4(a1, kb + row * 128 + (((kp * 4 + 2 + (mi >> 1)) ^ l7) * 16));
          mma16816(sa[2 * kp], a0, b[0], b[1]); mma16816(sa[2 * kp + 1], a1, b[2], b[3]);
        }
        asm volatile("bar.arrive 6, 224;" :: "f"(sa[0][0]), "f"(sa[1][0]), "f"(sa[2][0]), "f"(sa[3][0]) : "memory");
#pragma unroll
        for (int e = 0; e < 4; e++) {
          uint32_t off = ((2 * t + (e & 1)) * 56 + mt * 16 + (e >> 1) * 8 + g) * 4, v = __float_as_uint((sa[0][e] + sa[1][e]) + (sa[2][e] + sa[3][e]));
          if (mt < 2 || e < 2) { st_async1(sc_r + off, v, bs_r); st_async1(sc_l + off, v, bs_l); }
        }
        CP(5);
      }
      if (s < NSEG - 1) {
        prefetch_kv(s + 1, tid);
        const int w3 = warp & 3;
        uint32_t vt[3][4];
#pragma unroll
        for (int kk = 1; kk < 3; kk++) { int row = kk * 16 + (mi >> 1) * 8 + l7; ldsm4t(vt[kk], vb + row * 128 + (((w3 * 2 + (mi & 1)) ^ l7) * 16)); }
        mbar_wait_b(bs, par);
        CP(7);
        float z[10]; float mx = -INFINITY;
        const float scl = 0.08838834764831845f * 1.4426950408889634f;
#pragma unroll
        for (int i = 0; i < 5; i++) {
          float2 u0, u1; uint32_t a = sb + CH_SC + (g * 56 + i * 8 + 2 * t) * 4;
          asm volatile("ld.shared.v2.f32 {%0,%1}, [%2];" : "=f"(u0.x), "=f"(u0.y) : "r"(a) : "memory");
          asm volatile("ld.shared.v2.f32 {%0,%1}, [%2];" : "=f"(u1.x), "=f"(u1.y) : "r"(a + 1792) : "memory");
          z[2 * i] = (u0.x + u1.x) * scl; z[2 * i + 1] = (u0.y + u1.y) * scl;
        }
        mx = fmaxf(fmaxf(fmaxf(z[0], z[1]), fmaxf(z[2], z[3])), fmaxf(fmaxf(fmaxf(z[4], z[5]), fmaxf(z[6], z[7])), fmaxf(z[8], z[9])));
        mx = fmaxf(mx, __shfl_xor_sync(~0u, mx, 1)); mx = fmaxf(mx, __shfl_xor_sync(~0u, mx, 2));
        uint32_t pb[5];
#pragma unroll
        for (int i = 0; i < 5; i++) pb[i] = pack_bf16(exp2f(z[2 * i] - mx), exp2f(z[2 * i + 1] - mx));
        const uint32_t ones[4] = {0x3F803F80u, 0x3F803F80u, 0x3F803F80u, 0x3F803F80u};
        float o0[4] = {}, o1[4] = {}, o2[4] = {}, s0[4] = {}, s1[4] = {}, s2[4] = {};
        mma16816(s0, ones, pb[0], pb[1]);
        mma16816(o1, vt[1], pb[2], pb[3]); mma16816(s1, ones, pb[2], pb[3]);
        mma16816(o2, vt[2], pb[4], 0u); mma16816(s2, ones, pb[4], 0u);
        asm volatile("bar.sync 7, 256;" ::: "memory");
        ldsm4t(vt[0], vb + ((mi >> 1) * 8 + l7) * 128 + (((w3 * 2 + (mi & 1)) ^ l7) * 16));
        mma16816(o0, vt[0], pb[0], pb[1]);
        const float i0 = __fdividef(1.f, s0[0] + s1[0] + s2[0]), i1 = __fdividef(1.f, s0[1] + s1[1] + s2[1]);
        uint32_t f0 = movm(pack_bf16((o0[0] + o1[0] + o2[0]) * i0, (o0[1] + o1[1] + o2[1]) * i1));
        uint32_t f1 = movm(pack_bf16((o0[2] + o1[2] + o2[2]) * i0, (o0[3] + o1[3] + o2[3]) * i1));
        const int ks = r * 4 + w3;
        const uint32_t off = CH_OF + ks * 256 + (t >> 1) * 128 + g * 16 + (t & 1) * 8;
        const uint32_t cl0 = mapa_v(sb, 0), clstep = mapa_v(sb, 1) - cl0;
#pragma unroll
        for (int d = 0; d < 8; d++) st_async2(cl0 + d * clstep + off, f0, f1, cl0 + d * clstep + CH_BAR + 16);
      } else asm volatile("bar.sync 7, 256;" ::: "memory");
    }
    if (s == NSEG - 1) break;
    CP(8);
    uint32_t wo[16][4];
#pragma unroll
    for (int i = 0; i < 16; i++) { uint4 v = lds128(sb + CH_WO + 8192 + (warp * 16 + i) * 512 + lane * 16); wo[i][0] = v.x; wo[i][1] = v.y; wo[i][2] = v.z; wo[i][3] = v.w; }
    mbar_wait_b(bo, par);
    CP(9);
    const uint32_t tag = ((s >> 1) + 1) & 1;
    float* pbase = g_part + (size_t)par * 8 * 5120 + lane * 4;
    auto put = [&](int slot, const float (&a)[4]) {
      asm volatile("st.relaxed.gpu.global.v4.b32 [%0], {%1,%2,%3,%4};" ::"l"(pbase + c * 5120 + slot * 128), "r"((__float_as_uint(a[0]) & ~1u) | tag),
                   "r"((__float_as_uint(a[1]) & ~1u) | tag), "r"((__float_as_uint(a[2]) & ~1u) | tag), "r"((__float_as_uint(a[3]) & ~1u) | tag) : "memory");
    };
    {
      float acc[4][4];
      asm volatile("wgmma.fence.sync.aligned;" ::: "memory");
      const uint32_t dof = dsb + ((CH_OF >> 4) + wgi * 256);
#pragma unroll
      for (int i = 0; i < 16; i++) { if (i < 4) wg_rs<0>(acc[i & 3], wo[i], dof + i * 16); else wg_rs<1>(acc[i & 3], wo[i], dof + i * 16); }
      wg_wait(acc);
#pragma unroll
      for (int e = 0; e < 4; e++) acc[0][e] = (acc[0][e] + acc[1][e]) + (acc[2][e] + acc[3][e]);
      CP(10);
      const int w3 = warp & 3;
      if (wgi) {
        sts128f(sb + CH_R2 + w3 * 512 + lane * 16, acc[0]);
        asm volatile("bar.arrive %0, 64;" ::"r"(1 + w3) : "memory");
        if (w3 < 2) {
          float ex[2][4] = {};
#pragma unroll
          for (int i = 0; i < 8; i += 2) {
            uint32_t b[4]; ldsm4(b, sb + CH_OF + ((r & 1) * 16 + w3 * 8 + i) * 256 + mi * 128 + l7 * 16);
            uint4 v0 = lds128(sb + CH_WO + (w3 * 8 + i) * 512 + lane * 16), v1 = lds128(sb + CH_WO + (w3 * 8 + i + 1) * 512 + lane * 16);
            uint32_t a0[4] = {v0.x, v0.y, v0.z, v0.w}, a1[4] = {v1.x, v1.y, v1.z, v1.w};
            mma16816(ex[0], a0, b[0], b[1]); mma16816(ex[1], a1, b[2], b[3]);
          }
#pragma unroll
          for (int e = 0; e < 4; e++) ex[0][e] += ex[1][e];
          if (w3 == 1) { sts128f(sb + CH_R2 + 4 * 512 + lane * 16, ex[0]); asm volatile("bar.arrive 5, 64;" ::: "memory"); }
          else {
            asm volatile("bar.sync 5, 64;" ::: "memory");
            uint4 v = lds128(sb + CH_R2 + 4 * 512 + lane * 16);
            ex[0][0] += __uint_as_float(v.x); ex[0][1] += __uint_as_float(v.y); ex[0][2] += __uint_as_float(v.z); ex[0][3] += __uint_as_float(v.w);
            put(32 + r, ex[0]);
          }
        }
      } else {
        asm volatile("bar.sync %0, 64;" ::"r"(1 + w3) : "memory");
        uint4 v = lds128(sb + CH_R2 + w3 * 512 + lane * 16);
        acc[0][0] += __uint_as_float(v.x); acc[0][1] += __uint_as_float(v.y); acc[0][2] += __uint_as_float(v.z); acc[0][3] += __uint_as_float(v.w);
        put(r * 4 + w3, acc[0]);
      }
    }
    CP(11);
    if (warp < 4 || warp == 6) { long long t0 = clock64(); while (clock64() - t0 < POLL_DELAY) {} }
    if (warp < 4) {
      const float* pb = pbase + (r * 4 + warp) * 128;
      uint4 v[8]; int n = 0; uint32_t need = 0xFF;
#pragma unroll
      for (int i = 0; i < 8; i++) v[i] = make_uint4(0, 0, 0, 0);
      do {
#pragma unroll
        for (int i = 0; i < 8; i++)
          asm volatile("{\n.reg .pred p;\nsetp.ne.b32 p, %5, 0;\n@p ld.relaxed.gpu.global.v4.b32 {%0,%1,%2,%3}, [%4];\n}" : "+r"(v[i].x), "+r"(v[i].y), "+r"(v[i].z), "+r"(v[i].w) : "l"(pb + i * 5120), "r"(need & (1u << i)) : "memory");
#pragma unroll
        for (int i = 0; i < 8; i++) {
          bool ok = ((v[i].x & v[i].y & v[i].z & v[i].w & 1u) == tag) && (((v[i].x | v[i].y | v[i].z | v[i].w) & 1u) == tag);
          if (__all_sync(~0u, ok)) need &= ~(1u << i);
        }
      } while (need && ++n < (1 << 18));
      float m[4] = {};
#pragma unroll
      for (int i = 0; i < 8; i++) { m[0] += __uint_as_float(v[i].x); m[1] += __uint_as_float(v[i].y); m[2] += __uint_as_float(v[i].z); m[3] += __uint_as_float(v[i].w); }
      __syncwarp();
      CP(12);
      uint32_t b0 = movm(pack_bf16(m[0], m[1])), b1 = movm(pack_bf16(m[2], m[3]));
      const uint32_t off = CH_MEM + (r * 4 + warp) * 256 + g * 16 + t * 4;
      const uint32_t cl0 = mapa_v(sb, 0), clstep = mapa_v(sb, 1) - cl0;
#pragma unroll
      for (int d = 0; d < 8; d++) { st_async1(cl0 + d * clstep + off, b0, cl0 + d * clstep + CH_BAR); st_async1(cl0 + d * clstep + off + 128, b1, cl0 + d * clstep + CH_BAR); }
    } else if (warp == 6) {
      const float* pb = pbase - lane * 4 + (32 + (r & ~1u)) * 128 + lane * 4 + (r & 1) * 2;
      uint2 v[16]; int n = 0; uint32_t need = 0xFF;
#pragma unroll
      for (int i = 0; i < 16; i++) v[i] = make_uint2(0, 0);
      do {
#pragma unroll
        for (int i = 0; i < 16; i++)
          asm volatile("{\n.reg .pred p;\nsetp.ne.b32 p, %3, 0;\n@p ld.relaxed.gpu.global.v2.b32 {%0,%1}, [%2];\n}" : "+r"(v[i].x), "+r"(v[i].y) : "l"(pb + (i >> 1) * 5120 + (i & 1) * 128), "r"(need & (1u << (i >> 1))) : "memory");
#pragma unroll
        for (int i = 0; i < 16; i += 2) {
          bool ok = ((v[i].x & v[i].y & v[i + 1].x & v[i + 1].y & 1u) == tag) && (((v[i].x | v[i].y | v[i + 1].x | v[i + 1].y) & 1u) == tag);
          if (__all_sync(~0u, ok)) need &= ~(1u << (i >> 1));
        }
      } while (need && ++n < (1 << 18));
      float m0 = 0.f, m1 = 0.f;
#pragma unroll
      for (int i = 0; i < 16; i++) { m0 += __uint_as_float(v[i].x); m1 += __uint_as_float(v[i].y); }
      __syncwarp();
      uint32_t b0 = movm(pack_bf16(m0, m1));
      const uint32_t off = CH_MEM + (32 + (r >> 1)) * 256 + (r & 1) * 128 + g * 16 + t * 4;
      const uint32_t cl0 = mapa_v(sb, 0), clstep = mapa_v(sb, 1) - cl0;
#pragma unroll
      for (int d = 0; d < 8; d++) st_async1(cl0 + d * clstep + off, b0, cl0 + d * clstep + CH_BAR);
    }
  }
  BAR_ALL();
  if (tid == 0) { __threadfence(); atomicAdd(&g_cnt[96 + NSEG - 1], 1); }
  if (blockIdx.x == 0 && tid == 0) PT(8);
  cluster_sync();
}
typedef CUresult (*EncodeFn)(CUtensorMap*, CUtensorMapDataType, cuuint32_t, void*, const cuuint64_t*, const cuuint64_t*, const cuuint32_t*, const cuuint32_t*,
                             CUtensorMapInterleave, CUtensorMapSwizzle, CUtensorMapL2promotion, CUtensorMapFloatOOBfill);
static EncodeFn g_enc;
static void mkmap(CUtensorMap* m, const void* ptr, int rows, int cols, int boxc, int boxr) {
  cuuint64_t dims[2] = {(cuuint64_t)cols, (cuuint64_t)rows}, strides[1] = {(cuuint64_t)cols * 2};
  cuuint32_t box[2] = {(cuuint32_t)boxc, (cuuint32_t)boxr}, es[2] = {1, 1};
  g_enc(m, CU_TENSOR_MAP_DATA_TYPE_BFLOAT16, 2, (void*)ptr, dims, strides, box, es, CU_TENSOR_MAP_INTERLEAVE_NONE, CU_TENSOR_MAP_SWIZZLE_128B,
        CU_TENSOR_MAP_L2_PROMOTION_L2_256B, CU_TENSOR_MAP_FLOAT_OOB_FILL_NONE);
}
#define URG 50.0
#define CHDT 3.6
constexpr double CH_T0 = 24.0, CH_DT = CHDT;
static inline uint16_t mkjob(int type, int m, int n) { return (uint16_t)(type << 12 | m << 6 | n); }
static void schedule_side(GemmParams& p, const uint16_t* base, int nb, int ncl) {
  static const double cost[8] = {7.6, 7.6, 7.6, 19.5, 56.0, 33.0, 12.5, 7.0};
  double t[66]; int cnt[66] = {};
  for (int c = 0; c < 66; c++) t[c] = 9.0;
  p.stride = 960 / ncl;
  for (int i = 0; i < 960; i++) p.job[i] = 0xFFFF;
  double g2_end = 0, q_end[8] = {}, g3_end[8] = {}, at_end[8] = {}; int qn[8] = {}, g3n[8] = {}, atn[8] = {};
  int bi = 0, ai = 0, gi = 0;
  while (bi < nb || ai < 96 || gi < 60) {
    int b = -1;
    for (int c = 0; c < ncl; c++) if (cnt[c] < p.stride && (b < 0 || t[c] < t[b] || (t[c] == t[b] && cnt[c] < cnt[b]))) b = c;
    const double inf = 1e30;
    int am = ai >> 4, gm = gi < 12 ? gi / 3 : 4 + (gi - 12) / 24;
    double ra = ai < 96 && qn[am] == 16 ? (q_end[am] > CH_T0 + CH_DT * (am * 8 + ((ai & 15) >> 1) + 2) ? q_end[am] : CH_T0 + CH_DT * (am * 8 + ((ai & 15) >> 1) + 2)) : inf;
    double rg = gi < 60 && atn[gm] == 16 && g3n[gm] == 3 ? (at_end[gm] > g3_end[gm] - 30 ? at_end[gm] : g3_end[gm] - 30) : inf;
    bool urgent = bi < nb && (base[bi] >> 12) >= 1 && (base[bi] >> 12) <= 2 && CH_T0 + CH_DT * 8 * ((base[bi] >> 6) & 63) - t[b] < URG;
    uint16_t job; double start = t[b];
    if (urgent) job = base[bi++];
    else if (rg <= t[b] || (bi >= nb && rg < inf && (rg <= ra || (gi < 60 && ai >= 96)))) { job = gi < 12 ? mkjob(5, gm, gi % 3) : mkjob(7, gm, (gi - 12) % 24); gi++; if (rg > start) start = rg; }
    else if (ra <= t[b] || bi >= nb) { job = mkjob(6, am, ai & 15); ai++; if (ra > start) start = ra; }
    else job = base[bi++];
    int ty = job >> 12, m = (job >> 6) & 63;
    if (ty == 4 && start < g2_end) start = g2_end;
    t[b] = start + cost[ty];
    if (ty == 3 && t[b] > g2_end) g2_end = t[b];
    if (ty == 0) { qn[m]++; if (t[b] > q_end[m]) q_end[m] = t[b]; }
    if (ty == 4) { g3n[m]++; if (t[b] > g3_end[m]) g3_end[m] = t[b]; }
    if (ty == 6) { atn[m]++; if (t[b] > at_end[m]) at_end[m] = t[b]; }
    p.job[b * p.stride + cnt[b]++] = job;
  }
}
template <class... A>
static void launch(void (*k)(A...), int grid, int block, int smem, int cluster, bool pdl, A... a) {
  cudaLaunchConfig_t c = {};
  c.gridDim = grid; c.blockDim = block; c.dynamicSmemBytes = smem; c.stream = cudaStreamPerThread;
  cudaLaunchAttribute at[2]; int n = 0;
  if (cluster > 1) { at[n].id = cudaLaunchAttributeClusterDimension; at[n].val.clusterDim.x = cluster; at[n].val.clusterDim.y = 1; at[n].val.clusterDim.z = 1; n++; }
  if (pdl) { at[n].id = cudaLaunchAttributeProgrammaticStreamSerialization; at[n].val.programmaticStreamSerializationAllowed = 1; n++; }
  c.attrs = at; c.numAttrs = n;
  cudaLaunchKernelEx(&c, k, a...);
}

extern "C" void kernel_launch(void* const* d_in, const int* in_sizes, int n_in, void* d_out, int out_size) {
  const bf16 *x = (const bf16*)d_in[0], *mem0 = (const bf16*)d_in[1], *Wq = (const bf16*)d_in[2], *Wk = (const bf16*)d_in[3], *Wv = (const bf16*)d_in[4],
             *Wo = (const bf16*)d_in[5], *w1 = (const bf16*)d_in[8], *b1 = (const bf16*)d_in[9], *w2 = (const bf16*)d_in[10], *b2 = (const bf16*)d_in[11];
  static bool init = false;
  static GemmParams side, post;
  if (!init) {
    init = true;
    cudaDriverEntryPointQueryResult qr;
    cudaGetDriverEntryPoint("cuTensorMapEncodeTiled", (void**)&g_enc, cudaEnableDefault, &qr);
    void *xn, *h2, *o, *ut;
    cudaGetSymbolAddress(&xn, g_xn); cudaGetSymbolAddress(&h2, g_h2); cudaGetSymbolAddress(&o, g_o); cudaGetSymbolAddress(&ut, g_ut);
    GemmParams b = {};
    mkmap(&b.mA[0], xn, S_, D_, 64, 128); mkmap(&b.mA[1], w1, S_, F_, 64, 64); mkmap(&b.mA[2], w2, F_, S_, 64, 64); mkmap(&b.mA[3], o, S_, HD_, 64, 128);
    mkmap(&b.mB[0], Wq, D_, HD_, 64, 32); mkmap(&b.mB[1], Wk, D_, HD_, 64, 32); mkmap(&b.mB[2], Wv, D_, HD_, 64, 32);
    mkmap(&b.mB[3], h2, S_, D_, 64, 32); mkmap(&b.mB[4], ut, F_, D_, 64, 32); mkmap(&b.mB[5], Wo, HD_, D_, 64, 32);
    b.x = x; b.b1 = b1; b.b2 = b2; b.out = (bf16*)d_out;
    side = b; post = b; side.kid = 1; post.kid = 2;
    static uint16_t jl[1024]; int n = 0;
    auto kv = [&](int m) { for (int j = 0; j < 16; j++) { jl[n++] = mkjob(1, m, j); jl[n++] = mkjob(2, m, j); } };
    auto qq = [&](int m) { for (int j = 0; j < 16; j++) jl[n++] = mkjob(0, m, j); };
    kv(0); kv(1);
    for (int m = 0; m < 18; m++) for (int j = 0; j < 3; j++) jl[n++] = mkjob(3, m, j);
    kv(2); qq(0); kv(3); qq(1);
    for (int m = 0; m < 8; m++) for (int j = 0; j < 3; j++) jl[n++] = mkjob(4, m, j);
    for (int m = 4; m < 8; m++) { kv(m); qq(m - 2); }
    qq(6); qq(7);
    schedule_side(side, jl, n, 34);
    side.wait_at_end = 0;
    post.stride = 2;
    for (int i = 0; i < 960; i++) post.job[i] = 0xFFFF;
    for (int i = 0; i < 48; i++) {
      if (i < 32) { post.job[i * 2] = mkjob(6, 6 + (i >> 4), i & 15); post.job[i * 2 + 1] = mkjob(7, 6 + i / 24, i % 24); }
      else post.job[i * 2] = mkjob(7, 6 + i / 24, i % 24);
    }
    cudaFuncSetAttribute(gemm_kernel, cudaFuncAttributeMaxDynamicSharedMemorySize, GEMM_SMEM);
    cudaFuncSetAttribute(chain_kernel, cudaFuncAttributeMaxDynamicSharedMemorySize, CHAIN_SMEM);
  }
  launch(ln_kernel, 256, 256, 0, 1, false, x);
  launch(chain_kernel, 64, 256, CHAIN_SMEM, 8, false, mem0, Wq, Wk, Wv, Wo);
  launch(gemm_kernel, 68, 384, GEMM_SMEM, 2, true, side);
  launch(gemm_kernel, 96, 384, GEMM_SMEM, 2, true, post);
}
```

```cpp
#include <cuda_runtime.h>
#include <cuda_bf16.h>
#include <cuda.h>
#include <stdint.h>

typedef __nv_bfloat16 bf16;
constexpr int S_ = 2048, D_ = 576, HD_ = 4096, F_ = 4608, NSEG = 64;

__device__ bf16 g_xn[S_ * D_];
__device__ bf16 g_h2[S_ * D_];
__device__ bf16 g_q[S_ * HD_];
__device__ bf16 g_k[S_ * HD_];
__device__ bf16 g_v[S_ * HD_];
__device__ bf16 g_o[S_ * HD_];
__device__ bf16 g_km[NSEG * 8 * HD_];
__device__ bf16 g_vm[NSEG * 8 * HD_];
__device__ bf16 g_ut[F_ * D_];
__device__ float g_yb[S_ * D_];
__device__ float g_pk[8 * 512 * D_];
__device__ float g_part[2 * 8 * 8 * 5 * 32 * 4];
__device__ unsigned int g_cnt[192];

#define PT(i)
#define PC(i)
__device__ __forceinline__ uint32_t smem_u32(const void* p) { return (uint32_t)__cvta_generic_to_shared(p); }
__device__ __forceinline__ void mbar_init(uint32_t b, uint32_t c) { asm volatile("mbarrier.init.shared::cta.b64 [%0], %1;" ::"r"(b), "r"(c)); }
__device__ __forceinline__ void mbar_expect(uint32_t b, uint32_t bytes) { asm volatile("mbarrier.arrive.expect_tx.shared::cta.b64 _, [%0], %1;" ::"r"(b), "r"(bytes) : "memory"); }
__device__ __forceinline__ void mbar_wait(uint32_t b, uint32_t parity) {
  uint32_t ok;
  do { asm volatile("{\n.reg .pred p;\nmbarrier.try_wait.parity.shared::cta.b64 p, [%1], %2;\nselp.u32 %0, 1, 0, p;\n}" : "=r"(ok) : "r"(b), "r"(parity) : "memory"); } while (!ok);
}
__device__ __forceinline__ void mbar_wait_cl(uint32_t b, uint32_t parity) {
  uint32_t ok;
  do { asm volatile("{\n.reg .pred p;\nmbarrier.try_wait.parity.shared::cta.b64 p, [%1], %2;\nselp.u32 %0, 1, 0, p;\n}" : "=r"(ok) : "r"(b), "r"(parity) : "memory"); } while (!ok);
}
__device__ __forceinline__ uint32_t mapa(uint32_t a, uint32_t r) { uint32_t o; asm("mapa.shared::cluster.u32 %0, %1, %2;" : "=r"(o) : "r"(a), "r"(r)); return o; }
__device__ __forceinline__ void mbar_arrive_remote(uint32_t remote_b) { asm volatile("mbarrier.arrive.shared::cluster.b64 _, [%0];" ::"r"(remote_b) : "memory"); }
__device__ __forceinline__ uint32_t cluster_rank() { uint32_t r; asm("mov.u32 %0, %%cluster_ctarank;" : "=r"(r)); return r; }
__device__ __forceinline__ void cluster_sync() { asm volatile("barrier.cluster.arrive.release.aligned;\nbarrier.cluster.wait.acquire.aligned;" ::: "memory"); }
__device__ __forceinline__ void tma2d(uint32_t dst, const CUtensorMap* m, int c0, int c1, uint32_t bar) {
  asm volatile("cp.async.bulk.tensor.2d.shared::cluster.global.mbarrier::complete_tx::bytes [%0], [%1, {%3, %4}], [%2];"
               ::"r"(dst), "l"(m), "r"(bar), "r"(c0), "r"(c1) : "memory");
}
__device__ __forceinline__ void tma2d_mc(uint32_t dst, const CUtensorMap* m, int c0, int c1, uint32_t bar, uint16_t mask) {
  asm volatile("cp.async.bulk.tensor.2d.shared::cluster.global.mbarrier::complete_tx::bytes.multicast::cluster [%0], [%1, {%3, %4}], [%2], %5;"
               ::"r"(dst), "l"(m), "r"(bar), "r"(c0), "r"(c1), "h"(mask) : "memory");
}
__device__ __forceinline__ uint32_t pack_bf16(float a, float b) { __nv_bfloat162 t = __floats2bfloat162_rn(a, b); return *(uint32_t*)&t; }
__device__ __forceinline__ float2 unpack_bf16(uint32_t u) { return __bfloat1622float2(*(__nv_bfloat162*)&u); }
__device__ __forceinline__ void mma16816(float (&c)[4], const uint32_t (&a)[4], uint32_t b0, uint32_t b1) {
  asm volatile("mma.sync.aligned.m16n8k16.row.col.f32.bf16.bf16.f32 {%0,%1,%2,%3},{%4,%5,%6,%7},{%8,%9},{%0,%1,%2,%3};"
               : "+f"(c[0]), "+f"(c[1]), "+f"(c[2]), "+f"(c[3]) : "r"(a[0]), "r"(a[1]), "r"(a[2]), "r"(a[3]), "r"(b0), "r"(b1));
}
__device__ __forceinline__ void ldsm4(uint32_t (&r)[4], uint32_t a) { asm volatile("ldmatrix.sync.aligned.m8n8.x4.shared.b16 {%0,%1,%2,%3},[%4];" : "=r"(r[0]), "=r"(r[1]), "=r"(r[2]), "=r"(r[3]) : "r"(a) : "memory"); }
__device__ __forceinline__ void ldsm4t(uint32_t (&r)[4], uint32_t a) { asm volatile("ldmatrix.sync.aligned.m8n8.x4.trans.shared.b16 {%0,%1,%2,%3},[%4];" : "=r"(r[0]), "=r"(r[1]), "=r"(r[2]), "=r"(r[3]) : "r"(a) : "memory"); }
__device__ __forceinline__ uint32_t movm(uint32_t a) { uint32_t o; asm volatile("movmatrix.sync.aligned.m8n8.trans.b16 %0, %1;" : "=r"(o) : "r"(a)); return o; }
__device__ __forceinline__ void cp16(uint32_t dst, const void* src) { asm volatile("cp.async.cg.shared.global [%0], [%1], 16;" ::"r"(dst), "l"(src) : "memory"); }
__device__ __forceinline__ void pdl_wait() { asm volatile("griddepcontrol.wait;" ::: "memory"); }
__device__ __forceinline__ void pdl_launch() { asm volatile("griddepcontrol.launch_dependents;" ::: "memory"); }

__device__ __forceinline__ void wait_cnt(const unsigned int* c, unsigned int target) {
  uint32_t v; int n = 0;
  do { asm volatile("ld.acquire.gpu.global.u32 %0, [%1];" : "=r"(v) : "l"(c) : "memory"); if (v >= target) break; __nanosleep(64); } while (++n < (1 << 22));
}
__global__ void __launch_bounds__(256) ln_kernel(const bf16* __restrict__ x) {
  int row = blockIdx.x * 8 + (threadIdx.x >> 5), lane = threadIdx.x & 31;
  if (blockIdx.x == 0 && threadIdx.x < 192) { g_cnt[threadIdx.x] = 0; if (threadIdx.x == 0) PT(0); }
  for (int i = blockIdx.x * 256 + threadIdx.x; i < 2 * 64 * 640; i += 256 * 256) g_part[i] = 0.f;
  const uint32_t* xr = (const uint32_t*)(x + (size_t)row * D_);
  float v[18]; float s = 0.f;
#pragma unroll
  for (int i = 0; i < 9; i++) { float2 f = unpack_bf16(xr[lane + 32 * i]); v[2 * i] = f.x; v[2 * i + 1] = f.y; s += f.x + f.y; }
#pragma unroll
  for (int pass = 0; pass < 2; pass++) {
#pragma unroll
    for (int o = 16; o; o >>= 1) s += __shfl_xor_sync(~0u, s, o);
    float m = s * (1.f / D_), q = 0.f;
#pragma unroll
    for (int i = 0; i < 18; i++) { v[i] -= m; q += v[i] * v[i]; }
#pragma unroll
    for (int o = 16; o; o >>= 1) q += __shfl_xor_sync(~0u, q, o);
    float r = 1.f / sqrtf(q * (1.f / D_) + 1e-5f);
    uint32_t* dst = (uint32_t*)((pass == 0 ? g_xn : g_h2) + (size_t)row * D_);
    s = 0.f;
#pragma unroll
    for (int i = 0; i < 9; i++) {
      uint32_t p = pack_bf16(v[2 * i] * r, v[2 * i + 1] * r);
      dst[lane + 32 * i] = p;
      float2 f = unpack_bf16(p); v[2 * i] = f.x; v[2 * i + 1] = f.y; s += f.x + f.y;
    }
  }
}

template<int TA> __device__ __forceinline__ void wgmma_n256(float (&d)[128], uint64_t da, uint64_t db, int sc) {
  asm volatile("{\n.reg .pred p;\nsetp.ne.b32 p, %130, 0;\n"
    "wgmma.mma_async.sync.aligned.m64n256k16.f32.bf16.bf16 {%0, %1, %2, %3, %4, %5, %6, %7, %8, %9, %10, %11, %12, %13, %14, %15, %16, %17, %18, %19, %20, %21, %22, %23, %24, %25, %26, %27, %28, %29, %30, %31, %32, %33, %34, %35, %36, %37, %38, %39, %40, %41, %42, %43, %44, %45, %46, %47, %48, %49, %50, %51, %52, %53, %54, %55, %56, %57, %58, %59, %60, %61, %62, %63, %64, %65, %66, %67, %68, %69, %70, %71, %72, %73, %74, %75, %76, %77, %78, %79, %80, %81, %82, %83, %84, %85, %86, %87, %88, %89, %90, %91, %92, %93, %94, %95, %96, %97, %98, %99, %100, %101, %102, %103, %104, %105, %106, %107, %108, %109, %110, %111, %112, %113, %114, %115, %116, %117, %118, %119, %120, %121, %122, %123, %124, %125, %126, %127}, %128, %129, p, 1, 1, %131, 1;\n}\n"
    : "+f"(d[0]), "+f"(d[1]), "+f"(d[2]), "+f"(d[3]), "+f"(d[4]), "+f"(d[5]), "+f"(d[6]), "+f"(d[7]), "+f"(d[8]), "+f"(d[9]), "+f"(d[10]), "+f"(d[11]), "+f"(d[12]), "+f"(d[13]), "+f"(d[14]), "+f"(d[15]), "+f"(d[16]), "+f"(d[17]), "+f"(d[18]), "+f"(d[19]), "+f"(d[20]), "+f"(d[21]), "+f"(d[22]), "+f"(d[23]), "+f"(d[24]), "+f"(d[25]), "+f"(d[26]), "+f"(d[27]), "+f"(d[28]), "+f"(d[29]), "+f"(d[30]), "+f"(d[31]), "+f"(d[32]), "+f"(d[33]), "+f"(d[34]), "+f"(d[35]), "+f"(d[36]), "+f"(d[37]), "+f"(d[38]), "+f"(d[39]), "+f"(d[40]), "+f"(d[41]), "+f"(d[42]), "+f"(d[43]), "+f"(d[44]), "+f"(d[45]), "+f"(d[46]), "+f"(d[47]), "+f"(d[48]), "+f"(d[49]), "+f"(d[50]), "+f"(d[51]), "+f"(d[52]), "+f"(d[53]), "+f"(d[54]), "+f"(d[55]), "+f"(d[56]), "+f"(d[57]), "+f"(d[58]), "+f"(d[59]), "+f"(d[60]), "+f"(d[61]), "+f"(d[62]), "+f"(d[63]), "+f"(d[64]), "+f"(d[65]), "+f"(d[66]), "+f"(d[67]), "+f"(d[68]), "+f"(d[69]), "+f"(d[70]), "+f"(d[71]), "+f"(d[72]), "+f"(d[73]), "+f"(d[74]), "+f"(d[75]), "+f"(d[76]), "+f"(d[77]), "+f"(d[78]), "+f"(d[79]), "+f"(d[80]), "+f"(d[81]), "+f"(d[82]), "+f"(d[83]), "+f"(d[84]), "+f"(d[85]), "+f"(d[86]), "+f"(d[87]), "+f"(d[88]), "+f"(d[89]), "+f"(d[90]), "+f"(d[91]), "+f"(d[92]), "+f"(d[93]), "+f"(d[94]), "+f"(d[95]), "+f"(d[96]), "+f"(d[97]), "+f"(d[98]), "+f"(d[99]), "+f"(d[100]), "+f"(d[101]), "+f"(d[102]), "+f"(d[103]), "+f"(d[104]), "+f"(d[105]), "+f"(d[106]), "+f"(d[107]), "+f"(d[108]), "+f"(d[109]), "+f"(d[110]), "+f"(d[111]), "+f"(d[112]), "+f"(d[113]), "+f"(d[114]), "+f"(d[115]), "+f"(d[116]), "+f"(d[117]), "+f"(d[118]), "+f"(d[119]), "+f"(d[120]), "+f"(d[121]), "+f"(d[122]), "+f"(d[123]), "+f"(d[124]), "+f"(d[125]), "+f"(d[126]), "+f"(d[127])
    : "l"(da), "l"(db), "r"(sc), "n"(TA));
}

template<int TA> __device__ __forceinline__ void wgmma_n192(float (&d)[128], uint64_t da, uint64_t db, int sc) {
  asm volatile("{\n.reg .pred p;\nsetp.ne.b32 p, %98, 0;\n"
    "wgmma.mma_async.sync.aligned.m64n192k16.f32.bf16.bf16 {%0, %1, %2, %3, %4, %5, %6, %7, %8, %9, %10, %11, %12, %13, %14, %15, %16, %17, %18, %19, %20, %21, %22, %23, %24, %25, %26, %27, %28, %29, %30, %31, %32, %33, %34, %35, %36, %37, %38, %39, %40, %41, %42, %43, %44, %45, %46, %47, %48, %49, %50, %51, %52, %53, %54, %55, %56, %57, %58, %59, %60, %61, %62, %63, %64, %65, %66, %67, %68, %69, %70, %71, %72, %73, %74, %75, %76, %77, %78, %79, %80, %81, %82, %83, %84, %85, %86, %87, %88, %89, %90, %91, %92, %93, %94, %95}, %96, %97, p, 1, 1, %99, 1;\n}\n"
    : "+f"(d[0]), "+f"(d[1]), "+f"(d[2]), "+f"(d[3]), "+f"(d[4]), "+f"(d[5]), "+f"(d[6]), "+f"(d[7]), "+f"(d[8]), "+f"(d[9]), "+f"(d[10]), "+f"(d[11]), "+f"(d[12]), "+f"(d[13]), "+f"(d[14]), "+f"(d[15]), "+f"(d[16]), "+f"(d[17]), "+f"(d[18]), "+f"(d[19]), "+f"(d[20]), "+f"(d[21]), "+f"(d[22]), "+f"(d[23]), "+f"(d[24]), "+f"(d[25]), "+f"(d[26]), "+f"(d[27]), "+f"(d[28]), "+f"(d[29]), "+f"(d[30]), "+f"(d[31]), "+f"(d[32]), "+f"(d[33]), "+f"(d[34]), "+f"(d[35]), "+f"(d[36]), "+f"(d[37]), "+f"(d[38]), "+f"(d[39]), "+f"(d[40]), "+f"(d[41]), "+f"(d[42]), "+f"(d[43]), "+f"(d[44]), "+f"(d[45]), "+f"(d[46]), "+f"(d[47]), "+f"(d[48]), "+f"(d[49]), "+f"(d[50]), "+f"(d[51]), "+f"(d[52]), "+f"(d[53]), "+f"(d[54]), "+f"(d[55]), "+f"(d[56]), "+f"(d[57]), "+f"(d[58]), "+f"(d[59]), "+f"(d[60]), "+f"(d[61]), "+f"(d[62]), "+f"(d[63]), "+f"(d[64]), "+f"(d[65]), "+f"(d[66]), "+f"(d[67]), "+f"(d[68]), "+f"(d[69]), "+f"(d[70]), "+f"(d[71]), "+f"(d[72]), "+f"(d[73]), "+f"(d[74]), "+f"(d[75]), "+f"(d[76]), "+f"(d[77]), "+f"(d[78]), "+f"(d[79]), "+f"(d[80]), "+f"(d[81]), "+f"(d[82]), "+f"(d[83]), "+f"(d[84]), "+f"(d[85]), "+f"(d[86]), "+f"(d[87]), "+f"(d[88]), "+f"(d[89]), "+f"(d[90]), "+f"(d[91]), "+f"(d[92]), "+f"(d[93]), "+f"(d[94]), "+f"(d[95])
    : "l"(da), "l"(db), "r"(sc), "n"(TA));
}

struct GemmParams {
  CUtensorMap mA[4];
  CUtensorMap mB[6];
  const bf16* x; const bf16* b1; const bf16* b2; bf16* out;
  int stride, kid;
  int wait_at_end;
  uint16_t job[960];
};
constexpr int NSTAGE = 4, STAGE_BYTES = 49152;
constexpr int GEMM_SMEM = NSTAGE * STAGE_BYTES + 8 * 2048 + 256 + 1024;

__device__ __forceinline__ uint64_t mkdesc(uint32_t addr, uint32_t lbo, uint32_t sbo) {
  return (uint64_t)((addr & 0x3FFFF) >> 4) | ((uint64_t)(lbo >> 4) << 16) | ((uint64_t)(sbo >> 4) << 32) | (1ull << 62);
}
__device__ __forceinline__ float gelu_tanh(float u) {
  float z = 0.7978845608028654f * (u + 0.044715f * u * u * u);
  float e = __expf(2.f * z);
  float th = 1.f - __fdividef(2.f, e + 1.f);
  return 0.5f * u * (1.f + th);
}
template <int BN, int TA>
__device__ __forceinline__ void gemm_mainloop(float (&d)[128], int kiters, uint32_t sbase, uint32_t fullb, uint32_t emptyb_l, uint32_t emptyb_r,
                                              int wg, int& stage, uint32_t& phase, bool elect) {
  int prev = -1;
  for (int k = 0; k < kiters; k++) {
    mbar_wait(fullb + stage * 8, phase);
    uint32_t a = sbase + stage * STAGE_BYTES + wg * 8192, b = sbase + stage * STAGE_BYTES + 16384;
    asm volatile("wgmma.fence.sync.aligned;" ::: "memory");
#pragma unroll
    for (int kk = 0; kk < 4; kk++) {
      uint64_t da = TA ? mkdesc(a + kk * 2048, 8192, 1024) : mkdesc(a + kk * 32, 16, 1024);
      uint64_t db = mkdesc(b + kk * 2048, 8192, 1024);
      if constexpr (BN == 256) wgmma_n256<TA>(d, da, db, (k | kk) != 0); else wgmma_n192<TA>(d, da, db, (k | kk) != 0);
    }
    asm volatile("wgmma.commit_group.sync.aligned;" ::: "memory");
    asm volatile("wgmma.wait_group.sync.aligned 1;" ::: "memory");
    if (prev >= 0 && elect) { mbar_arrive_remote(emptyb_l + prev * 8); mbar_arrive_remote(emptyb_r + prev * 8); }
    prev = stage;
    if (++stage == NSTAGE) { stage = 0; phase ^= 1; }
  }
  asm volatile("wgmma.wait_group.sync.aligned 0;" ::: "memory");
  if (elect) { mbar_arrive_remote(emptyb_l + prev * 8); mbar_arrive_remote(emptyb_r + prev * 8); }
}
template <int BN, class F>
__device__ __forceinline__ void store_tile(const float (&d)[128], uint32_t stg, bf16* dst, int ld, int lane, F f) {
#pragma unroll
  for (int c = 0; c < BN / 64; c++) {
#pragma unroll
    for (int i = 0; i < 8; i += 2) {
      const int o = c * 32 + i * 4;
      uint32_t r0 = f(d[o], d[o + 1], 0, c * 64 + i * 8), r1 = f(d[o + 2], d[o + 3], 1, c * 64 + i * 8);
      uint32_t r2 = f(d[o + 4], d[o + 5], 0, c * 64 + i * 8 + 8), r3 = f(d[o + 6], d[o + 7], 1, c * 64 + i * 8 + 8);
      int m = lane >> 3, row = (m & 1) * 8 + (lane & 7), ch = (i + (m >> 1)) ^ (row & 7);
      asm volatile("stmatrix.sync.aligned.m8n8.x4.shared.b16 [%0], {%1,%2,%3,%4};" ::"r"(stg + row * 128 + ch * 16), "r"(r0), "r"(r1), "r"(r2), "r"(r3) : "memory");
    }
    __syncwarp();
#pragma unroll
    for (int j = 0; j < 4; j++) {
      int idx = lane + 32 * j, row = idx >> 3, ch = idx & 7;
      uint4 v;
      asm volatile("ld.shared.v4.u32 {%0,%1,%2,%3}, [%4];" : "=r"(v.x), "=r"(v.y), "=r"(v.z), "=r"(v.w) : "r"(stg + row * 128 + ((ch ^ (row & 7)) * 16)));
      *(uint4*)(dst + (size_t)row * ld + c * 64 + ch * 8) = v;
    }
    __syncwarp();
  }
}

__device__ __forceinline__ void attn_unit(int seg, int h, uint8_t* sm, int lane, const unsigned int* segflag) {
  const int g = lane >> 2, t = lane & 3;
  const uint32_t sv = smem_u32(sm);
  const size_t tok0 = (size_t)seg * 32;
  for (int i = 128 + lane; i < 40 * 16; i += 32) {
    int r = i >> 4, c = i & 15;
    cp16(sv + r * 256 + ((c ^ (r & 7)) * 16), g_v + (tok0 + r - 8) * HD_ + h * 128 + c * 8);
  }
  for (int i = lane; i < 8 * 16; i += 32) *(uint4*)(sm + 40 * 256 + i * 16) = make_uint4(0, 0, 0, 0);
  asm volatile("cp.async.commit_group;" ::: "memory");
  float s[2][5][4];
#pragma unroll
  for (int m = 0; m < 2; m++)
#pragma unroll
    for (int n = 0; n < 5; n++) { s[m][n][0] = s[m][n][1] = s[m][n][2] = s[m][n][3] = 0.f; }
#pragma unroll
  for (int j = 0; j < 4; j++) {
    uint4 qa[2][2], kb[5];
#pragma unroll
    for (int m = 0; m < 2; m++)
#pragma unroll
      for (int hh = 0; hh < 2; hh++) qa[m][hh] = *(const uint4*)(g_q + (tok0 + m * 16 + hh * 8 + g) * HD_ + h * 128 + j * 32 + t * 8);
#pragma unroll
    for (int n = 1; n < 5; n++) kb[n] = *(const uint4*)(g_k + (tok0 + (n - 1) * 8 + g) * HD_ + h * 128 + j * 32 + t * 8);
#pragma unroll
    for (int m = 0; m < 2; m++) {
      uint32_t a0[4] = {qa[m][0].x, qa[m][1].x, qa[m][0].y, qa[m][1].y}, a1[4] = {qa[m][0].z, qa[m][1].z, qa[m][0].w, qa[m][1].w};
#pragma unroll
      for (int n = 1; n < 5; n++) { mma16816(s[m][n], a0, kb[n].x, kb[n].y); mma16816(s[m][n], a1, kb[n].z, kb[n].w); }
    }
  }
  if (lane == 0) wait_cnt(segflag, 64);
  __syncwarp();
  for (int i = lane; i < 128; i += 32) {
    int r = i >> 4, c = i & 15;
    cp16(sv + r * 256 + ((c ^ (r & 7)) * 16), g_vm + ((size_t)seg * 8 + r) * HD_ + h * 128 + c * 8);
  }
  asm volatile("cp.async.commit_group;" ::: "memory");
  {
    uint4 km[4], qa[4][2][2];
#pragma unroll
    for (int j = 0; j < 4; j++) {
      km[j] = __ldcg((const uint4*)(g_km + ((size_t)seg * 8 + g) * HD_ + h * 128 + j * 32 + t * 8));
#pragma unroll
      for (int m = 0; m < 2; m++)
#pragma unroll
        for (int hh = 0; hh < 2; hh++) qa[j][m][hh] = *(const uint4*)(g_q + (tok0 + m * 16 + hh * 8 + g) * HD_ + h * 128 + j * 32 + t * 8);
    }
#pragma unroll
    for (int j = 0; j < 4; j++)
#pragma unroll
      for (int m = 0; m < 2; m++) {
        uint32_t a0[4] = {qa[j][m][0].x, qa[j][m][1].x, qa[j][m][0].y, qa[j][m][1].y}, a1[4] = {qa[j][m][0].z, qa[j][m][1].z, qa[j][m][0].w, qa[j][m][1].w};
        mma16816(s[m][0], a0, km[j].x, km[j].y); mma16816(s[m][0], a1, km[j].z, km[j].w);
      }
  }
  const float sc = 0.08838834764831845f * 1.4426950408889634f;
  uint32_t pa[2][3][4];
#pragma unroll
  for (int m = 0; m < 2; m++) {
    float inv[2];
#pragma unroll
    for (int hh = 0; hh < 2; hh++) {
      int qi = 8 + m * 16 + hh * 8 + g;
      float mx = -INFINITY;
#pragma unroll
      for (int n = 0; n < 5; n++)
#pragma unroll
        for (int e = 0; e < 2; e++) { float& z = s[m][n][hh * 2 + e]; z = (n * 8 + t * 2 + e <= qi) ? z * sc : -INFINITY; mx = fmaxf(mx, z); }
      mx = fmaxf(mx, __shfl_xor_sync(~0u, mx, 1)); mx = fmaxf(mx, __shfl_xor_sync(~0u, mx, 2));
      float sum = 0.f;
#pragma unroll
      for (int n = 0; n < 5; n++)
#pragma unroll
        for (int e = 0; e < 2; e++) { float& z = s[m][n][hh * 2 + e]; z = exp2f(z - mx); sum += z; }
      sum += __shfl_xor_sync(~0u, sum, 1); sum += __shfl_xor_sync(~0u, sum, 2);
      inv[hh] = 1.f / sum;
    }
#pragma unroll
    for (int kk = 0; kk < 3; kk++) {
      pa[m][kk][0] = pack_bf16(s[m][2 * kk][0] * inv[0], s[m][2 * kk][1] * inv[0]);
      pa[m][kk][1] = pack_bf16(s[m][2 * kk][2] * inv[1], s[m][2 * kk][3] * inv[1]);
      if (kk < 2) {
        pa[m][kk][2] = pack_bf16(s[m][2 * kk + 1][0] * inv[0], s[m][2 * kk + 1][1] * inv[0]);
        pa[m][kk][3] = pack_bf16(s[m][2 * kk + 1][2] * inv[1], s[m][2 * kk + 1][3] * inv[1]);
      } else { pa[m][kk][2] = 0; pa[m][kk][3] = 0; }
    }
  }
  asm volatile("cp.async.wait_group 0;" ::: "memory");
  __syncwarp();
  uint32_t ov[2][16][2];
#pragma unroll
  for (int np = 0; np < 8; np++) {
    float o[2][2][4] = {};
#pragma unroll
    for (int kk = 0; kk < 3; kk++) {
      uint32_t b[4];
      int mi = lane >> 3, r = kk * 16 + (mi & 1) * 8 + (lane & 7), c = np * 2 + (mi >> 1);
      ldsm4t(b, sv + r * 256 + ((c ^ (r & 7)) * 16));
#pragma unroll
      for (int m = 0; m < 2; m++) { mma16816(o[m][0], pa[m][kk], b[0], b[1]); mma16816(o[m][1], pa[m][kk], b[2], b[3]); }
    }
#pragma unroll
    for (int m = 0; m < 2; m++)
#pragma unroll
      for (int q = 0; q < 2; q++) { ov[m][np * 2 + q][0] = pack_bf16(o[m][q][0], o[m][q][1]); ov[m][np * 2 + q][1] = pack_bf16(o[m][q][2], o[m][q][3]); }
  }
  __syncwarp();
#pragma unroll
  for (int m = 0; m < 2; m++)
#pragma unroll
    for (int n = 0; n < 16; n++)
#pragma unroll
      for (int hh = 0; hh < 2; hh++) {
        int r = m * 16 + hh * 8 + g;
        *(uint32_t*)(sm + r * 256 + ((n ^ (r & 7)) * 16) + t * 4) = ov[m][n][hh];
      }
  __syncwarp();
#pragma unroll
  for (int i = 0; i < 16; i++) {
    int idx = lane + 32 * i, r = idx >> 4, c = idx & 15;
    *(uint4*)(g_o + (tok0 + r) * HD_ + h * 128 + c * 8) = *(const uint4*)(sm + r * 256 + ((c ^ (r & 7)) * 16));
  }
}

__global__ void __launch_bounds__(384, 1) gemm_kernel(const __grid_constant__ GemmParams p) {
  extern __shared__ uint8_t smem_raw[];
  const uint32_t sbase = (smem_u32(smem_raw) + 1023) & ~1023u;
  const uint32_t stg0 = sbase + NSTAGE * STAGE_BYTES, fullb = stg0 + 8 * 2048, emptyb = fullb + 64;
  const uint32_t rank = cluster_rank();
  const int wg = __shfl_sync(~0u, (int)(threadIdx.x >> 7), 0), lane = threadIdx.x & 31;
  const int cl = blockIdx.x >> 1;
  if (threadIdx.x == 0) {
    for (int i = 0; i < NSTAGE; i++) { mbar_init(fullb + i * 8, 1); mbar_init(emptyb + i * 8, 4); }
    asm volatile("fence.mbarrier_init.release.cluster;" ::: "memory");
  }
  cluster_sync();
  if (blockIdx.x == 0 && threadIdx.x == 0) PT(1 + p.kid * 2);
  const uint16_t* jobs = p.job + cl * p.stride;
  if (wg == 0) {
    asm volatile("setmaxnreg.dec.sync.aligned.u32 40;");
    if (threadIdx.x == 0) {
      int stage = 0; uint32_t phase = 1;
      for (int j = 0; j < p.stride; j++) {
        uint32_t job = jobs[j];
        if (job == 0xFFFF) break;
        int type = job >> 12, m = (job >> 6) & 63, n = job & 63;
        int row0 = m * 256 + rank * 128;
        int bn = type < 3 ? 256 : 192;
        if (type == 6) {
          for (int k = 0; k < NSTAGE; k++) {
            mbar_wait_cl(emptyb + stage * 8, phase);
            asm volatile("mbarrier.arrive.shared::cta.b64 _, [%0];" ::"r"(fullb + stage * 8) : "memory");
            if (++stage == NSTAGE) { stage = 0; phase ^= 1; }
          }
          continue;
        }
        int kit = type < 3 ? 9 : (type == 3 ? 32 : (type == 4 ? 72 : (type == 5 ? 64 : 8)));
        int k0 = 0;
        if (type == 7) { k0 = (n / 3) * 8; n = n % 3; type = 5; }
        if (type == 5) wait_cnt(&g_cnt[16 + m], 32);
        const CUtensorMap* ma = &p.mA[type < 3 ? 0 : type - 2];
        const CUtensorMap* mb = &p.mB[type];
        bool ta = (type == 3 || type == 4);
        if (type >= 4) {
          if (type == 4) wait_cnt(&g_cnt[0], 108);
          asm volatile("fence.proxy.async;" ::: "memory");
        }
        for (int k = k0; k < k0 + kit; k++) {
          mbar_wait_cl(emptyb + stage * 8, phase);
          uint32_t fb = fullb + stage * 8, a = sbase + stage * STAGE_BYTES, b = a + 16384;
          mbar_expect(fb, 16384 + bn * 128);
          if (ta) { tma2d(a, ma, row0, k * 64, fb); tma2d(a + 8192, ma, row0 + 64, k * 64, fb); }
          else tma2d(a, ma, k * 64, row0, fb);
          for (int i = 0; i < bn / 64; i++) tma2d_mc(b + i * 8192 + rank * 4096, mb, n * bn + i * 64, k * 64 + rank * 32, fb, (uint16_t)3);
          if (++stage == NSTAGE) { stage = 0; phase ^= 1; }
        }
      }
    }
    __syncwarp();
    pdl_launch();
    cluster_sync();
  } else {
    asm volatile("setmaxnreg.inc.sync.aligned.u32 232;");
    const int cw = wg - 1, warp = __shfl_sync(~0u, (int)(threadIdx.x >> 5) & 3, 0);
    const uint32_t eb_l = mapa(emptyb, rank), eb_r = mapa(emptyb, rank ^ 1);
    const uint32_t stg = stg0 + (cw * 4 + warp) * 2048;
    const bool elect = (threadIdx.x & 127) == 0;
    const int g = lane >> 2, t = lane & 3;
    int stage = 0; uint32_t phase = 0;
    float d[128];
    for (int j = 0; j < p.stride; j++) {
      uint32_t job = jobs[j];
      if (job == 0xFFFF) break;
      int type = job >> 12, m = (job >> 6) & 63, n = job & 63;
      int row0 = m * 256 + rank * 128 + cw * 64 + warp * 16;
      if (type < 3) {
        gemm_mainloop<256, 0>(d, 9, sbase, fullb, eb_l, eb_r, cw, stage, phase, elect);
        bf16* dst = (type == 0 ? g_q : (type == 1 ? g_k : g_v)) + (size_t)row0 * HD_ + n * 256;
        store_tile<256>(d, stg, dst, HD_, lane, [](float a, float b, int, int) { return pack_bf16(a, b); });
        __threadfence();
        asm volatile("bar.sync %0, 256;" ::"r"(1) : "memory");
        if (threadIdx.x == 128) atomicAdd(&g_cnt[(type ? 8 : 40) + m], 1);
      } else if (type == 3) {
        gemm_mainloop<192, 1>(d, 32, sbase, fullb, eb_l, eb_r, cw, stage, phase, elect);
        float bb[2] = {__bfloat162float(p.b1[row0 + g]), __bfloat162float(p.b1[row0 + g + 8])};
        store_tile<192>(d, stg, g_ut + (size_t)row0 * D_ + n * 192, D_, lane,
                        [&](float a, float b, int h, int) { return pack_bf16(gelu_tanh(a + bb[h]), gelu_tanh(b + bb[h])); });
        __threadfence();
        asm volatile("fence.proxy.async;" ::: "memory");
        asm volatile("bar.sync %0, 256;" ::"r"(1) : "memory");
        if (threadIdx.x == 128) atomicAdd(&g_cnt[0], 1);
      } else if (type == 4) {
        gemm_mainloop<192, 1>(d, 72, sbase, fullb, eb_l, eb_r, cw, stage, phase, elect);
        float bb[2] = {__bfloat162float(p.b2[row0 + g]), __bfloat162float(p.b2[row0 + g + 8])};
#pragma unroll
        for (int i = 0; i < 24; i++)
#pragma unroll
          for (int h = 0; h < 2; h++) {
            size_t off = (size_t)(row0 + g + h * 8) * D_ + n * 192 + i * 8 + t * 2;
            float2 xv = unpack_bf16(*(const uint32_t*)(p.x + off));
            *(float2*)(g_yb + off) = make_float2(d[i * 4 + h * 2] + bb[h] + xv.x, d[i * 4 + h * 2 + 1] + bb[h] + xv.y);
          }
        __threadfence();
        asm volatile("bar.sync %0, 256;" ::"r"(1) : "memory");
        if (threadIdx.x == 128) atomicAdd(&g_cnt[24 + m], 1);
      } else if (type == 6) {
        const int st0 = stage;
        for (int k = 0; k < NSTAGE; k++) { mbar_wait(fullb + stage * 8, phase); if (++stage == NSTAGE) { stage = 0; phase ^= 1; } }
        const int seg = m * 8 + (n >> 1), w8 = cw * 4 + warp;
        if (lane == 0) wait_cnt(&g_cnt[40 + m], 32);
        __syncwarp();
        {
          const size_t o = ((size_t)seg * 32 + lane) * HD_ + ((n & 1) * 16 + rank * 8 + w8) * 128;
#pragma unroll
          for (int i = 0; i < 2; i++) {
            asm volatile("prefetch.global.L2 [%0];" ::"l"(g_q + o + i * 64)); asm volatile("prefetch.global.L2 [%0];" ::"l"(g_k + o + i * 64));
            asm volatile("prefetch.global.L2 [%0];" ::"l"(g_v + o + i * 64));
          }
        }
        attn_unit(seg, (n & 1) * 16 + rank * 8 + w8, smem_raw + (sbase - smem_u32(smem_raw)) + w8 * 12288, lane, &g_cnt[96 + seg]);
        __threadfence();
        asm volatile("fence.proxy.async;" ::: "memory");
        asm volatile("bar.sync %0, 256;" ::"r"(1) : "memory");
        if (elect) for (int k = 0; k < NSTAGE; k++) { mbar_arrive_remote(eb_l + k * 8); mbar_arrive_remote(eb_r + k * 8); }
        if (threadIdx.x == 128) atomicAdd(&g_cnt[16 + m], 1);
        (void)st0;
#pragma unroll
        for (int i = 0; i < 128; i++) d[i] = 0.f;
      } else if (type == 7) {
        const int nt = n % 3;
        gemm_mainloop<192, 0>(d, 8, sbase, fullb, eb_l, eb_r, cw, stage, phase, elect);
        if (lane == 0) wait_cnt(&g_cnt[24 + m], 6);
        __syncwarp();
        if (p.kid == 2) {
          const int ks = n / 3;
          float* pk = g_pk + ((size_t)ks * 512 + row0 - 1536 + g) * D_ + nt * 192 + t * 2;
#pragma unroll
          for (int i = 0; i < 24; i++)
#pragma unroll
            for (int h = 0; h < 2; h++) *(float2*)(pk + h * 8 * D_ + i * 8) = make_float2(d[i * 4 + h * 2], d[i * 4 + h * 2 + 1]);
          __threadfence();
          asm volatile("bar.sync %0, 256;" ::"r"(1) : "memory");
          unsigned int* cn = &g_cnt[48 + ((m - 4) * 3 + nt) * 2 + rank];
          if (threadIdx.x == 128) atomicAdd(cn, 1);
          if (lane == 0) wait_cnt(cn, 8);
          __syncwarp();
          const int r0 = m * 256 + rank * 128 + ks * 16;
#pragma unroll
          for (int it = 0; it < 3; it++) {
            int i = threadIdx.x - 128 + it * 256, rr = i / 48, cc = (i - rr * 48) * 4;
            size_t off = (size_t)(r0 + rr) * D_ + nt * 192 + cc;
            float4 y = __ldcg((const float4*)(g_yb + off)), q[8];
#pragma unroll
            for (int k = 0; k < 8; k++) q[k] = __ldcg((const float4*)(g_pk + (size_t)k * 512 * D_ + off - (size_t)1536 * D_));
#pragma unroll
            for (int k = 0; k < 8; k++) { y.x += q[k].x; y.y += q[k].y; y.z += q[k].z; y.w += q[k].w; }
            *(uint2*)(p.out + off) = make_uint2(pack_bf16(y.x, y.y), pack_bf16(y.z, y.w));
          }
          continue;
        }
#pragma unroll
        for (int i = 0; i < 24; i++)
#pragma unroll
          for (int h = 0; h < 2; h++)
            atomicAdd((float2*)(g_yb + (size_t)(row0 + g + h * 8) * D_ + nt * 192 + i * 8 + t * 2), make_float2(d[i * 4 + h * 2], d[i * 4 + h * 2 + 1]));
        __threadfence();
        asm volatile("bar.sync %0, 256;" ::"r"(1) : "memory");
        volatile uint32_t* lastf = (volatile uint32_t*)(smem_raw + (emptyb + 64 - smem_u32(smem_raw)));
        if (threadIdx.x == 128) { *lastf = atomicAdd(&g_cnt[48 + ((m - 4) * 3 + nt) * 2 + rank], 1); __threadfence(); }
        asm volatile("bar.sync %0, 256;" ::"r"(1) : "memory");
        if (*lastf == 7) {
          const int r0 = m * 256 + rank * 128;
#pragma unroll 8
          for (int i = threadIdx.x - 128; i < 128 * 48; i += 256) {
            int rr = i / 48, cc = (i - rr * 48) * 4;
            size_t off = (size_t)(r0 + rr) * D_ + nt * 192 + cc;
            float4 y = __ldcg((const float4*)(g_yb + off));
            *(uint2*)(p.out + off) = make_uint2(pack_bf16(y.x, y.y), pack_bf16(y.z, y.w));
          }
        }
        asm volatile("bar.sync %0, 256;" ::"r"(1) : "memory");
      } else {
        gemm_mainloop<192, 0>(d, 64, sbase, fullb, eb_l, eb_r, cw, stage, phase, elect);
        if (lane == 0) wait_cnt(&g_cnt[24 + m], 6);
        __syncwarp();
        const float* yb = g_yb + (size_t)(row0 + g) * D_ + n * 192 + t * 2;
        store_tile<192>(d, stg, p.out + (size_t)row0 * D_ + n * 192, D_, lane,
                        [&](float a, float b, int h, int c) { float2 y = *(const float2*)(yb + h * 8 * D_ + c); return pack_bf16(a + y.x, b + y.y); });
      }
    }
    if (blockIdx.x == 0 && threadIdx.x == 128) PT(2 + p.kid * 2);
    cluster_sync();
  }
}

constexpr int CH_WV = 0;
constexpr int CH_MEM = CH_WV + 73728;
constexpr int CH_KB = CH_MEM + 9216;
constexpr int CH_VB = CH_KB + 12288;
constexpr int CH_WO = CH_VB + 12288;
constexpr int CH_Q = CH_WO + 81920;
constexpr int CH_R1 = CH_Q + 1024;
constexpr int CH_SC = CH_R1 + 4096;
constexpr int CH_OF = CH_SC + 3584;
constexpr int CH_R2 = CH_OF + 8192;
constexpr int CH_BAR = CH_R2 + 12288;
constexpr int CHAIN_SMEM = CH_BAR + 64 + 1024;
#define POLL_DELAY 550
__device__ __forceinline__ void st_async1(uint32_t a, uint32_t v, uint32_t bar) { asm volatile("st.async.weak.shared::cluster.mbarrier::complete_tx::bytes.b32 [%0], %1, [%2];" ::"r"(a), "r"(v), "r"(bar) : "memory"); }
__device__ __forceinline__ void st_async2(uint32_t a, uint32_t v0, uint32_t v1, uint32_t bar) { asm volatile("st.async.weak.shared::cluster.mbarrier::complete_tx::bytes.v2.b32 [%0], {%1, %2}, [%3];" ::"r"(a), "r"(v0), "r"(v1), "r"(bar) : "memory"); }
__device__ __forceinline__ uint4 lds128(uint32_t a) { uint4 v; asm volatile("ld.shared.v4.u32 {%0,%1,%2,%3}, [%4];" : "=r"(v.x), "=r"(v.y), "=r"(v.z), "=r"(v.w) : "r"(a) : "memory"); return v; }
__device__ __forceinline__ void sts128f(uint32_t a, const float (&c)[4]) { asm volatile("st.shared.v4.f32 [%0], {%1,%2,%3,%4};" ::"r"(a), "f"(c[0]), "f"(c[1]), "f"(c[2]), "f"(c[3]) : "memory"); }
__device__ __forceinline__ void sts32(uint32_t a, uint32_t v) { asm volatile("st.shared.u32 [%0], %1;" ::"r"(a), "r"(v) : "memory"); }
__device__ __forceinline__ void mbar_wait_b(uint32_t b, uint32_t parity) {
  uint32_t ok; int n = 0;
  do { asm volatile("{\n.reg .pred p;\nmbarrier.try_wait.parity.shared::cta.b64 p, [%1], %2;\nselp.u32 %0, 1, 0, p;\n}" : "=r"(ok) : "r"(b), "r"(parity) : "memory"); } while (!ok && ++n < (1 << 20));
}
__device__ __forceinline__ uint32_t mapa_v(uint32_t a, uint32_t r) { uint32_t o; asm volatile("mapa.shared::cluster.u32 %0, %1, %2;" : "=r"(o) : "r"(a), "r"(r)); return o; }
__device__ __forceinline__ uint32_t tid_v() { uint32_t o; asm volatile("mov.u32 %0, %%tid.x;" : "=r"(o)); return o; }
template <int ACC>
__device__ __forceinline__ void wg_rs(float (&d)[4], const uint32_t (&a)[4], uint32_t dlo) {
  uint64_t db = ((uint64_t)16 << 32) | dlo;
  asm volatile("{\n.reg .pred p;\nsetp.ne.b32 p, %9, 0;\nwgmma.mma_async.sync.aligned.m64n8k16.f32.bf16.bf16 {%0,%1,%2,%3}, {%4,%5,%6,%7}, %8, p, 1, 1, 0;\n}"
               : "+f"(d[0]), "+f"(d[1]), "+f"(d[2]), "+f"(d[3]) : "r"(a[0]), "r"(a[1]), "r"(a[2]), "r"(a[3]), "l"(db), "n"(ACC));
}
template <int N>
__device__ __forceinline__ void wg_wait(float (&d)[N][4]) {
  asm volatile("wgmma.commit_group.sync.aligned;\nwgmma.wait_group.sync.aligned 0;" ::: "memory");
#pragma unroll
  for (int i = 0; i < N; i++) asm volatile("" : "+f"(d[i][0]), "+f"(d[i][1]), "+f"(d[i][2]), "+f"(d[i][3]) :: "memory");
}
#define BAR_ALL() asm volatile("bar.sync 0, 256;" ::: "memory")

__global__ void __launch_bounds__(256, 1) chain_kernel(const bf16* __restrict__ mem0, const bf16* __restrict__ Wq, const bf16* __restrict__ Wk,
                                                       const bf16* __restrict__ Wv, const bf16* __restrict__ Wo) {
  extern __shared__ uint8_t smem_raw[];
  const uint32_t sb = (smem_u32(smem_raw) + 1023) & ~1023u;
  const int tid = threadIdx.x, warp = __shfl_sync(~0u, tid >> 5, 0), wgi = __shfl_sync(~0u, tid >> 7, 0), lane = tid & 31, g = lane >> 2, t = lane & 3;
  const uint32_t r = cluster_rank();
  const int c = blockIdx.x >> 3, h = 4 * c + (r >> 1), j0 = h * 128 + (r & 1) * 64;
  const uint32_t bm = sb + CH_BAR, bs = bm + 8, bo = bm + 16;
  pdl_launch();
  if (blockIdx.x == 0 && tid == 0) PT(7);
  if (tid == 0) { mbar_init(bm, 1); mbar_init(bs, 1); mbar_init(bo, 1); asm volatile("fence.mbarrier_init.release.cluster;" ::: "memory"); }
  const int mi = lane >> 3, l7 = lane & 7;
  for (int i = tid; i < 576 * 8; i += 256) {
    int row = i >> 3, ch = i & 7;
    cp16(sb + CH_WV + row * 128 + ((ch ^ (row & 7)) * 16), Wq + (size_t)row * HD_ + j0 + ch * 8);
    cp16(sb + CH_WO + row * 128 + ((ch ^ (row & 7)) * 16), Wk + (size_t)row * HD_ + j0 + ch * 8);
  }
  asm volatile("cp.async.commit_group;\ncp.async.wait_group 0;" ::: "memory");
  BAR_ALL();
  uint32_t w1[36][4];
#pragma unroll
  for (int i = 0; i < 36; i++) {
    int row = i * 16 + (mi >> 1) * 8 + l7, ch = ((warp & 3) * 2 + (mi & 1)) ^ (row & 7);
    ldsm4t(w1[i], sb + (wgi ? CH_WO : CH_WV) + row * 128 + ch * 16);
  }
  BAR_ALL();
  for (int i = tid; i < 512 * 10; i += 256) {
    int row = i / 10, ch = i - row * 10;
    cp16(sb + CH_WV + row * 176 + ch * 16, Wo + (size_t)(c * 512 + row) * D_ + (ch < 8 ? r * 64 + ch * 8 : 512 + (r >> 1) * 16 + (ch - 8) * 8));
  }
  asm volatile("cp.async.commit_group;\ncp.async.wait_group 0;" ::: "memory");
  BAR_ALL();
  const int kperm = 2 * ((mi >> 1) * 2 + (l7 >> 2)) + (l7 & 1) + 8 * ((l7 >> 1) & 1);
  for (int i = 0; i < 16; i++) {
    uint32_t a[4];
    ldsm4t(a, sb + CH_WV + ((wgi * 16 + i) * 16 + kperm) * 176 + ((warp & 3) * 2 + (mi & 1)) * 16);
    asm volatile("st.shared.v4.u32 [%0], {%1,%2,%3,%4};" ::"r"(sb + CH_WO + 8192 + (warp * 16 + i) * 512 + lane * 16), "r"(a[0]), "r"(a[1]), "r"(a[2]), "r"(a[3]) : "memory");
  }
  for (int u = warp; u < 16; u += 8) {
    uint32_t a[4];
    ldsm4t(a, sb + CH_WV + (((r & 1) * 16 + u) * 16 + kperm) * 176 + (8 + (mi & 1)) * 16);
    asm volatile("st.shared.v4.u32 [%0], {%1,%2,%3,%4};" ::"r"(sb + CH_WO + u * 512 + lane * 16), "r"(a[0]), "r"(a[1]), "r"(a[2]), "r"(a[3]) : "memory");
  }
  BAR_ALL();
  for (int i = tid; i < 576 * 8; i += 256) {
    int row = i >> 3, ch = i & 7;
    cp16(sb + CH_WV + row * 128 + ((ch ^ (row & 7)) * 16), Wv + (size_t)row * HD_ + j0 + ch * 8);
  }
  for (int i = tid; i < 8 * 72; i += 256) {
    int row = i / 72, ch = i - row * 72;
    cp16(sb + CH_MEM + ch * 128 + row * 16, mem0 + row * D_ + ch * 8);
  }
  for (int i = tid; i < 4 * 64; i += 256) {
    int b = i >> 6, o = i & 63;
    asm volatile("st.shared.v4.u32 [%0], {%1,%1,%1,%1};" ::"r"(sb + CH_KB + b * 6144 + 40 * 128 + o * 16), "r"(0) : "memory");
  }
  auto prefetch_kv = [&](int s, int tid) {
    if ((s & 7) == 0) { if ((tid & 31) == 0) wait_cnt(&g_cnt[8 + (s >> 3)], 64); __syncwarp(); }
#pragma unroll
    for (int i = 0; i < 2; i++) {
      int u = tid + i * 256, which = u >> 8, row = (u & 255) >> 3, ch = u & 7;
      const bf16* src = (which ? g_v : g_k) + (size_t)(s * 32 + row) * HD_ + j0 + ch * 8;
      cp16(sb + (which ? CH_VB : CH_KB) + (s & 1) * 6144 + (row + 8) * 128 + ((ch ^ (row & 7)) * 16), src);
    }
    asm volatile("cp.async.commit_group;" ::: "memory");
  };
  prefetch_kv(0, tid);
  asm volatile("cp.async.wait_group 0;" ::: "memory");
  asm volatile("fence.proxy.async.shared::cta;" ::: "memory");
  BAR_ALL();
  cluster_sync();
  const uint32_t dsb = ((sb & 0x3FFFF) >> 4) | (8u << 16);
  if (blockIdx.x == 0 && tid == 0) PT(10);
#define CP(i) if (blockIdx.x == 0 && lane == 0 && warp == (((i) == 5 || (i) == 7) ? 4 : 0)) PC(64 + s * 16 + (i))
  for (int s = 0; s < NSEG; s++) {
    const int tid = tid_v(), lane = tid & 31, g = lane >> 2, t = lane & 3, mi = lane >> 3, l7 = lane & 7;
    CP(0);
    const uint32_t par = s & 1, kb = sb + CH_KB + par * 6144, vb = sb + CH_VB + par * 6144;
    if (s > 0) mbar_wait_b(bm, par ^ 1);
    CP(1);
    if (tid == 0 && s < NSEG - 1) { mbar_expect(bs, 2560); mbar_expect(bo, 8192); mbar_expect(bm, 9216); }
    auto phase1 = [&]() {
      float pa[3][4] = {};
#pragma unroll
      for (int i = 0; i < 36; i += 2) {
        uint32_t b[4];
        ldsm4(b, sb + CH_MEM + i * 256 + mi * 128 + l7 * 16);
        mma16816(pa[i % 3], w1[i], b[0], b[1]); mma16816(pa[(i + 1) % 3], w1[i + 1], b[2], b[3]);
      }
      CP(2);
      uint32_t b0 = movm(pack_bf16(pa[0][0] + pa[1][0] + pa[2][0], pa[0][1] + pa[1][1] + pa[2][1]));
      uint32_t b1 = movm(pack_bf16(pa[0][2] + pa[1][2] + pa[2][2], pa[0][3] + pa[1][3] + pa[2][3]));
      uint32_t dst = (wgi ? kb : sb + CH_Q) + g * 128 + t * 4;
      sts32(dst + ((((warp & 3) * 2) ^ g) * 16), b0); sts32(dst + ((((warp & 3) * 2 + 1) ^ g) * 16), b1);
      if (wgi) { uint32_t* gp = (uint32_t*)(g_km + ((size_t)s * 8 + g) * HD_ + j0 + (warp & 3) * 16 + t * 2); gp[0] = b0; gp[4] = b1; }
      asm volatile("cp.async.wait_group 0;" ::: "memory");
    };
    if (wgi == 0) {
      phase1();
      BAR_ALL();
      CP(4);
      if (s + 1 < NSEG) { prefetch_kv(s + 1, tid); asm volatile("bar.sync 6, 224;" ::: "memory"); }
      float va[4][4];
      asm volatile("wgmma.fence.sync.aligned;" ::: "memory");
      const uint32_t dwa = (((sb + CH_WV) & 0x3FFFF) >> 4) | ((8192u >> 4) << 16);
#pragma unroll
      for (int ks = 0; ks < 36; ks++) {
        uint64_t da = ((uint64_t)(0x40000000u | (1024 >> 4)) << 32) | (dwa + ks * 128), db = ((uint64_t)16 << 32) | (dsb + ((CH_MEM + ks * 256) >> 4));
        if (ks < 4)
          asm volatile("{\n.reg .pred p;\nsetp.ne.b32 p, 0, 0;\nwgmma.mma_async.sync.aligned.m64n8k16.f32.bf16.bf16 {%0,%1,%2,%3}, %4, %5, p, 1, 1, 1, 0;\n}"
                       : "=f"(va[ks & 3][0]), "=f"(va[ks & 3][1]), "=f"(va[ks & 3][2]), "=f"(va[ks & 3][3]) : "l"(da), "l"(db));
        else
          asm volatile("{\n.reg .pred p;\nsetp.ne.b32 p, 1, 0;\nwgmma.mma_async.sync.aligned.m64n8k16.f32.bf16.bf16 {%0,%1,%2,%3}, %4, %5, p, 1, 1, 1, 0;\n}"
                       : "+f"(va[ks & 3][0]), "+f"(va[ks & 3][1]), "+f"(va[ks & 3][2]), "+f"(va[ks & 3][3]) : "l"(da), "l"(db));
      }
      wg_wait(va);
      CP(6);
      uint32_t b0 = movm(pack_bf16(va[0][0] + va[1][0] + va[2][0] + va[3][0], va[0][1] + va[1][1] + va[2][1] + va[3][1]));
      uint32_t b1 = movm(pack_bf16(va[0][2] + va[1][2] + va[2][2] + va[3][2], va[0][3] + va[1][3] + va[2][3] + va[3][3]));
      sts32(vb + g * 128 + t * 4 + (((warp * 2) ^ g) * 16), b0); sts32(vb + g * 128 + t * 4 + (((warp * 2 + 1) ^ g) * 16), b1);
      uint32_t* gp = (uint32_t*)(g_vm + ((size_t)s * 8 + g) * HD_ + j0 + warp * 16 + t * 2); gp[0] = b0; gp[4] = b1;
      asm volatile("bar.arrive 7, 256;" ::: "memory");
    } else {
      phase1();
      BAR_ALL();
      if (warp == 7 && lane == 0 && s > 0) { __threadfence(); atomicAdd(&g_cnt[96 + s - 1], 1); }
      if (warp < 7 && s < NSEG - 1) {
        const int mt = warp - 4;
        const uint32_t sc_l = mapa_v(sb + CH_SC + (r & 1) * 1792, r), sc_r = mapa_v(sb + CH_SC + (r & 1) * 1792, r ^ 1), bs_l = mapa_v(bs, r), bs_r = mapa_v(bs, r ^ 1);
        float sa[4][4] = {};
#pragma unroll
        for (int kp = 0; kp < 2; kp++) {
          uint32_t b[4], a0[4], a1[4];
          ldsm4(b, sb + CH_Q + l7 * 128 + (((kp * 4 + mi) ^ l7) * 16));
          int row = mt * 16 + (mi & 1) * 8 + l7;
          ldsm4(a0, kb + row * 128 + (((kp * 4 + (mi >> 1)) ^ l7) * 16));
          ldsm4(a1, kb + row * 128 + (((kp * 4 + 2 + (mi >> 1)) ^ l7) * 16));
          mma16816(sa[2 * kp], a0, b[0], b[1]); mma16816(sa[2 * kp + 1], a1, b[2], b[3]);
        }
        asm volatile("bar.arrive 6, 224;" :: "f"(sa[0][0]), "f"(sa[1][0]), "f"(sa[2][0]), "f"(sa[3][0]) : "memory");
#pragma unroll
        for (int e = 0; e < 4; e++) {
          uint32_t off = ((2 * t + (e & 1)) * 56 + mt * 16 + (e >> 1) * 8 + g) * 4, v = __float_as_uint((sa[0][e] + sa[1][e]) + (sa[2][e] + sa[3][e]));
          if (mt < 2 || e < 2) { st_async1(sc_r + off, v, bs_r); st_async1(sc_l + off, v, bs_l); }
        }
        CP(5);
      }
      if (s < NSEG - 1) {
        prefetch_kv(s + 1, tid);
        const int w3 = warp & 3;
        uint32_t vt[3][4];
#pragma unroll
        for (int kk = 1; kk < 3; kk++) { int row = kk * 16 + (mi >> 1) * 8 + l7; ldsm4t(vt[kk], vb + row * 128 + (((w3 * 2 + (mi & 1)) ^ l7) * 16)); }
        mbar_wait_b(bs, par);
        CP(7);
        float z[10]; float mx = -INFINITY;
        const float scl = 0.08838834764831845f * 1.4426950408889634f;
#pragma unroll
        for (int i = 0; i < 5; i++) {
          float2 u0, u1; uint32_t a = sb + CH_SC + (g * 56 + i * 8 + 2 * t) * 4;
          asm volatile("ld.shared.v2.f32 {%0,%1}, [%2];" : "=f"(u0.x), "=f"(u0.y) : "r"(a) : "memory");
          asm volatile("ld.shared.v2.f32 {%0,%1}, [%2];" : "=f"(u1.x), "=f"(u1.y) : "r"(a + 1792) : "memory");
          z[2 * i] = (u0.x + u1.x) * scl; z[2 * i + 1] = (u0.y + u1.y) * scl;
        }
        mx = fmaxf(fmaxf(fmaxf(z[0], z[1]), fmaxf(z[2], z[3])), fmaxf(fmaxf(fmaxf(z[4], z[5]), fmaxf(z[6], z[7])), fmaxf(z[8], z[9])));
        mx = fmaxf(mx, __shfl_xor_sync(~0u, mx, 1)); mx = fmaxf(mx, __shfl_xor_sync(~0u, mx, 2));
        uint32_t pb[5];
#pragma unroll
        for (int i = 0; i < 5; i++) pb[i] = pack_bf16(exp2f(z[2 * i] - mx), exp2f(z[2 * i + 1] - mx));
        const uint32_t ones[4] = {0x3F803F80u, 0x3F803F80u, 0x3F803F80u, 0x3F803F80u};
        float o0[4] = {}, o1[4] = {}, o2[4] = {}, s0[4] = {}, s1[4] = {}, s2[4] = {};
        mma16816(s0, ones, pb[0], pb[1]);
        mma16816(o1, vt[1], pb[2], pb[3]); mma16816(s1, ones, pb[2], pb[3]);
        mma16816(o2, vt[2], pb[4], 0u); mma16816(s2, ones, pb[4], 0u);
        asm volatile("bar.sync 7, 256;" ::: "memory");
        ldsm4t(vt[0], vb + ((mi >> 1) * 8 + l7) * 128 + (((w3 * 2 + (mi & 1)) ^ l7) * 16));
        mma16816(o0, vt[0], pb[0], pb[1]);
        const float i0 = __fdividef(1.f, s0[0] + s1[0] + s2[0]), i1 = __fdividef(1.f, s0[1] + s1[1] + s2[1]);
        uint32_t f0 = movm(pack_bf16((o0[0] + o1[0] + o2[0]) * i0, (o0[1] + o1[1] + o2[1]) * i1));
        uint32_t f1 = movm(pack_bf16((o0[2] + o1[2] + o2[2]) * i0, (o0[3] + o1[3] + o2[3]) * i1));
        const int ks = r * 4 + w3;
        const uint32_t off = CH_OF + ks * 256 + (t >> 1) * 128 + g * 16 + (t & 1) * 8;
        const uint32_t cl0 = mapa_v(sb, 0), clstep = mapa_v(sb, 1) - cl0;
#pragma unroll
        for (int d = 0; d < 8; d++) st_async2(cl0 + d * clstep + off, f0, f1, cl0 + d * clstep + CH_BAR + 16);
      } else asm volatile("bar.sync 7, 256;" ::: "memory");
    }
    if (s == NSEG - 1) break;
    CP(8);
    uint32_t wo[16][4];
#pragma unroll
    for (int i = 0; i < 16; i++) { uint4 v = lds128(sb + CH_WO + 8192 + (warp * 16 + i) * 512 + lane * 16); wo[i][0] = v.x; wo[i][1] = v.y; wo[i][2] = v.z; wo[i][3] = v.w; }
    mbar_wait_b(bo, par);
    CP(9);
    const uint32_t tag = ((s >> 1) + 1) & 1;
    float* pbase = g_part + (size_t)par * 8 * 5120 + lane * 4;
    auto put = [&](int slot, const float (&a)[4]) {
      asm volatile("st.relaxed.gpu.global.v4.b32 [%0], {%1,%2,%3,%4};" ::"l"(pbase + c * 5120 + slot * 128), "r"((__float_as_uint(a[0]) & ~1u) | tag),
                   "r"((__float_as_uint(a[1]) & ~1u) | tag), "r"((__float_as_uint(a[2]) & ~1u) | tag), "r"((__float_as_uint(a[3]) & ~1u) | tag) : "memory");
    };
    {
      float acc[4][4];
      asm volatile("wgmma.fence.sync.aligned;" ::: "memory");
      const uint32_t dof = dsb + ((CH_OF >> 4) + wgi * 256);
#pragma unroll
      for (int i = 0; i < 16; i++) { if (i < 4) wg_rs<0>(acc[i & 3], wo[i], dof + i * 16); else wg_rs<1>(acc[i & 3], wo[i], dof + i * 16); }
      wg_wait(acc);
#pragma unroll
      for (int e = 0; e < 4; e++) acc[0][e] = (acc[0][e] + acc[1][e]) + (acc[2][e] + acc[3][e]);
      CP(10);
      const int w3 = warp & 3;
      if (wgi) {
        sts128f(sb + CH_R2 + w3 * 512 + lane * 16, acc[0]);
        asm volatile("bar.arrive %0, 64;" ::"r"(1 + w3) : "memory");
        if (w3 < 2) {
          float ex[2][4] = {};
#pragma unroll
          for (int i = 0; i < 8; i += 2) {
            uint32_t b[4]; ldsm4(b, sb + CH_OF + ((r & 1) * 16 + w3 * 8 + i) * 256 + mi * 128 + l7 * 16);
            uint4 v0 = lds128(sb + CH_WO + (w3 * 8 + i) * 512 + lane * 16), v1 = lds128(sb + CH_WO + (w3 * 8 + i + 1) * 512 + lane * 16);
            uint32_t a0[4] = {v0.x, v0.y, v0.z, v0.w}, a1[4] = {v1.x, v1.y, v1.z, v1.w};
            mma16816(ex[0], a0, b[0], b[1]); mma16816(ex[1], a1, b[2], b[3]);
          }
#pragma unroll
          for (int e = 0; e < 4; e++) ex[0][e] += ex[1][e];
          if (w3 == 1) { sts128f(sb + CH_R2 + 4 * 512 + lane * 16, ex[0]); asm volatile("bar.arrive 5, 64;" ::: "memory"); }
          else {
            asm volatile("bar.sync 5, 64;" ::: "memory");
            uint4 v = lds128(sb + CH_R2 + 4 * 512 + lane * 16);
            ex[0][0] += __uint_as_float(v.x); ex[0][1] += __uint_as_float(v.y); ex[0][2] += __uint_as_float(v.z); ex[0][3] += __uint_as_float(v.w);
            put(32 + r, ex[0]);
          }
        }
      } else {
        asm volatile("bar.sync %0, 64;" ::"r"(1 + w3) : "memory");
        uint4 v = lds128(sb + CH_R2 + w3 * 512 + lane * 16);
        acc[0][0] += __uint_as_float(v.x); acc[0][1] += __uint_as_float(v.y); acc[0][2] += __uint_as_float(v.z); acc[0][3] += __uint_as_float(v.w);
        put(r * 4 + w3, acc[0]);
      }
    }
    CP(11);
    if (warp < 4 || warp == 6) { long long t0 = clock64(); while (clock64() - t0 < POLL_DELAY) {} }
    if (warp < 4) {
      const float* pb = pbase + (r * 4 + warp) * 128;
      uint4 v[8]; int n = 0; uint32_t need = 0xFF;
#pragma unroll
      for (int i = 0; i < 8; i++) v[i] = make_uint4(0, 0, 0, 0);
      do {
#pragma unroll
        for (int i = 0; i < 8; i++)
          asm volatile("{\n.reg .pred p;\nsetp.ne.b32 p, %5, 0;\n@p ld.relaxed.gpu.global.v4.b32 {%0,%1,%2,%3}, [%4];\n}" : "+r"(v[i].x), "+r"(v[i].y), "+r"(v[i].z), "+r"(v[i].w) : "l"(pb + i * 5120), "r"(need & (1u << i)) : "memory");
#pragma unroll
        for (int i = 0; i < 8; i++) {
          bool ok = ((v[i].x & v[i].y & v[i].z & v[i].w & 1u) == tag) && (((v[i].x | v[i].y | v[i].z | v[i].w) & 1u) == tag);
          if (__all_sync(~0u, ok)) need &= ~(1u << i);
        }
      } while (need && ++n < (1 << 18));
      float m[4] = {};
#pragma unroll
      for (int i = 0; i < 8; i++) { m[0] += __uint_as_float(v[i].x); m[1] += __uint_as_float(v[i].y); m[2] += __uint_as_float(v[i].z); m[3] += __uint_as_float(v[i].w); }
      __syncwarp();
      CP(12);
      uint32_t b0 = movm(pack_bf16(m[0], m[1])), b1 = movm(pack_bf16(m[2], m[3]));
      const uint32_t off = CH_MEM + (r * 4 + warp) * 256 + g * 16 + t * 4;
      const uint32_t cl0 = mapa_v(sb, 0), clstep = mapa_v(sb, 1) - cl0;
#pragma unroll
      for (int d = 0; d < 8; d++) { st_async1(cl0 + d * clstep + off, b0, cl0 + d * clstep + CH_BAR); st_async1(cl0 + d * clstep + off + 128, b1, cl0 + d * clstep + CH_BAR); }
    } else if (warp == 6) {
      const float* pb = pbase - lane * 4 + (32 + (r & ~1u)) * 128 + lane * 4 + (r & 1) * 2;
      uint2 v[16]; int n = 0; uint32_t need = 0xFF;
#pragma unroll
      for (int i = 0; i < 16; i++) v[i] = make_uint2(0, 0);
      do {
#pragma unroll
        for (int i = 0; i < 16; i++)
          asm volatile("{\n.reg .pred p;\nsetp.ne.b32 p, %3, 0;\n@p ld.relaxed.gpu.global.v2.b32 {%0,%1}, [%2];\n}" : "+r"(v[i].x), "+r"(v[i].y) : "l"(pb + (i >> 1) * 5120 + (i & 1) * 128), "r"(need & (1u << (i >> 1))) : "memory");
#pragma unroll
        for (int i = 0; i < 16; i += 2) {
          bool ok = ((v[i].x & v[i].y & v[i + 1].x & v[i + 1].y & 1u) == tag) && (((v[i].x | v[i].y | v[i + 1].x | v[i + 1].y) & 1u) == tag);
          if (__all_sync(~0u, ok)) need &= ~(1u << (i >> 1));
        }
      } while (need && ++n < (1 << 18));
      float m0 = 0.f, m1 = 0.f;
#pragma unroll
      for (int i = 0; i < 16; i++) { m0 += __uint_as_float(v[i].x); m1 += __uint_as_float(v[i].y); }
      __syncwarp();
      uint32_t b0 = movm(pack_bf16(m0, m1));
      const uint32_t off = CH_MEM + (32 + (r >> 1)) * 256 + (r & 1) * 128 + g * 16 + t * 4;
      const uint32_t cl0 = mapa_v(sb, 0), clstep = mapa_v(sb, 1) - cl0;
#pragma unroll
      for (int d = 0; d < 8; d++) st_async1(cl0 + d * clstep + off, b0, cl0 + d * clstep + CH_BAR);
    }
  }
  BAR_ALL();
  if (tid == 0) { __threadfence(); atomicAdd(&g_cnt[96 + NSEG - 1], 1); }
  if (blockIdx.x == 0 && tid == 0) PT(8);
  cluster_sync();
}
typedef CUresult (*EncodeFn)(CUtensorMap*, CUtensorMapDataType, cuuint32_t, void*, const cuuint64_t*, const cuuint64_t*, const cuuint32_t*, const cuuint32_t*,
                             CUtensorMapInterleave, CUtensorMapSwizzle, CUtensorMapL2promotion, CUtensorMapFloatOOBfill);
static EncodeFn g_enc;
static void mkmap(CUtensorMap* m, const void* ptr, int rows, int cols, int boxc, int boxr) {
  cuuint64_t dims[2] = {(cuuint64_t)cols, (cuuint64_t)rows}, strides[1] = {(cuuint64_t)cols * 2};
  cuuint32_t box[2] = {(cuuint32_t)boxc, (cuuint32_t)boxr}, es[2] = {1, 1};
  g_enc(m, CU_TENSOR_MAP_DATA_TYPE_BFLOAT16, 2, (void*)ptr, dims, strides, box, es, CU_TENSOR_MAP_INTERLEAVE_NONE, CU_TENSOR_MAP_SWIZZLE_128B,
        CU_TENSOR_MAP_L2_PROMOTION_L2_256B, CU_TENSOR_MAP_FLOAT_OOB_FILL_NONE);
}
#define URG 60.0
#define CHDT 3.7
constexpr double CH_T0 = 24.0, CH_DT = CHDT;
static inline uint16_t mkjob(int type, int m, int n) { return (uint16_t)(type << 12 | m << 6 | n); }
static void schedule_side(GemmParams& p, const uint16_t* base, int nb, int ncl) {
  static const double cost[8] = {7.6, 7.6, 7.6, 19.5, 56.0, 33.0, 12.5, 7.0};
  double t[66]; int cnt[66] = {};
  for (int c = 0; c < 66; c++) t[c] = 9.0;
  p.stride = 960 / ncl;
  for (int i = 0; i < 960; i++) p.job[i] = 0xFFFF;
  double g2_end = 0, q_end[8] = {}, g3_end[8] = {}, at_end[8] = {}; int qn[8] = {}, g3n[8] = {}, atn[8] = {};
  int bi = 0, ai = 0, gi = 0;
  while (bi < nb || ai < 96 || gi < 60) {
    int b = -1;
    for (int c = 0; c < ncl; c++) if (cnt[c] < p.stride && (b < 0 || t[c] < t[b] || (t[c] == t[b] && cnt[c] < cnt[b]))) b = c;
    const double inf = 1e30;
    int am = ai >> 4, gm = gi < 12 ? gi / 3 : 4 + (gi - 12) / 24;
    double ra = ai < 96 && qn[am] == 16 ? (q_end[am] > CH_T0 + CH_DT * (am * 8 + ((ai & 15) >> 1) + 2) ? q_end[am] : CH_T0 + CH_DT * (am * 8 + ((ai & 15) >> 1) + 2)) : inf;
    double rg = gi < 60 && atn[gm] == 16 && g3n[gm] == 3 ? (at_end[gm] > g3_end[gm] - 30 ? at_end[gm] : g3_end[gm] - 30) : inf;
    bool urgent = bi < nb && (base[bi] >> 12) >= 1 && (base[bi] >> 12) <= 2 && CH_T0 + CH_DT * 8 * ((base[bi] >> 6) & 63) - t[b] < URG;
    uint16_t job; double start = t[b];
    if (urgent) job = base[bi++];
    else if (rg <= t[b] || (bi >= nb && rg < inf && (rg <= ra || (gi < 60 && ai >= 96)))) { job = gi < 12 ? mkjob(5, gm, gi % 3) : mkjob(7, gm, (gi - 12) % 24); gi++; if (rg > start) start = rg; }
    else if (ra <= t[b] || bi >= nb) { job = mkjob(6, am, ai & 15); ai++; if (ra > start) start = ra; }
    else job = base[bi++];
    int ty = job >> 12, m = (job >> 6) & 63;
    if (ty == 4 && start < g2_end) start = g2_end;
    t[b] = start + cost[ty];
    if (ty == 3 && t[b] > g2_end) g2_end = t[b];
    if (ty == 0) { qn[m]++; if (t[b] > q_end[m]) q_end[m] = t[b]; }
    if (ty == 4) { g3n[m]++; if (t[b] > g3_end[m]) g3_end[m] = t[b]; }
    if (ty == 6) { atn[m]++; if (t[b] > at_end[m]) at_end[m] = t[b]; }
    p.job[b * p.stride + cnt[b]++] = job;
  }
}
template <class... A>
static void launch(void (*k)(A...), int grid, int block, int smem, int cluster, bool pdl, A... a) {
  cudaLaunchConfig_t c = {};
  c.gridDim = grid; c.blockDim = block; c.dynamicSmemBytes = smem; c.stream = cudaStreamPerThread;
  cudaLaunchAttribute at[2]; int n = 0;
  if (cluster > 1) { at[n].id = cudaLaunchAttributeClusterDimension; at[n].val.clusterDim.x = cluster; at[n].val.clusterDim.y = 1; at[n].val.clusterDim.z = 1; n++; }
  if (pdl) { at[n].id = cudaLaunchAttributeProgrammaticStreamSerialization; at[n].val.programmaticStreamSerializationAllowed = 1; n++; }
  c.attrs = at; c.numAttrs = n;
  cudaLaunchKernelEx(&c, k, a...);
}

extern "C" void kernel_launch(void* const* d_in, const int* in_sizes, int n_in, void* d_out, int out_size) {
  const bf16 *x = (const bf16*)d_in[0], *mem0 = (const bf16*)d_in[1], *Wq = (const bf16*)d_in[2], *Wk = (const bf16*)d_in[3], *Wv = (const bf16*)d_in[4],
             *Wo = (const bf16*)d_in[5], *w1 = (const bf16*)d_in[8], *b1 = (const bf16*)d_in[9], *w2 = (const bf16*)d_in[10], *b2 = (const bf16*)d_in[11];
  static bool init = false;
  static GemmParams side, post;
  if (!init) {
    init = true;
    cudaDriverEntryPointQueryResult qr;
    cudaGetDriverEntryPoint("cuTensorMapEncodeTiled", (void**)&g_enc, cudaEnableDefault, &qr);
    void *xn, *h2, *o, *ut;
    cudaGetSymbolAddress(&xn, g_xn); cudaGetSymbolAddress(&h2, g_h2); cudaGetSymbolAddress(&o, g_o); cudaGetSymbolAddress(&ut, g_ut);
    GemmParams b = {};
    mkmap(&b.mA[0], xn, S_, D_, 64, 128); mkmap(&b.mA[1], w1, S_, F_, 64, 64); mkmap(&b.mA[2], w2, F_, S_, 64, 64); mkmap(&b.mA[3], o, S_, HD_, 64, 128);
    mkmap(&b.mB[0], Wq, D_, HD_, 64, 32); mkmap(&b.mB[1], Wk, D_, HD_, 64, 32); mkmap(&b.mB[2], Wv, D_, HD_, 64, 32);
    mkmap(&b.mB[3], h2, S_, D_, 64, 32); mkmap(&b.mB[4], ut, F_, D_, 64, 32); mkmap(&b.mB[5], Wo, HD_, D_, 64, 32);
    b.x = x; b.b1 = b1; b.b2 = b2; b.out = (bf16*)d_out;
    side = b; post = b; side.kid = 1; post.kid = 2;
    static uint16_t jl[1024]; int n = 0;
    auto kv = [&](int m) { for (int j = 0; j < 16; j++) { jl[n++] = mkjob(1, m, j); jl[n++] = mkjob(2, m, j); } };
    auto qq = [&](int m) { for (int j = 0; j < 16; j++) jl[n++] = mkjob(0, m, j); };
    kv(0); kv(1);
    for (int m = 0; m < 18; m++) for (int j = 0; j < 3; j++) jl[n++] = mkjob(3, m, j);
    kv(2); qq(0); kv(3); qq(1);
    for (int m = 0; m < 8; m++) for (int j = 0; j < 3; j++) jl[n++] = mkjob(4, m, j);
    for (int m = 4; m < 8; m++) { kv(m); qq(m - 2); }
    qq(6); qq(7);
    schedule_side(side, jl, n, 34);
    side.wait_at_end = 0;
    post.stride = 2;
    for (int i = 0; i < 960; i++) post.job[i] = 0xFFFF;
    for (int i = 0; i < 48; i++) {
      if (i < 32) { post.job[i * 2] = mkjob(6, 6 + (i >> 4), i & 15); post.job[i * 2 + 1] = mkjob(7, 6 + i / 24, i % 24); }
      else post.job[i * 2] = mkjob(7, 6 + i / 24, i % 24);
    }
    cudaFuncSetAttribute(gemm_kernel, cudaFuncAttributeMaxDynamicSharedMemorySize, GEMM_SMEM);
    cudaFuncSetAttribute(chain_kernel, cudaFuncAttributeMaxDynamicSharedMemorySize, CHAIN_SMEM);
  }
  launch(ln_kernel, 256, 256, 0, 1, false, x);
  launch(chain_kernel, 64, 256, CHAIN_SMEM, 8, false, mem0, Wq, Wk, Wv, Wo);
  launch(gemm_kernel, 68, 384, GEMM_SMEM, 2, true, side);
  launch(gemm_kernel, 96, 384, GEMM_SMEM, 2, true, post);
}
```

```cpp
#include <cuda_runtime.h>
#include <cuda_bf16.h>
#include <cuda.h>
#include <stdint.h>

typedef __nv_bfloat16 bf16;
constexpr int S_ = 2048, D_ = 576, HD_ = 4096, F_ = 4608, NSEG = 64;

__device__ bf16 g_xn[S_ * D_];
__device__ bf16 g_h2[S_ * D_];
__device__ bf16 g_q[S_ * HD_];
__device__ bf16 g_k[S_ * HD_];
__device__ bf16 g_v[S_ * HD_];
__device__ bf16 g_o[S_ * HD_];
__device__ bf16 g_km[NSEG * 8 * HD_];
__device__ bf16 g_vm[NSEG * 8 * HD_];
__device__ bf16 g_ut[F_ * D_];
__device__ float g_yb[S_ * D_];
__device__ float g_pk[8 * 512 * D_];
__device__ float g_part[2 * 8 * 8 * 5 * 32 * 4];
__device__ unsigned int g_cnt[192];

#define PT(i)
#define PC(i)
__device__ __forceinline__ uint32_t smem_u32(const void* p) { return (uint32_t)__cvta_generic_to_shared(p); }
__device__ __forceinline__ void mbar_init(uint32_t b, uint32_t c) { asm volatile("mbarrier.init.shared::cta.b64 [%0], %1;" ::"r"(b), "r"(c)); }
__device__ __forceinline__ void mbar_expect(uint32_t b, uint32_t bytes) { asm volatile("mbarrier.arrive.expect_tx.shared::cta.b64 _, [%0], %1;" ::"r"(b), "r"(bytes) : "memory"); }
__device__ __forceinline__ void mbar_wait(uint32_t b, uint32_t parity) {
  uint32_t ok;
  do { asm volatile("{\n.reg .pred p;\nmbarrier.try_wait.parity.shared::cta.b64 p, [%1], %2;\nselp.u32 %0, 1, 0, p;\n}" : "=r"(ok) : "r"(b), "r"(parity) : "memory"); } while (!ok);
}
__device__ __forceinline__ void mbar_wait_cl(uint32_t b, uint32_t parity) {
  uint32_t ok;
  do { asm volatile("{\n.reg .pred p;\nmbarrier.try_wait.parity.shared::cta.b64 p, [%1], %2;\nselp.u32 %0, 1, 0, p;\n}" : "=r"(ok) : "r"(b), "r"(parity) : "memory"); } while (!ok);
}
__device__ __forceinline__ uint32_t mapa(uint32_t a, uint32_t r) { uint32_t o; asm("mapa.shared::cluster.u32 %0, %1, %2;" : "=r"(o) : "r"(a), "r"(r)); return o; }
__device__ __forceinline__ void mbar_arrive_remote(uint32_t remote_b) { asm volatile("mbarrier.arrive.shared::cluster.b64 _, [%0];" ::"r"(remote_b) : "memory"); }
__device__ __forceinline__ uint32_t cluster_rank() { uint32_t r; asm("mov.u32 %0, %%cluster_ctarank;" : "=r"(r)); return r; }
__device__ __forceinline__ void cluster_sync() { asm volatile("barrier.cluster.arrive.release.aligned;\nbarrier.cluster.wait.acquire.aligned;" ::: "memory"); }
__device__ __forceinline__ void tma2d(uint32_t dst, const CUtensorMap* m, int c0, int c1, uint32_t bar) {
  asm volatile("cp.async.bulk.tensor.2d.shared::cluster.global.mbarrier::complete_tx::bytes [%0], [%1, {%3, %4}], [%2];"
               ::"r"(dst), "l"(m), "r"(bar), "r"(c0), "r"(c1) : "memory");
}
__device__ __forceinline__ void tma2d_mc(uint32_t dst, const CUtensorMap* m, int c0, int c1, uint32_t bar, uint16_t mask) {
  asm volatile("cp.async.bulk.tensor.2d.shared::cluster.global.mbarrier::complete_tx::bytes.multicast::cluster [%0], [%1, {%3, %4}], [%2], %5;"
               ::"r"(dst), "l"(m), "r"(bar), "r"(c0), "r"(c1), "h"(mask) : "memory");
}
__device__ __forceinline__ uint32_t pack_bf16(float a, float b) { __nv_bfloat162 t = __floats2bfloat162_rn(a, b); return *(uint32_t*)&t; }
__device__ __forceinline__ float2 unpack_bf16(uint32_t u) { return __bfloat1622float2(*(__nv_bfloat162*)&u); }
__device__ __forceinline__ void mma16816(float (&c)[4], const uint32_t (&a)[4], uint32_t b0, uint32_t b1) {
  asm volatile("mma.sync.aligned.m16n8k16.row.col.f32.bf16.bf16.f32 {%0,%1,%2,%3},{%4,%5,%6,%7},{%8,%9},{%0,%1,%2,%3};"
               : "+f"(c[0]), "+f"(c[1]), "+f"(c[2]), "+f"(c[3]) : "r"(a[0]), "r"(a[1]), "r"(a[2]), "r"(a[3]), "r"(b0), "r"(b1));
}
__device__ __forceinline__ void ldsm4(uint32_t (&r)[4], uint32_t a) { asm volatile("ldmatrix.sync.aligned.m8n8.x4.shared.b16 {%0,%1,%2,%3},[%4];" : "=r"(r[0]), "=r"(r[1]), "=r"(r[2]), "=r"(r[3]) : "r"(a) : "memory"); }
__device__ __forceinline__ void ldsm4t(uint32_t (&r)[4], uint32_t a) { asm volatile("ldmatrix.sync.aligned.m8n8.x4.trans.shared.b16 {%0,%1,%2,%3},[%4];" : "=r"(r[0]), "=r"(r[1]), "=r"(r[2]), "=r"(r[3]) : "r"(a) : "memory"); }
__device__ __forceinline__ uint32_t movm(uint32_t a) { uint32_t o; asm volatile("movmatrix.sync.aligned.m8n8.trans.b16 %0, %1;" : "=r"(o) : "r"(a)); return o; }
__device__ __forceinline__ void cp16(uint32_t dst, const void* src) { asm volatile("cp.async.cg.shared.global [%0], [%1], 16;" ::"r"(dst), "l"(src) : "memory"); }
__device__ __forceinline__ void pdl_wait() { asm volatile("griddepcontrol.wait;" ::: "memory"); }
__device__ __forceinline__ void pdl_launch() { asm volatile("griddepcontrol.launch_dependents;" ::: "memory"); }

__device__ __forceinline__ void wait_cnt(const unsigned int* c, unsigned int target) {
  uint32_t v; int n = 0;
  do { asm volatile("ld.acquire.gpu.global.u32 %0, [%1];" : "=r"(v) : "l"(c) : "memory"); if (v >= target) break; __nanosleep(64); } while (++n < (1 << 22));
}
__global__ void __launch_bounds__(256) ln_kernel(const bf16* __restrict__ x) {
  int row = blockIdx.x * 8 + (threadIdx.x >> 5), lane = threadIdx.x & 31;
  if (blockIdx.x == 0 && threadIdx.x < 192) { g_cnt[threadIdx.x] = 0; if (threadIdx.x == 0) PT(0); }
  for (int i = blockIdx.x * 256 + threadIdx.x; i < 2 * 64 * 640; i += 256 * 256) g_part[i] = 0.f;
  const uint32_t* xr = (const uint32_t*)(x + (size_t)row * D_);
  float v[18]; float s = 0.f;
#pragma unroll
  for (int i = 0; i < 9; i++) { float2 f = unpack_bf16(xr[lane + 32 * i]); v[2 * i] = f.x; v[2 * i + 1] = f.y; s += f.x + f.y; }
#pragma unroll
  for (int pass = 0; pass < 2; pass++) {
#pragma unroll
    for (int o = 16; o; o >>= 1) s += __shfl_xor_sync(~0u, s, o);
    float m = s * (1.f / D_), q = 0.f;
#pragma unroll
    for (int i = 0; i < 18; i++) { v[i] -= m; q += v[i] * v[i]; }
#pragma unroll
    for (int o = 16; o; o >>= 1) q += __shfl_xor_sync(~0u, q, o);
    float r = 1.f / sqrtf(q * (1.f / D_) + 1e-5f);
    uint32_t* dst = (uint32_t*)((pass == 0 ? g_xn : g_h2) + (size_t)row * D_);
    s = 0.f;
#pragma unroll
    for (int i = 0; i < 9; i++) {
      uint32_t p = pack_bf16(v[2 * i] * r, v[2 * i + 1] * r);
      dst[lane + 32 * i] = p;
      float2 f = unpack_bf16(p); v[2 * i] = f.x; v[2 * i + 1] = f.y; s += f.x + f.y;
    }
  }
}

template<int TA> __device__ __forceinline__ void wgmma_n256(float (&d)[128], uint64_t da, uint64_t db, int sc) {
  asm volatile("{\n.reg .pred p;\nsetp.ne.b32 p, %130, 0;\n"
    "wgmma.mma_async.sync.aligned.m64n256k16.f32.bf16.bf16 {%0, %1, %2, %3, %4, %5, %6, %7, %8, %9, %10, %11, %12, %13, %14, %15, %16, %17, %18, %19, %20, %21, %22, %23, %24, %25, %26, %27, %28, %29, %30, %31, %32, %33, %34, %35, %36, %37, %38, %39, %40, %41, %42, %43, %44, %45, %46, %47, %48, %49, %50, %51, %52, %53, %54, %55, %56, %57, %58, %59, %60, %61, %62, %63, %64, %65, %66, %67, %68, %69, %70, %71, %72, %73, %74, %75, %76, %77, %78, %79, %80, %81, %82, %83, %84, %85, %86, %87, %88, %89, %90, %91, %92, %93, %94, %95, %96, %97, %98, %99, %100, %101, %102, %103, %104, %105, %106, %107, %108, %109, %110, %111, %112, %113, %114, %115, %116, %117, %118, %119, %120, %121, %122, %123, %124, %125, %126, %127}, %128, %129, p, 1, 1, %131, 1;\n}\n"
    : "+f"(d[0]), "+f"(d[1]), "+f"(d[2]), "+f"(d[3]), "+f"(d[4]), "+f"(d[5]), "+f"(d[6]), "+f"(d[7]), "+f"(d[8]), "+f"(d[9]), "+f"(d[10]), "+f"(d[11]), "+f"(d[12]), "+f"(d[13]), "+f"(d[14]), "+f"(d[15]), "+f"(d[16]), "+f"(d[17]), "+f"(d[18]), "+f"(d[19]), "+f"(d[20]), "+f"(d[21]), "+f"(d[22]), "+f"(d[23]), "+f"(d[24]), "+f"(d[25]), "+f"(d[26]), "+f"(d[27]), "+f"(d[28]), "+f"(d[29]), "+f"(d[30]), "+f"(d[31]), "+f"(d[32]), "+f"(d[33]), "+f"(d[34]), "+f"(d[35]), "+f"(d[36]), "+f"(d[37]), "+f"(d[38]), "+f"(d[39]), "+f"(d[40]), "+f"(d[41]), "+f"(d[42]), "+f"(d[43]), "+f"(d[44]), "+f"(d[45]), "+f"(d[46]), "+f"(d[47]), "+f"(d[48]), "+f"(d[49]), "+f"(d[50]), "+f"(d[51]), "+f"(d[52]), "+f"(d[53]), "+f"(d[54]), "+f"(d[55]), "+f"(d[56]), "+f"(d[57]), "+f"(d[58]), "+f"(d[59]), "+f"(d[60]), "+f"(d[61]), "+f"(d[62]), "+f"(d[63]), "+f"(d[64]), "+f"(d[65]), "+f"(d[66]), "+f"(d[67]), "+f"(d[68]), "+f"(d[69]), "+f"(d[70]), "+f"(d[71]), "+f"(d[72]), "+f"(d[73]), "+f"(d[74]), "+f"(d[75]), "+f"(d[76]), "+f"(d[77]), "+f"(d[78]), "+f"(d[79]), "+f"(d[80]), "+f"(d[81]), "+f"(d[82]), "+f"(d[83]), "+f"(d[84]), "+f"(d[85]), "+f"(d[86]), "+f"(d[87]), "+f"(d[88]), "+f"(d[89]), "+f"(d[90]), "+f"(d[91]), "+f"(d[92]), "+f"(d[93]), "+f"(d[94]), "+f"(d[95]), "+f"(d[96]), "+f"(d[97]), "+f"(d[98]), "+f"(d[99]), "+f"(d[100]), "+f"(d[101]), "+f"(d[102]), "+f"(d[103]), "+f"(d[104]), "+f"(d[105]), "+f"(d[106]), "+f"(d[107]), "+f"(d[108]), "+f"(d[109]), "+f"(d[110]), "+f"(d[111]), "+f"(d[112]), "+f"(d[113]), "+f"(d[114]), "+f"(d[115]), "+f"(d[116]), "+f"(d[117]), "+f"(d[118]), "+f"(d[119]), "+f"(d[120]), "+f"(d[121]), "+f"(d[122]), "+f"(d[123]), "+f"(d[124]), "+f"(d[125]), "+f"(d[126]), "+f"(d[127])
    : "l"(da), "l"(db), "r"(sc), "n"(TA));
}

template<int TA> __device__ __forceinline__ void wgmma_n192(float (&d)[128], uint64_t da, uint64_t db, int sc) {
  asm volatile("{\n.reg .pred p;\nsetp.ne.b32 p, %98, 0;\n"
    "wgmma.mma_async.sync.aligned.m64n192k16.f32.bf16.bf16 {%0, %1, %2, %3, %4, %5, %6, %7, %8, %9, %10, %11, %12, %13, %14, %15, %16, %17, %18, %19, %20, %21, %22, %23, %24, %25, %26, %27, %28, %29, %30, %31, %32, %33, %34, %35, %36, %37, %38, %39, %40, %41, %42, %43, %44, %45, %46, %47, %48, %49, %50, %51, %52, %53, %54, %55, %56, %57, %58, %59, %60, %61, %62, %63, %64, %65, %66, %67, %68, %69, %70, %71, %72, %73, %74, %75, %76, %77, %78, %79, %80, %81, %82, %83, %84, %85, %86, %87, %88, %89, %90, %91, %92, %93, %94, %95}, %96, %97, p, 1, 1, %99, 1;\n}\n"
    : "+f"(d[0]), "+f"(d[1]), "+f"(d[2]), "+f"(d[3]), "+f"(d[4]), "+f"(d[5]), "+f"(d[6]), "+f"(d[7]), "+f"(d[8]), "+f"(d[9]), "+f"(d[10]), "+f"(d[11]), "+f"(d[12]), "+f"(d[13]), "+f"(d[14]), "+f"(d[15]), "+f"(d[16]), "+f"(d[17]), "+f"(d[18]), "+f"(d[19]), "+f"(d[20]), "+f"(d[21]), "+f"(d[22]), "+f"(d[23]), "+f"(d[24]), "+f"(d[25]), "+f"(d[26]), "+f"(d[27]), "+f"(d[28]), "+f"(d[29]), "+f"(d[30]), "+f"(d[31]), "+f"(d[32]), "+f"(d[33]), "+f"(d[34]), "+f"(d[35]), "+f"(d[36]), "+f"(d[37]), "+f"(d[38]), "+f"(d[39]), "+f"(d[40]), "+f"(d[41]), "+f"(d[42]), "+f"(d[43]), "+f"(d[44]), "+f"(d[45]), "+f"(d[46]), "+f"(d[47]), "+f"(d[48]), "+f"(d[49]), "+f"(d[50]), "+f"(d[51]), "+f"(d[52]), "+f"(d[53]), "+f"(d[54]), "+f"(d[55]), "+f"(d[56]), "+f"(d[57]), "+f"(d[58]), "+f"(d[59]), "+f"(d[60]), "+f"(d[61]), "+f"(d[62]), "+f"(d[63]), "+f"(d[64]), "+f"(d[65]), "+f"(d[66]), "+f"(d[67]), "+f"(d[68]), "+f"(d[69]), "+f"(d[70]), "+f"(d[71]), "+f"(d[72]), "+f"(d[73]), "+f"(d[74]), "+f"(d[75]), "+f"(d[76]), "+f"(d[77]), "+f"(d[78]), "+f"(d[79]), "+f"(d[80]), "+f"(d[81]), "+f"(d[82]), "+f"(d[83]), "+f"(d[84]), "+f"(d[85]), "+f"(d[86]), "+f"(d[87]), "+f"(d[88]), "+f"(d[89]), "+f"(d[90]), "+f"(d[91]), "+f"(d[92]), "+f"(d[93]), "+f"(d[94]), "+f"(d[95])
    : "l"(da), "l"(db), "r"(sc), "n"(TA));
}

struct GemmParams {
  CUtensorMap mA[4];
  CUtensorMap mB[6];
  const bf16* x; const bf16* b1; const bf16* b2; bf16* out;
  int stride, kid;
  int wait_at_end;
  uint16_t job[960];
};
constexpr int NSTAGE = 4, STAGE_BYTES = 49152;
constexpr int GEMM_SMEM = NSTAGE * STAGE_BYTES + 8 * 2048 + 256 + 1024;

__device__ __forceinline__ uint64_t mkdesc(uint32_t addr, uint32_t lbo, uint32_t sbo) {
  return (uint64_t)((addr & 0x3FFFF) >> 4) | ((uint64_t)(lbo >> 4) << 16) | ((uint64_t)(sbo >> 4) << 32) | (1ull << 62);
}
__device__ __forceinline__ float gelu_tanh(float u) {
  float z = 0.7978845608028654f * (u + 0.044715f * u * u * u);
  float e = __expf(2.f * z);
  float th = 1.f - __fdividef(2.f, e + 1.f);
  return 0.5f * u * (1.f + th);
}
template <int BN, int TA>
__device__ __forceinline__ void gemm_mainloop(float (&d)[128], int kiters, uint32_t sbase, uint32_t fullb, uint32_t emptyb_l, uint32_t emptyb_r,
                                              int wg, int& stage, uint32_t& phase, bool elect) {
  int prev = -1;
  for (int k = 0; k < kiters; k++) {
    mbar_wait(fullb + stage * 8, phase);
    uint32_t a = sbase + stage * STAGE_BYTES + wg * 8192, b = sbase + stage * STAGE_BYTES + 16384;
    asm volatile("wgmma.fence.sync.aligned;" ::: "memory");
#pragma unroll
    for (int kk = 0; kk < 4; kk++) {
      uint64_t da = TA ? mkdesc(a + kk * 2048, 8192, 1024) : mkdesc(a + kk * 32, 16, 1024);
      uint64_t db = mkdesc(b + kk * 2048, 8192, 1024);
      if constexpr (BN == 256) wgmma_n256<TA>(d, da, db, (k | kk) != 0); else wgmma_n192<TA>(d, da, db, (k | kk) != 0);
    }
    asm volatile("wgmma.commit_group.sync.aligned;" ::: "memory");
    asm volatile("wgmma.wait_group.sync.aligned 1;" ::: "memory");
    if (prev >= 0 && elect) { mbar_arrive_remote(emptyb_l + prev * 8); mbar_arrive_remote(emptyb_r + prev * 8); }
    prev = stage;
    if (++stage == NSTAGE) { stage = 0; phase ^= 1; }
  }
  asm volatile("wgmma.wait_group.sync.aligned 0;" ::: "memory");
  if (elect) { mbar_arrive_remote(emptyb_l + prev * 8); mbar_arrive_remote(emptyb_r + prev * 8); }
}
template <int BN, class F>
__device__ __forceinline__ void store_tile(const float (&d)[128], uint32_t stg, bf16* dst, int ld, int lane, F f) {
#pragma unroll
  for (int c = 0; c < BN / 64; c++) {
#pragma unroll
    for (int i = 0; i < 8; i += 2) {
      const int o = c * 32 + i * 4;
      uint32_t r0 = f(d[o], d[o + 1], 0, c * 64 + i * 8), r1 = f(d[o + 2], d[o + 3], 1, c * 64 + i * 8);
      uint32_t r2 = f(d[o + 4], d[o + 5], 0, c * 64 + i * 8 + 8), r3 = f(d[o + 6], d[o + 7], 1, c * 64 + i * 8 + 8);
      int m = lane >> 3, row = (m & 1) * 8 + (lane & 7), ch = (i + (m >> 1)) ^ (row & 7);
      asm volatile("stmatrix.sync.aligned.m8n8.x4.shared.b16 [%0], {%1,%2,%3,%4};" ::"r"(stg + row * 128 + ch * 16), "r"(r0), "r"(r1), "r"(r2), "r"(r3) : "memory");
    }
    __syncwarp();
#pragma unroll
    for (int j = 0; j < 4; j++) {
      int idx = lane + 32 * j, row = idx >> 3, ch = idx & 7;
      uint4 v;
      asm volatile("ld.shared.v4.u32 {%0,%1,%2,%3}, [%4];" : "=r"(v.x), "=r"(v.y), "=r"(v.z), "=r"(v.w) : "r"(stg + row * 128 + ((ch ^ (row & 7)) * 16)));
      *(uint4*)(dst + (size_t)row * ld + c * 64 + ch * 8) = v;
    }
    __syncwarp();
  }
}

__device__ __forceinline__ void attn_unit(int seg, int h, uint8_t* sm, int lane, const unsigned int* segflag) {
  const int g = lane >> 2, t = lane & 3;
  const uint32_t sv = smem_u32(sm);
  const size_t tok0 = (size_t)seg * 32;
  for (int i = 128 + lane; i < 40 * 16; i += 32) {
    int r = i >> 4, c = i & 15;
    cp16(sv + r * 256 + ((c ^ (r & 7)) * 16), g_v + (tok0 + r - 8) * HD_ + h * 128 + c * 8);
  }
  for (int i = lane; i < 8 * 16; i += 32) *(uint4*)(sm + 40 * 256 + i * 16) = make_uint4(0, 0, 0, 0);
  asm volatile("cp.async.commit_group;" ::: "memory");
  float s[2][5][4];
#pragma unroll
  for (int m = 0; m < 2; m++)
#pragma unroll
    for (int n = 0; n < 5; n++) { s[m][n][0] = s[m][n][1] = s[m][n][2] = s[m][n][3] = 0.f; }
#pragma unroll
  for (int j = 0; j < 4; j++) {
    uint4 qa[2][2], kb[5];
#pragma unroll
    for (int m = 0; m < 2; m++)
#pragma unroll
      for (int hh = 0; hh < 2; hh++) qa[m][hh] = *(const uint4*)(g_q + (tok0 + m * 16 + hh * 8 + g) * HD_ + h * 128 + j * 32 + t * 8);
#pragma unroll
    for (int n = 1; n < 5; n++) kb[n] = *(const uint4*)(g_k + (tok0 + (n - 1) * 8 + g) * HD_ + h * 128 + j * 32 + t * 8);
#pragma unroll
    for (int m = 0; m < 2; m++) {
      uint32_t a0[4] = {qa[m][0].x, qa[m][1].x, qa[m][0].y, qa[m][1].y}, a1[4] = {qa[m][0].z, qa[m][1].z, qa[m][0].w, qa[m][1].w};
#pragma unroll
      for (int n = 1; n < 5; n++) { mma16816(s[m][n], a0, kb[n].x, kb[n].y); mma16816(s[m][n], a1, kb[n].z, kb[n].w); }
    }
  }
  if (lane == 0) wait_cnt(segflag, 64);
  __syncwarp();
  for (int i = lane; i < 128; i += 32) {
    int r = i >> 4, c = i & 15;
    cp16(sv + r * 256 + ((c ^ (r & 7)) * 16), g_vm + ((size_t)seg * 8 + r) * HD_ + h * 128 + c * 8);
  }
  asm volatile("cp.async.commit_group;" ::: "memory");
  {
    uint4 km[4], qa[4][2][2];
#pragma unroll
    for (int j = 0; j < 4; j++) {
      km[j] = __ldcg((const uint4*)(g_km + ((size_t)seg * 8 + g) * HD_ + h * 128 + j * 32 + t * 8));
#pragma unroll
      for (int m = 0; m < 2; m++)
#pragma unroll
        for (int hh = 0; hh < 2; hh++) qa[j][m][hh] = *(const uint4*)(g_q + (tok0 + m * 16 + hh * 8 + g) * HD_ + h * 128 + j * 32 + t * 8);
    }
#pragma unroll
    for (int j = 0; j < 4; j++)
#pragma unroll
      for (int m = 0; m < 2; m++) {
        uint32_t a0[4] = {qa[j][m][0].x, qa[j][m][1].x, qa[j][m][0].y, qa[j][m][1].y}, a1[4] = {qa[j][m][0].z, qa[j][m][1].z, qa[j][m][0].w, qa[j][m][1].w};
        mma16816(s[m][0], a0, km[j].x, km[j].y); mma16816(s[m][0], a1, km[j].z, km[j].w);
      }
  }
  const float sc = 0.08838834764831845f * 1.4426950408889634f;
  uint32_t pa[2][3][4];
#pragma unroll
  for (int m = 0; m < 2; m++) {
    float inv[2];
#pragma unroll
    for (int hh = 0; hh < 2; hh++) {
      int qi = 8 + m * 16 + hh * 8 + g;
      float mx = -INFINITY;
#pragma unroll
      for (int n = 0; n < 5; n++)
#pragma unroll
        for (int e = 0; e < 2; e++) { float& z = s[m][n][hh * 2 + e]; z = (n * 8 + t * 2 + e <= qi) ? z * sc : -INFINITY; mx = fmaxf(mx, z); }
      mx = fmaxf(mx, __shfl_xor_sync(~0u, mx, 1)); mx = fmaxf(mx, __shfl_xor_sync(~0u, mx, 2));
      float sum = 0.f;
#pragma unroll
      for (int n = 0; n < 5; n++)
#pragma unroll
        for (int e = 0; e < 2; e++) { float& z = s[m][n][hh * 2 + e]; z = exp2f(z - mx); sum += z; }
      sum += __shfl_xor_sync(~0u, sum, 1); sum += __shfl_xor_sync(~0u, sum, 2);
      inv[hh] = 1.f / sum;
    }
#pragma unroll
    for (int kk = 0; kk < 3; kk++) {
      pa[m][kk][0] = pack_bf16(s[m][2 * kk][0] * inv[0], s[m][2 * kk][1] * inv[0]);
      pa[m][kk][1] = pack_bf16(s[m][2 * kk][2] * inv[1], s[m][2 * kk][3] * inv[1]);
      if (kk < 2) {
        pa[m][kk][2] = pack_bf16(s[m][2 * kk + 1][0] * inv[0], s[m][2 * kk + 1][1] * inv[0]);
        pa[m][kk][3] = pack_bf16(s[m][2 * kk + 1][2] * inv[1], s[m][2 * kk + 1][3] * inv[1]);
      } else { pa[m][kk][2] = 0; pa[m][kk][3] = 0; }
    }
  }
  asm volatile("cp.async.wait_group 0;" ::: "memory");
  __syncwarp();
  uint32_t ov[2][16][2];
#pragma unroll
  for (int np = 0; np < 8; np++) {
    float o[2][2][4] = {};
#pragma unroll
    for (int kk = 0; kk < 3; kk++) {
      uint32_t b[4];
      int mi = lane >> 3, r = kk * 16 + (mi & 1) * 8 + (lane & 7), c = np * 2 + (mi >> 1);
      ldsm4t(b, sv + r * 256 + ((c ^ (r & 7)) * 16));
#pragma unroll
      for (int m = 0; m < 2; m++) { mma16816(o[m][0], pa[m][kk], b[0], b[1]); mma16816(o[m][1], pa[m][kk], b[2], b[3]); }
    }
#pragma unroll
    for (int m = 0; m < 2; m++)
#pragma unroll
      for (int q = 0; q < 2; q++) { ov[m][np * 2 + q][0] = pack_bf16(o[m][q][0], o[m][q][1]); ov[m][np * 2 + q][1] = pack_bf16(o[m][q][2], o[m][q][3]); }
  }
  __syncwarp();
#pragma unroll
  for (int m = 0; m < 2; m++)
#pragma unroll
    for (int n = 0; n < 16; n++)
#pragma unroll
      for (int hh = 0; hh < 2; hh++) {
        int r = m * 16 + hh * 8 + g;
        *(uint32_t*)(sm + r * 256 + ((n ^ (r & 7)) * 16) + t * 4) = ov[m][n][hh];
      }
  __syncwarp();
#pragma unroll
  for (int i = 0; i < 16; i++) {
    int idx = lane + 32 * i, r = idx >> 4, c = idx & 15;
    *(uint4*)(g_o + (tok0 + r) * HD_ + h * 128 + c * 8) = *(const uint4*)(sm + r * 256 + ((c ^ (r & 7)) * 16));
  }
}

__global__ void __launch_bounds__(384, 1) gemm_kernel(const __grid_constant__ GemmParams p) {
  extern __shared__ uint8_t smem_raw[];
  const uint32_t sbase = (smem_u32(smem_raw) + 1023) & ~1023u;
  const uint32_t stg0 = sbase + NSTAGE * STAGE_BYTES, fullb = stg0 + 8 * 2048, emptyb = fullb + 64;
  const uint32_t rank = cluster_rank();
  const int wg = __shfl_sync(~0u, (int)(threadIdx.x >> 7), 0), lane = threadIdx.x & 31;
  const int cl = blockIdx.x >> 1;
  if (threadIdx.x == 0) {
    for (int i = 0; i < NSTAGE; i++) { mbar_init(fullb + i * 8, 1); mbar_init(emptyb + i * 8, 4); }
    asm volatile("fence.mbarrier_init.release.cluster;" ::: "memory");
  }
  cluster_sync();
  if (blockIdx.x == 0 && threadIdx.x == 0) PT(1 + p.kid * 2);
  const uint16_t* jobs = p.job + cl * p.stride;
  if (wg == 0) {
    asm volatile("setmaxnreg.dec.sync.aligned.u32 40;");
    if (threadIdx.x == 0) {
      int stage = 0; uint32_t phase = 1;
      for (int j = 0; j < p.stride; j++) {
        uint32_t job = jobs[j];
        if (job == 0xFFFF) break;
        int type = job >> 12, m = (job >> 6) & 63, n = job & 63;
        int row0 = m * 256 + rank * 128;
        int bn = type < 3 ? 256 : 192;
        if (type == 6) {
          for (int k = 0; k < NSTAGE; k++) {
            mbar_wait_cl(emptyb + stage * 8, phase);
            asm volatile("mbarrier.arrive.shared::cta.b64 _, [%0];" ::"r"(fullb + stage * 8) : "memory");
            if (++stage == NSTAGE) { stage = 0; phase ^= 1; }
          }
          continue;
        }
        int kit = type < 3 ? 9 : (type == 3 ? 32 : (type == 4 ? 72 : (type == 5 ? 64 : 8)));
        int k0 = 0;
        if (type == 7) { k0 = (n / 3) * 8; n = n % 3; type = 5; }
        if (type == 5) wait_cnt(&g_cnt[16 + m], 32);
        const CUtensorMap* ma = &p.mA[type < 3 ? 0 : type - 2];
        const CUtensorMap* mb = &p.mB[type];
        bool ta = (type == 3 || type == 4);
        if (type >= 4) {
          if (type == 4) wait_cnt(&g_cnt[0], 108);
          asm volatile("fence.proxy.async;" ::: "memory");
        }
        for (int k = k0; k < k0 + kit; k++) {
          mbar_wait_cl(emptyb + stage * 8, phase);
          uint32_t fb = fullb + stage * 8, a = sbase + stage * STAGE_BYTES, b = a + 16384;
          mbar_expect(fb, 16384 + bn * 128);
          if (ta) { tma2d(a, ma, row0, k * 64, fb); tma2d(a + 8192, ma, row0 + 64, k * 64, fb); }
          else tma2d(a, ma, k * 64, row0, fb);
          for (int i = 0; i < bn / 64; i++) tma2d_mc(b + i * 8192 + rank * 4096, mb, n * bn + i * 64, k * 64 + rank * 32, fb, (uint16_t)3);
          if (++stage == NSTAGE) { stage = 0; phase ^= 1; }
        }
      }
    }
    __syncwarp();
    pdl_launch();
    cluster_sync();
  } else {
    asm volatile("setmaxnreg.inc.sync.aligned.u32 232;");
    const int cw = wg - 1, warp = __shfl_sync(~0u, (int)(threadIdx.x >> 5) & 3, 0);
    const uint32_t eb_l = mapa(emptyb, rank), eb_r = mapa(emptyb, rank ^ 1);
    const uint32_t stg = stg0 + (cw * 4 + warp) * 2048;
    const bool elect = (threadIdx.x & 127) == 0;
    const int g = lane >> 2, t = lane & 3;
    int stage = 0; uint32_t phase = 0;
    float d[128];
    for (int j = 0; j < p.stride; j++) {
      uint32_t job = jobs[j];
      if (job == 0xFFFF) break;
      int type = job >> 12, m = (job >> 6) & 63, n = job & 63;
      int row0 = m * 256 + rank * 128 + cw * 64 + warp * 16;
      if (type < 3) {
        gemm_mainloop<256, 0>(d, 9, sbase, fullb, eb_l, eb_r, cw, stage, phase, elect);
        bf16* dst = (type == 0 ? g_q : (type == 1 ? g_k : g_v)) + (size_t)row0 * HD_ + n * 256;
        store_tile<256>(d, stg, dst, HD_, lane, [](float a, float b, int, int) { return pack_bf16(a, b); });
        __threadfence();
        asm volatile("bar.sync %0, 256;" ::"r"(1) : "memory");
        if (threadIdx.x == 128) atomicAdd(&g_cnt[(type ? 8 : 40) + m], 1);
      } else if (type == 3) {
        gemm_mainloop<192, 1>(d, 32, sbase, fullb, eb_l, eb_r, cw, stage, phase, elect);
        float bb[2] = {__bfloat162float(p.b1[row0 + g]), __bfloat162float(p.b1[row0 + g + 8])};
        store_tile<192>(d, stg, g_ut + (size_t)row0 * D_ + n * 192, D_, lane,
                        [&](float a, float b, int h, int) { return pack_bf16(gelu_tanh(a + bb[h]), gelu_tanh(b + bb[h])); });
        __threadfence();
        asm volatile("fence.proxy.async;" ::: "memory");
        asm volatile("bar.sync %0, 256;" ::"r"(1) : "memory");
        if (threadIdx.x == 128) atomicAdd(&g_cnt[0], 1);
      } else if (type == 4) {
        gemm_mainloop<192, 1>(d, 72, sbase, fullb, eb_l, eb_r, cw, stage, phase, elect);
        float bb[2] = {__bfloat162float(p.b2[row0 + g]), __bfloat162float(p.b2[row0 + g + 8])};
#pragma unroll
        for (int i = 0; i < 24; i++)
#pragma unroll
          for (int h = 0; h < 2; h++) {
            size_t off = (size_t)(row0 + g + h * 8) * D_ + n * 192 + i * 8 + t * 2;
            float2 xv = unpack_bf16(*(const uint32_t*)(p.x + off));
            *(float2*)(g_yb + off) = make_float2(d[i * 4 + h * 2] + bb[h] + xv.x, d[i * 4 + h * 2 + 1] + bb[h] + xv.y);
          }
        __threadfence();
        asm volatile("bar.sync %0, 256;" ::"r"(1) : "memory");
        if (threadIdx.x == 128) atomicAdd(&g_cnt[24 + m], 1);
      } else if (type == 6) {
        const int st0 = stage;
        for (int k = 0; k < NSTAGE; k++) { mbar_wait(fullb + stage * 8, phase); if (++stage == NSTAGE) { stage = 0; phase ^= 1; } }
        const int seg = m * 8 + (n >> 1), w8 = cw * 4 + warp;
        if (lane == 0) wait_cnt(&g_cnt[40 + m], 32);
        __syncwarp();
        {
          const size_t o = ((size_t)seg * 32 + lane) * HD_ + ((n & 1) * 16 + rank * 8 + w8) * 128;
#pragma unroll
          for (int i = 0; i < 2; i++) {
            asm volatile("prefetch.global.L2 [%0];" ::"l"(g_q + o + i * 64)); asm volatile("prefetch.global.L2 [%0];" ::"l"(g_k + o + i * 64));
            asm volatile("prefetch.global.L2 [%0];" ::"l"(g_v + o + i * 64));
          }
        }
        attn_unit(seg, (n & 1) * 16 + rank * 8 + w8, smem_raw + (sbase - smem_u32(smem_raw)) + w8 * 12288, lane, &g_cnt[96 + seg]);
        __threadfence();
        asm volatile("fence.proxy.async;" ::: "memory");
        asm volatile("bar.sync %0, 256;" ::"r"(1) : "memory");
        if (elect) for (int k = 0; k < NSTAGE; k++) { mbar_arrive_remote(eb_l + k * 8); mbar_arrive_remote(eb_r + k * 8); }
        if (threadIdx.x == 128) atomicAdd(&g_cnt[16 + m], 1);
        (void)st0;
#pragma unroll
        for (int i = 0; i < 128; i++) d[i] = 0.f;
      } else if (type == 7) {
        const int nt = n % 3;
        gemm_mainloop<192, 0>(d, 8, sbase, fullb, eb_l, eb_r, cw, stage, phase, elect);
        if (lane == 0) wait_cnt(&g_cnt[24 + m], 6);
        __syncwarp();
        if (p.kid == 2) {
          const int ks = n / 3;
          float* pk = g_pk + ((size_t)ks * 512 + row0 - 1536 + g) * D_ + nt * 192 + t * 2;
#pragma unroll
          for (int i = 0; i < 24; i++)
#pragma unroll
            for (int h = 0; h < 2; h++) *(float2*)(pk + h * 8 * D_ + i * 8) = make_float2(d[i * 4 + h * 2], d[i * 4 + h * 2 + 1]);
          __threadfence();
          asm volatile("bar.sync %0, 256;" ::"r"(1) : "memory");
          unsigned int* cn = &g_cnt[48 + ((m - 4) * 3 + nt) * 2 + rank];
          if (threadIdx.x == 128) atomicAdd(cn, 1);
          if (lane == 0) wait_cnt(cn, 8);
          __syncwarp();
          const int r0 = m * 256 + rank * 128 + ks * 16;
#pragma unroll
          for (int it = 0; it < 3; it++) {
            int i = threadIdx.x - 128 + it * 256, rr = i / 48, cc = (i - rr * 48) * 4;
            size_t off = (size_t)(r0 + rr) * D_ + nt * 192 + cc;
            float4 y = __ldcg((const float4*)(g_yb + off)), q[8];
#pragma unroll
            for (int k = 0; k < 8; k++) q[k] = __ldcg((const float4*)(g_pk + (size_t)k * 512 * D_ + off - (size_t)1536 * D_));
#pragma unroll
            for (int k = 0; k < 8; k++) { y.x += q[k].x; y.y += q[k].y; y.z += q[k].z; y.w += q[k].w; }
            *(uint2*)(p.out + off) = make_uint2(pack_bf16(y.x, y.y), pack_bf16(y.z, y.w));
          }
          continue;
        }
#pragma unroll
        for (int i = 0; i < 24; i++)
#pragma unroll
          for (int h = 0; h < 2; h++)
            atomicAdd((float2*)(g_yb + (size_t)(row0 + g + h * 8) * D_ + nt * 192 + i * 8 + t * 2), make_float2(d[i * 4 + h * 2], d[i * 4 + h * 2 + 1]));
        __threadfence();
        asm volatile("bar.sync %0, 256;" ::"r"(1) : "memory");
        volatile uint32_t* lastf = (volatile uint32_t*)(smem_raw + (emptyb + 64 - smem_u32(smem_raw)));
        if (threadIdx.x == 128) { *lastf = atomicAdd(&g_cnt[48 + ((m - 4) * 3 + nt) * 2 + rank], 1); __threadfence(); }
        asm volatile("bar.sync %0, 256;" ::"r"(1) : "memory");
        if (*lastf == 7) {
          const int r0 = m * 256 + rank * 128;
#pragma unroll 8
          for (int i = threadIdx.x - 128; i < 128 * 48; i += 256) {
            int rr = i / 48, cc = (i - rr * 48) * 4;
            size_t off = (size_t)(r0 + rr) * D_ + nt * 192 + cc;
            float4 y = __ldcg((const float4*)(g_yb + off));
            *(uint2*)(p.out + off) = make_uint2(pack_bf16(y.x, y.y), pack_bf16(y.z, y.w));
          }
        }
        asm volatile("bar.sync %0, 256;" ::"r"(1) : "memory");
      } else {
        gemm_mainloop<192, 0>(d, 64, sbase, fullb, eb_l, eb_r, cw, stage, phase, elect);
        if (lane == 0) wait_cnt(&g_cnt[24 + m], 6);
        __syncwarp();
        const float* yb = g_yb + (size_t)(row0 + g) * D_ + n * 192 + t * 2;
        store_tile<192>(d, stg, p.out + (size_t)row0 * D_ + n * 192, D_, lane,
                        [&](float a, float b, int h, int c) { float2 y = *(const float2*)(yb + h * 8 * D_ + c); return pack_bf16(a + y.x, b + y.y); });
      }
    }
    if (blockIdx.x == 0 && threadIdx.x == 128) PT(2 + p.kid * 2);
    cluster_sync();
  }
}

constexpr int CH_WV = 0;
constexpr int CH_MEM = CH_WV + 73728;
constexpr int CH_KB = CH_MEM + 9216;
constexpr int CH_VB = CH_KB + 12288;
constexpr int CH_WO = CH_VB + 12288;
constexpr int CH_Q = CH_WO + 81920;
constexpr int CH_R1 = CH_Q + 1024;
constexpr int CH_SC = CH_R1 + 4096;
constexpr int CH_OF = CH_SC + 3584;
constexpr int CH_R2 = CH_OF + 8192;
constexpr int CH_BAR = CH_R2 + 12288;
constexpr int CHAIN_SMEM = CH_BAR + 64 + 1024;
#define POLL_DELAY 550
__device__ __forceinline__ void st_async1(uint32_t a, uint32_t v, uint32_t bar) { asm volatile("st.async.weak.shared::cluster.mbarrier::complete_tx::bytes.b32 [%0], %1, [%2];" ::"r"(a), "r"(v), "r"(bar) : "memory"); }
__device__ __forceinline__ void st_async2(uint32_t a, uint32_t v0, uint32_t v1, uint32_t bar) { asm volatile("st.async.weak.shared::cluster.mbarrier::complete_tx::bytes.v2.b32 [%0], {%1, %2}, [%3];" ::"r"(a), "r"(v0), "r"(v1), "r"(bar) : "memory"); }
__device__ __forceinline__ uint4 lds128(uint32_t a) { uint4 v; asm volatile("ld.shared.v4.u32 {%0,%1,%2,%3}, [%4];" : "=r"(v.x), "=r"(v.y), "=r"(v.z), "=r"(v.w) : "r"(a) : "memory"); return v; }
__device__ __forceinline__ void sts128f(uint32_t a, const float (&c)[4]) { asm volatile("st.shared.v4.f32 [%0], {%1,%2,%3,%4};" ::"r"(a), "f"(c[0]), "f"(c[1]), "f"(c[2]), "f"(c[3]) : "memory"); }
__device__ __forceinline__ void sts32(uint32_t a, uint32_t v) { asm volatile("st.shared.u32 [%0], %1;" ::"r"(a), "r"(v) : "memory"); }
__device__ __forceinline__ void mbar_wait_b(uint32_t b, uint32_t parity) {
  uint32_t ok; int n = 0;
  do { asm volatile("{\n.reg .pred p;\nmbarrier.try_wait.parity.shared::cta.b64 p, [%1], %2;\nselp.u32 %0, 1, 0, p;\n}" : "=r"(ok) : "r"(b), "r"(parity) : "memory"); } while (!ok && ++n < (1 << 20));
}
__device__ __forceinline__ uint32_t mapa_v(uint32_t a, uint32_t r) { uint32_t o; asm volatile("mapa.shared::cluster.u32 %0, %1, %2;" : "=r"(o) : "r"(a), "r"(r)); return o; }
__device__ __forceinline__ uint32_t tid_v() { uint32_t o; asm volatile("mov.u32 %0, %%tid.x;" : "=r"(o)); return o; }
template <int ACC>
__device__ __forceinline__ void wg_rs(float (&d)[4], const uint32_t (&a)[4], uint32_t dlo) {
  uint64_t db = ((uint64_t)16 << 32) | dlo;
  asm volatile("{\n.reg .pred p;\nsetp.ne.b32 p, %9, 0;\nwgmma.mma_async.sync.aligned.m64n8k16.f32.bf16.bf16 {%0,%1,%2,%3}, {%4,%5,%6,%7}, %8, p, 1, 1, 0;\n}"
               : "+f"(d[0]), "+f"(d[1]), "+f"(d[2]), "+f"(d[3]) : "r"(a[0]), "r"(a[1]), "r"(a[2]), "r"(a[3]), "l"(db), "n"(ACC));
}
template <int N>
__device__ __forceinline__ void wg_wait(float (&d)[N][4]) {
  asm volatile("wgmma.commit_group.sync.aligned;\nwgmma.wait_group.sync.aligned 0;" ::: "memory");
#pragma unroll
  for (int i = 0; i < N; i++) asm volatile("" : "+f"(d[i][0]), "+f"(d[i][1]), "+f"(d[i][2]), "+f"(d[i][3]) :: "memory");
}
#define BAR_ALL() asm volatile("bar.sync 0, 256;" ::: "memory")

__global__ void __launch_bounds__(256, 1) chain_kernel(const bf16* __restrict__ mem0, const bf16* __restrict__ Wq, const bf16* __restrict__ Wk,
                                                       const bf16* __restrict__ Wv, const bf16* __restrict__ Wo) {
  extern __shared__ uint8_t smem_raw[];
  const uint32_t sb = (smem_u32(smem_raw) + 1023) & ~1023u;
  const int tid = threadIdx.x, warp = __shfl_sync(~0u, tid >> 5, 0), wgi = __shfl_sync(~0u, tid >> 7, 0), lane = tid & 31, g = lane >> 2, t = lane & 3;
  const uint32_t r = cluster_rank();
  const int c = blockIdx.x >> 3, h = 4 * c + (r >> 1), j0 = h * 128 + (r & 1) * 64;
  const uint32_t bm = sb + CH_BAR, bs = bm + 8, bo = bm + 16;
  pdl_launch();
  if (blockIdx.x == 0 && tid == 0) PT(7);
  if (tid == 0) { mbar_init(bm, 1); mbar_init(bs, 1); mbar_init(bo, 1); asm volatile("fence.mbarrier_init.release.cluster;" ::: "memory"); }
  const int mi = lane >> 3, l7 = lane & 7;
  for (int i = tid; i < 576 * 8; i += 256) {
    int row = i >> 3, ch = i & 7;
    cp16(sb + CH_WV + row * 128 + ((ch ^ (row & 7)) * 16), Wq + (size_t)row * HD_ + j0 + ch * 8);
    cp16(sb + CH_WO + row * 128 + ((ch ^ (row & 7)) * 16), Wk + (size_t)row * HD_ + j0 + ch * 8);
  }
  asm volatile("cp.async.commit_group;\ncp.async.wait_group 0;" ::: "memory");
  BAR_ALL();
  uint32_t w1[36][4];
#pragma unroll
  for (int i = 0; i < 36; i++) {
    int row = i * 16 + (mi >> 1) * 8 + l7, ch = ((warp & 3) * 2 + (mi & 1)) ^ (row & 7);
    ldsm4t(w1[i], sb + (wgi ? CH_WO : CH_WV) + row * 128 + ch * 16);
  }
  BAR_ALL();
  for (int i = tid; i < 512 * 10; i += 256) {
    int row = i / 10, ch = i - row * 10;
    cp16(sb + CH_WV + row * 176 + ch * 16, Wo + (size_t)(c * 512 + row) * D_ + (ch < 8 ? r * 64 + ch * 8 : 512 + (r >> 1) * 16 + (ch - 8) * 8));
  }
  asm volatile("cp.async.commit_group;\ncp.async.wait_group 0;" ::: "memory");
  BAR_ALL();
  const int kperm = 2 * ((mi >> 1) * 2 + (l7 >> 2)) + (l7 & 1) + 8 * ((l7 >> 1) & 1);
  for (int i = 0; i < 16; i++) {
    uint32_t a[4];
    ldsm4t(a, sb + CH_WV + ((wgi * 16 + i) * 16 + kperm) * 176 + ((warp & 3) * 2 + (mi & 1)) * 16);
    asm volatile("st.shared.v4.u32 [%0], {%1,%2,%3,%4};" ::"r"(sb + CH_WO + 8192 + (warp * 16 + i) * 512 + lane * 16), "r"(a[0]), "r"(a[1]), "r"(a[2]), "r"(a[3]) : "memory");
  }
  for (int u = warp; u < 16; u += 8) {
    uint32_t a[4];
    ldsm4t(a, sb + CH_WV + (((r & 1) * 16 + u) * 16 + kperm) * 176 + (8 + (mi & 1)) * 16);
    asm volatile("st.shared.v4.u32 [%0], {%1,%2,%3,%4};" ::"r"(sb + CH_WO + u * 512 + lane * 16), "r"(a[0]), "r"(a[1]), "r"(a[2]), "r"(a[3]) : "memory");
  }
  BAR_ALL();
  for (int i = tid; i < 576 * 8; i += 256) {
    int row = i >> 3, ch = i & 7;
    cp16(sb + CH_WV + row * 128 + ((ch ^ (row & 7)) * 16), Wv + (size_t)row * HD_ + j0 + ch * 8);
  }
  for (int i = tid; i < 8 * 72; i += 256) {
    int row = i / 72, ch = i - row * 72;
    cp16(sb + CH_MEM + ch * 128 + row * 16, mem0 + row * D_ + ch * 8);
  }
  for (int i = tid; i < 4 * 64; i += 256) {
    int b = i >> 6, o = i & 63;
    asm volatile("st.shared.v4.u32 [%0], {%1,%1,%1,%1};" ::"r"(sb + CH_KB + b * 6144 + 40 * 128 + o * 16), "r"(0) : "memory");
  }
  auto prefetch_kv = [&](int s, int tid) {
    if ((s & 7) == 0) { if ((tid & 31) == 0) wait_cnt(&g_cnt[8 + (s >> 3)], 64); __syncwarp(); }
#pragma unroll
    for (int i = 0; i < 2; i++) {
      int u = tid + i * 256, which = u >> 8, row = (u & 255) >> 3, ch = u & 7;
      const bf16* src = (which ? g_v : g_k) + (size_t)(s * 32 + row) * HD_ + j0 + ch * 8;
      cp16(sb + (which ? CH_VB : CH_KB) + (s & 1) * 6144 + (row + 8) * 128 + ((ch ^ (row & 7)) * 16), src);
    }
    asm volatile("cp.async.commit_group;" ::: "memory");
  };
  prefetch_kv(0, tid);
  asm volatile("cp.async.wait_group 0;" ::: "memory");
  asm volatile("fence.proxy.async.shared::cta;" ::: "memory");
  BAR_ALL();
  cluster_sync();
  const uint32_t dsb = ((sb & 0x3FFFF) >> 4) | (8u << 16);
  if (blockIdx.x == 0 && tid == 0) PT(10);
#define CP(i) if (blockIdx.x == 0 && lane == 0 && warp == (((i) == 5 || (i) == 7) ? 4 : 0)) PC(64 + s * 16 + (i))
  for (int s = 0; s < NSEG; s++) {
    const int tid = tid_v(), lane = tid & 31, g = lane >> 2, t = lane & 3, mi = lane >> 3, l7 = lane & 7;
    CP(0);
    const uint32_t par = s & 1, kb = sb + CH_KB + par * 6144, vb = sb + CH_VB + par * 6144;
    if (s > 0) mbar_wait_b(bm, par ^ 1);
    CP(1);
    if (tid == 0 && s < NSEG - 1) { mbar_expect(bs, 2560); mbar_expect(bo, 8192); mbar_expect(bm, 9216); }
    auto phase1 = [&]() {
      float pa[3][4] = {};
#pragma unroll
      for (int i = 0; i < 36; i += 2) {
        uint32_t b[4];
        ldsm4(b, sb + CH_MEM + i * 256 + mi * 128 + l7 * 16);
        mma16816(pa[i % 3], w1[i], b[0], b[1]); mma16816(pa[(i + 1) % 3], w1[i + 1], b[2], b[3]);
      }
      CP(2);
      uint32_t b0 = movm(pack_bf16(pa[0][0] + pa[1][0] + pa[2][0], pa[0][1] + pa[1][1] + pa[2][1]));
      uint32_t b1 = movm(pack_bf16(pa[0][2] + pa[1][2] + pa[2][2], pa[0][3] + pa[1][3] + pa[2][3]));
      uint32_t dst = (wgi ? kb : sb + CH_Q) + g * 128 + t * 4;
      sts32(dst + ((((warp & 3) * 2) ^ g) * 16), b0); sts32(dst + ((((warp & 3) * 2 + 1) ^ g) * 16), b1);
      if (wgi) { uint32_t* gp = (uint32_t*)(g_km + ((size_t)s * 8 + g) * HD_ + j0 + (warp & 3) * 16 + t * 2); gp[0] = b0; gp[4] = b1; }
      asm volatile("cp.async.wait_group 0;" ::: "memory");
    };
    if (wgi == 0) {
      phase1();
      BAR_ALL();
      CP(4);
      if (s + 1 < NSEG) { prefetch_kv(s + 1, tid); asm volatile("bar.sync 6, 224;" ::: "memory"); }
      float va[4][4];
      asm volatile("wgmma.fence.sync.aligned;" ::: "memory");
      const uint32_t dwa = (((sb + CH_WV) & 0x3FFFF) >> 4) | ((8192u >> 4) << 16);
#pragma unroll
      for (int ks = 0; ks < 36; ks++) {
        uint64_t da = ((uint64_t)(0x40000000u | (1024 >> 4)) << 32) | (dwa + ks * 128), db = ((uint64_t)16 << 32) | (dsb + ((CH_MEM + ks * 256) >> 4));
        if (ks < 4)
          asm volatile("{\n.reg .pred p;\nsetp.ne.b32 p, 0, 0;\nwgmma.mma_async.sync.aligned.m64n8k16.f32.bf16.bf16 {%0,%1,%2,%3}, %4, %5, p, 1, 1, 1, 0;\n}"
                       : "=f"(va[ks & 3][0]), "=f"(va[ks & 3][1]), "=f"(va[ks & 3][2]), "=f"(va[ks & 3][3]) : "l"(da), "l"(db));
        else
          asm volatile("{\n.reg .pred p;\nsetp.ne.b32 p, 1, 0;\nwgmma.mma_async.sync.aligned.m64n8k16.f32.bf16.bf16 {%0,%1,%2,%3}, %4, %5, p, 1, 1, 1, 0;\n}"
                       : "+f"(va[ks & 3][0]), "+f"(va[ks & 3][1]), "+f"(va[ks & 3][2]), "+f"(va[ks & 3][3]) : "l"(da), "l"(db));
      }
      wg_wait(va);
      CP(6);
      uint32_t b0 = movm(pack_bf16(va[0][0] + va[1][0] + va[2][0] + va[3][0], va[0][1] + va[1][1] + va[2][1] + va[3][1]));
      uint32_t b1 = movm(pack_bf16(va[0][2] + va[1][2] + va[2][2] + va[3][2], va[0][3] + va[1][3] + va[2][3] + va[3][3]));
      sts32(vb + g * 128 + t * 4 + (((warp * 2) ^ g) * 16), b0); sts32(vb + g * 128 + t * 4 + (((warp * 2 + 1) ^ g) * 16), b1);
      uint32_t* gp = (uint32_t*)(g_vm + ((size_t)s * 8 + g) * HD_ + j0 + warp * 16 + t * 2); gp[0] = b0; gp[4] = b1;
      asm volatile("bar.arrive 7, 256;" ::: "memory");
    } else {
      phase1();
      BAR_ALL();
      if (warp == 7 && lane == 0 && s > 0) { __threadfence(); atomicAdd(&g_cnt[96 + s - 1], 1); }
      if (warp < 7 && s < NSEG - 1) {
        const int mt = warp - 4;
        const uint32_t sc_l = mapa_v(sb + CH_SC + (r & 1) * 1792, r), sc_r = mapa_v(sb + CH_SC + (r & 1) * 1792, r ^ 1), bs_l = mapa_v(bs, r), bs_r = mapa_v(bs, r ^ 1);
        float sa[4][4] = {};
#pragma unroll
        for (int kp = 0; kp < 2; kp++) {
          uint32_t b[4], a0[4], a1[4];
          ldsm4(b, sb + CH_Q + l7 * 128 + (((kp * 4 + mi) ^ l7) * 16));
          int row = mt * 16 + (mi & 1) * 8 + l7;
          ldsm4(a0, kb + row * 128 + (((kp * 4 + (mi >> 1)) ^ l7) * 16));
          ldsm4(a1, kb + row * 128 + (((kp * 4 + 2 + (mi >> 1)) ^ l7) * 16));
          mma16816(sa[2 * kp], a0, b[0], b[1]); mma16816(sa[2 * kp + 1], a1, b[2], b[3]);
        }
        asm volatile("bar.arrive 6, 224;" :: "f"(sa[0][0]), "f"(sa[1][0]), "f"(sa[2][0]), "f"(sa[3][0]) : "memory");
#pragma unroll
        for (int e = 0; e < 4; e++) {
          uint32_t off = ((2 * t + (e & 1)) * 56 + mt * 16 + (e >> 1) * 8 + g) * 4, v = __float_as_uint((sa[0][e] + sa[1][e]) + (sa[2][e] + sa[3][e]));
          if (mt < 2 || e < 2) { st_async1(sc_r + off, v, bs_r); st_async1(sc_l + off, v, bs_l); }
        }
        CP(5);
      }
      if (s < NSEG - 1) {
        prefetch_kv(s + 1, tid);
        const int w3 = warp & 3;
        uint32_t vt[3][4];
#pragma unroll
        for (int kk = 1; kk < 3; kk++) { int row = kk * 16 + (mi >> 1) * 8 + l7; ldsm4t(vt[kk], vb + row * 128 + (((w3 * 2 + (mi & 1)) ^ l7) * 16)); }
        mbar_wait_b(bs, par);
        CP(7);
        float z[10]; float mx = -INFINITY;
        const float scl = 0.08838834764831845f * 1.4426950408889634f;
#pragma unroll
        for (int i = 0; i < 5; i++) {
          float2 u0, u1; uint32_t a = sb + CH_SC + (g * 56 + i * 8 + 2 * t) * 4;
          asm volatile("ld.shared.v2.f32 {%0,%1}, [%2];" : "=f"(u0.x), "=f"(u0.y) : "r"(a) : "memory");
          asm volatile("ld.shared.v2.f32 {%0,%1}, [%2];" : "=f"(u1.x), "=f"(u1.y) : "r"(a + 1792) : "memory");
          z[2 * i] = (u0.x + u1.x) * scl; z[2 * i + 1] = (u0.y + u1.y) * scl;
        }
        mx = fmaxf(fmaxf(fmaxf(z[0], z[1]), fmaxf(z[2], z[3])), fmaxf(fmaxf(fmaxf(z[4], z[5]), fmaxf(z[6], z[7])), fmaxf(z[8], z[9])));
        mx = fmaxf(mx, __shfl_xor_sync(~0u, mx, 1)); mx = fmaxf(mx, __shfl_xor_sync(~0u, mx, 2));
        uint32_t pb[5];
#pragma unroll
        for (int i = 0; i < 5; i++) pb[i] = pack_bf16(exp2f(z[2 * i] - mx), exp2f(z[2 * i + 1] - mx));
        const uint32_t ones[4] = {0x3F803F80u, 0x3F803F80u, 0x3F803F80u, 0x3F803F80u};
        float o0[4] = {}, o1[4] = {}, o2[4] = {}, s0[4] = {}, s1[4] = {}, s2[4] = {};
        mma16816(s0, ones, pb[0], pb[1]);
        mma16816(o1, vt[1], pb[2], pb[3]); mma16816(s1, ones, pb[2], pb[3]);
        mma16816(o2, vt[2], pb[4], 0u); mma16816(s2, ones, pb[4], 0u);
        asm volatile("bar.sync 7, 256;" ::: "memory");
        ldsm4t(vt[0], vb + ((mi >> 1) * 8 + l7) * 128 + (((w3 * 2 + (mi & 1)) ^ l7) * 16));
        mma16816(o0, vt[0], pb[0], pb[1]);
        const float i0 = __fdividef(1.f, s0[0] + s1[0] + s2[0]), i1 = __fdividef(1.f, s0[1] + s1[1] + s2[1]);
        uint32_t f0 = movm(pack_bf16((o0[0] + o1[0] + o2[0]) * i0, (o0[1] + o1[1] + o2[1]) * i1));
        uint32_t f1 = movm(pack_bf16((o0[2] + o1[2] + o2[2]) * i0, (o0[3] + o1[3] + o2[3]) * i1));
        const int ks = r * 4 + w3;
        const uint32_t off = CH_OF + ks * 256 + (t >> 1) * 128 + g * 16 + (t & 1) * 8;
        const uint32_t cl0 = mapa_v(sb, 0), clstep = mapa_v(sb, 1) - cl0;
#pragma unroll
        for (int d = 0; d < 8; d++) st_async2(cl0 + d * clstep + off, f0, f1, cl0 + d * clstep + CH_BAR + 16);
      } else asm volatile("bar.sync 7, 256;" ::: "memory");
    }
    if (s == NSEG - 1) break;
    CP(8);
    uint32_t wo[16][4];
#pragma unroll
    for (int i = 0; i < 16; i++) { uint4 v = lds128(sb + CH_WO + 8192 + (warp * 16 + i) * 512 + lane * 16); wo[i][0] = v.x; wo[i][1] = v.y; wo[i][2] = v.z; wo[i][3] = v.w; }
    mbar_wait_b(bo, par);
    CP(9);
    const uint32_t tag = ((s >> 1) + 1) & 1;
    float* pbase = g_part + (size_t)par * 8 * 5120 + lane * 4;
    auto put = [&](int slot, const float (&a)[4]) {
      asm volatile("st.relaxed.gpu.global.v4.b32 [%0], {%1,%2,%3,%4};" ::"l"(pbase + c * 5120 + slot * 128), "r"((__float_as_uint(a[0]) & ~1u) | tag),
                   "r"((__float_as_uint(a[1]) & ~1u) | tag), "r"((__float_as_uint(a[2]) & ~1u) | tag), "r"((__float_as_uint(a[3]) & ~1u) | tag) : "memory");
    };
    {
      float acc[4][4];
      asm volatile("wgmma.fence.sync.aligned;" ::: "memory");
      const uint32_t dof = dsb + ((CH_OF >> 4) + wgi * 256);
#pragma unroll
      for (int i = 0; i < 16; i++) { if (i < 4) wg_rs<0>(acc[i & 3], wo[i], dof + i * 16); else wg_rs<1>(acc[i & 3], wo[i], dof + i * 16); }
      wg_wait(acc);
#pragma unroll
      for (int e = 0; e < 4; e++) acc[0][e] = (acc[0][e] + acc[1][e]) + (acc[2][e] + acc[3][e]);
      CP(10);
      const int w3 = warp & 3;
      if (wgi) {
        sts128f(sb + CH_R2 + w3 * 512 + lane * 16, acc[0]);
        asm volatile("bar.arrive %0, 64;" ::"r"(1 + w3) : "memory");
        if (w3 < 2) {
          float ex[2][4] = {};
#pragma unroll
          for (int i = 0; i < 8; i += 2) {
            uint32_t b[4]; ldsm4(b, sb + CH_OF + ((r & 1) * 16 + w3 * 8 + i) * 256 + mi * 128 + l7 * 16);
            uint4 v0 = lds128(sb + CH_WO + (w3 * 8 + i) * 512 + lane * 16), v1 = lds128(sb + CH_WO + (w3 * 8 + i + 1) * 512 + lane * 16);
            uint32_t a0[4] = {v0.x, v0.y, v0.z, v0.w}, a1[4] = {v1.x, v1.y, v1.z, v1.w};
            mma16816(ex[0], a0, b[0], b[1]); mma16816(ex[1], a1, b[2], b[3]);
          }
#pragma unroll
          for (int e = 0; e < 4; e++) ex[0][e] += ex[1][e];
          if (w3 == 1) { sts128f(sb + CH_R2 + 4 * 512 + lane * 16, ex[0]); asm volatile("bar.arrive 5, 64;" ::: "memory"); }
          else {
            asm volatile("bar.sync 5, 64;" ::: "memory");
            uint4 v = lds128(sb + CH_R2 + 4 * 512 + lane * 16);
            ex[0][0] += __uint_as_float(v.x); ex[0][1] += __uint_as_float(v.y); ex[0][2] += __uint_as_float(v.z); ex[0][3] += __uint_as_float(v.w);
            put(32 + r, ex[0]);
          }
        }
      } else {
        asm volatile("bar.sync %0, 64;" ::"r"(1 + w3) : "memory");
        uint4 v = lds128(sb + CH_R2 + w3 * 512 + lane * 16);
        acc[0][0] += __uint_as_float(v.x); acc[0][1] += __uint_as_float(v.y); acc[0][2] += __uint_as_float(v.z); acc[0][3] += __uint_as_float(v.w);
        put(r * 4 + w3, acc[0]);
      }
    }
    CP(11);
    if (warp < 4 || warp == 6) { long long t0 = clock64(); while (clock64() - t0 < POLL_DELAY) {} }
    if (warp < 4) {
      const float* pb = pbase + (r * 4 + warp) * 128;
      uint4 v[8]; int n = 0; uint32_t need = 0xFF;
#pragma unroll
      for (int i = 0; i < 8; i++) v[i] = make_uint4(0, 0, 0, 0);
      do {
#pragma unroll
        for (int i = 0; i < 8; i++)
          asm volatile("{\n.reg .pred p;\nsetp.ne.b32 p, %5, 0;\n@p ld.relaxed.gpu.global.v4.b32 {%0,%1,%2,%3}, [%4];\n}" : "+r"(v[i].x), "+r"(v[i].y), "+r"(v[i].z), "+r"(v[i].w) : "l"(pb + i * 5120), "r"(need & (1u << i)) : "memory");
#pragma unroll
        for (int i = 0; i < 8; i++) {
          bool ok = ((v[i].x & v[i].y & v[i].z & v[i].w & 1u) == tag) && (((v[i].x | v[i].y | v[i].z | v[i].w) & 1u) == tag);
          if (__all_sync(~0u, ok)) need &= ~(1u << i);
        }
      } while (need && ++n < (1 << 18));
      float m[4] = {};
#pragma unroll
      for (int i = 0; i < 8; i++) { m[0] += __uint_as_float(v[i].x); m[1] += __uint_as_float(v[i].y); m[2] += __uint_as_float(v[i].z); m[3] += __uint_as_float(v[i].w); }
      __syncwarp();
      CP(12);
      uint32_t b0 = movm(pack_bf16(m[0], m[1])), b1 = movm(pack_bf16(m[2], m[3]));
      const uint32_t off = CH_MEM + (r * 4 + warp) * 256 + g * 16 + t * 4;
      const uint32_t cl0 = mapa_v(sb, 0), clstep = mapa_v(sb, 1) - cl0;
#pragma unroll
      for (int d = 0; d < 8; d++) { st_async1(cl0 + d * clstep + off, b0, cl0 + d * clstep + CH_BAR); st_async1(cl0 + d * clstep + off + 128, b1, cl0 + d * clstep + CH_BAR); }
    } else if (warp == 6) {
      const float* pb = pbase - lane * 4 + (32 + (r & ~1u)) * 128 + lane * 4 + (r & 1) * 2;
      uint2 v[16]; int n = 0; uint32_t need = 0xFF;
#pragma unroll
      for (int i = 0; i < 16; i++) v[i] = make_uint2(0, 0);
      do {
#pragma unroll
        for (int i = 0; i < 16; i++)
          asm volatile("{\n.reg .pred p;\nsetp.ne.b32 p, %3, 0;\n@p ld.relaxed.gpu.global.v2.b32 {%0,%1}, [%2];\n}" : "+r"(v[i].x), "+r"(v[i].y) : "l"(pb + (i >> 1) * 5120 + (i & 1) * 128), "r"(need & (1u << (i >> 1))) : "memory");
#pragma unroll
        for (int i = 0; i < 16; i += 2) {
          bool ok = ((v[i].x & v[i].y & v[i + 1].x & v[i + 1].y & 1u) == tag) && (((v[i].x | v[i].y | v[i + 1].x | v[i + 1].y) & 1u) == tag);
          if (__all_sync(~0u, ok)) need &= ~(1u << (i >> 1));
        }
      } while (need && ++n < (1 << 18));
      float m0 = 0.f, m1 = 0.f;
#pragma unroll
      for (int i = 0; i < 16; i++) { m0 += __uint_as_float(v[i].x); m1 += __uint_as_float(v[i].y); }
      __syncwarp();
      uint32_t b0 = movm(pack_bf16(m0, m1));
      const uint32_t off = CH_MEM + (32 + (r >> 1)) * 256 + (r & 1) * 128 + g * 16 + t * 4;
      const uint32_t cl0 = mapa_v(sb, 0), clstep = mapa_v(sb, 1) - cl0;
#pragma unroll
      for (int d = 0; d < 8; d++) st_async1(cl0 + d * clstep + off, b0, cl0 + d * clstep + CH_BAR);
    }
  }
  BAR_ALL();
  if (tid == 0) { __threadfence(); atomicAdd(&g_cnt[96 + NSEG - 1], 1); }
  if (blockIdx.x == 0 && tid == 0) PT(8);
  cluster_sync();
}
typedef CUresult (*EncodeFn)(CUtensorMap*, CUtensorMapDataType, cuuint32_t, void*, const cuuint64_t*, const cuuint64_t*, const cuuint32_t*, const cuuint32_t*,
                             CUtensorMapInterleave, CUtensorMapSwizzle, CUtensorMapL2promotion, CUtensorMapFloatOOBfill);
static EncodeFn g_enc;
static void mkmap(CUtensorMap* m, const void* ptr, int rows, int cols, int boxc, int boxr) {
  cuuint64_t dims[2] = {(cuuint64_t)cols, (cuuint64_t)rows}, strides[1] = {(cuuint64_t)cols * 2};
  cuuint32_t box[2] = {(cuuint32_t)boxc, (cuuint32_t)boxr}, es[2] = {1, 1};
  g_enc(m, CU_TENSOR_MAP_DATA_TYPE_BFLOAT16, 2, (void*)ptr, dims, strides, box, es, CU_TENSOR_MAP_INTERLEAVE_NONE, CU_TENSOR_MAP_SWIZZLE_128B,
        CU_TENSOR_MAP_L2_PROMOTION_L2_256B, CU_TENSOR_MAP_FLOAT_OOB_FILL_NONE);
}
#define URG 60.0
#define CHDT 3.7
constexpr int NATT = 112;
constexpr double CH_T0 = 24.0, CH_DT = CHDT;
static inline uint16_t mkjob(int type, int m, int n) { return (uint16_t)(type << 12 | m << 6 | n); }
static void schedule_side(GemmParams& p, const uint16_t* base, int nb, int ncl) {
  static const double cost[8] = {7.6, 7.6, 7.6, 19.5, 56.0, 33.0, 12.5, 7.0};
  double t[66]; int cnt[66] = {};
  for (int c = 0; c < 66; c++) t[c] = 9.0;
  p.stride = 960 / ncl;
  for (int i = 0; i < 960; i++) p.job[i] = 0xFFFF;
  double g2_end = 0, q_end[8] = {}, g3_end[8] = {}, at_end[8] = {}; int qn[8] = {}, g3n[8] = {}, atn[8] = {};
  int bi = 0, ai = 0, gi = 0;
  while (bi < nb || ai < NATT || gi < 60) {
    int b = -1;
    for (int c = 0; c < ncl; c++) if (cnt[c] < p.stride && (b < 0 || t[c] < t[b] || (t[c] == t[b] && cnt[c] < cnt[b]))) b = c;
    const double inf = 1e30;
    int am = ai >> 4, gm = gi < 12 ? gi / 3 : 4 + (gi - 12) / 24;
    double ra = ai < NATT && qn[am] == 16 ? (q_end[am] > CH_T0 + CH_DT * (am * 8 + ((ai & 15) >> 1) + 2) ? q_end[am] : CH_T0 + CH_DT * (am * 8 + ((ai & 15) >> 1) + 2)) : inf;
    double rg = gi < 60 && atn[gm] == 16 && g3n[gm] == 3 ? (at_end[gm] > g3_end[gm] - 30 ? at_end[gm] : g3_end[gm] - 30) : inf;
    bool urgent = bi < nb && (base[bi] >> 12) >= 1 && (base[bi] >> 12) <= 2 && CH_T0 + CH_DT * 8 * ((base[bi] >> 6) & 63) - t[b] < URG;
    uint16_t job; double start = t[b];
    if (urgent) job = base[bi++];
    else if (rg <= t[b] || (bi >= nb && rg < inf && (rg <= ra || (gi < 60 && ai >= NATT)))) { job = gi < 12 ? mkjob(5, gm, gi % 3) : mkjob(7, gm, (gi - 12) % 24); gi++; if (rg > start) start = rg; }
    else if (ai < NATT && (ra <= t[b] || bi >= nb)) { job = mkjob(6, am, ai & 15); ai++; if (ra > start) start = ra; }
    else job = base[bi++];
    int ty = job >> 12, m = (job >> 6) & 63;
    if (ty == 4 && start < g2_end) start = g2_end;
    t[b] = start + cost[ty];
    if (ty == 3 && t[b] > g2_end) g2_end = t[b];
    if (ty == 0) { qn[m]++; if (t[b] > q_end[m]) q_end[m] = t[b]; }
    if (ty == 4) { g3n[m]++; if (t[b] > g3_end[m]) g3_end[m] = t[b]; }
    if (ty == 6) { atn[m]++; if (t[b] > at_end[m]) at_end[m] = t[b]; }
    p.job[b * p.stride + cnt[b]++] = job;
  }
}
template <class... A>
static void launch(void (*k)(A...), int grid, int block, int smem, int cluster, bool pdl, A... a) {
  cudaLaunchConfig_t c = {};
  c.gridDim = grid; c.blockDim = block; c.dynamicSmemBytes = smem; c.stream = cudaStreamPerThread;
  cudaLaunchAttribute at[2]; int n = 0;
  if (cluster > 1) { at[n].id = cudaLaunchAttributeClusterDimension; at[n].val.clusterDim.x = cluster; at[n].val.clusterDim.y = 1; at[n].val.clusterDim.z = 1; n++; }
  if (pdl) { at[n].id = cudaLaunchAttributeProgrammaticStreamSerialization; at[n].val.programmaticStreamSerializationAllowed = 1; n++; }
  c.attrs = at; c.numAttrs = n;
  cudaLaunchKernelEx(&c, k, a...);
}

extern "C" void kernel_launch(void* const* d_in, const int* in_sizes, int n_in, void* d_out, int out_size) {
  const bf16 *x = (const bf16*)d_in[0], *mem0 = (const bf16*)d_in[1], *Wq = (const bf16*)d_in[2], *Wk = (const bf16*)d_in[3], *Wv = (const bf16*)d_in[4],
             *Wo = (const bf16*)d_in[5], *w1 = (const bf16*)d_in[8], *b1 = (const bf16*)d_in[9], *w2 = (const bf16*)d_in[10], *b2 = (const bf16*)d_in[11];
  static bool init = false;
  static GemmParams side, post;
  if (!init) {
    init = true;
    cudaDriverEntryPointQueryResult qr;
    cudaGetDriverEntryPoint("cuTensorMapEncodeTiled", (void**)&g_enc, cudaEnableDefault, &qr);
    void *xn, *h2, *o, *ut;
    cudaGetSymbolAddress(&xn, g_xn); cudaGetSymbolAddress(&h2, g_h2); cudaGetSymbolAddress(&o, g_o); cudaGetSymbolAddress(&ut, g_ut);
    GemmParams b = {};
    mkmap(&b.mA[0], xn, S_, D_, 64, 128); mkmap(&b.mA[1], w1, S_, F_, 64, 64); mkmap(&b.mA[2], w2, F_, S_, 64, 64); mkmap(&b.mA[3], o, S_, HD_, 64, 128);
    mkmap(&b.mB[0], Wq, D_, HD_, 64, 32); mkmap(&b.mB[1], Wk, D_, HD_, 64, 32); mkmap(&b.mB[2], Wv, D_, HD_, 64, 32);
    mkmap(&b.mB[3], h2, S_, D_, 64, 32); mkmap(&b.mB[4], ut, F_, D_, 64, 32); mkmap(&b.mB[5], Wo, HD_, D_, 64, 32);
    b.x = x; b.b1 = b1; b.b2 = b2; b.out = (bf16*)d_out;
    side = b; post = b; side.kid = 1; post.kid = 2;
    static uint16_t jl[1024]; int n = 0;
    auto kv = [&](int m) { for (int j = 0; j < 16; j++) { jl[n++] = mkjob(1, m, j); jl[n++] = mkjob(2, m, j); } };
    auto qq = [&](int m) { for (int j = 0; j < 16; j++) jl[n++] = mkjob(0, m, j); };
    kv(0); kv(1);
    for (int m = 0; m < 18; m++) for (int j = 0; j < 3; j++) jl[n++] = mkjob(3, m, j);
    kv(2); qq(0); kv(3); qq(1);
    for (int m = 0; m < 8; m++) for (int j = 0; j < 3; j++) jl[n++] = mkjob(4, m, j);
    for (int m = 4; m < 8; m++) { kv(m); qq(m - 2); }
    qq(6); qq(7);
    schedule_side(side, jl, n, 34);
    side.wait_at_end = 0;
    post.stride = 2;
    for (int i = 0; i < 960; i++) post.job[i] = 0xFFFF;
    for (int i = 0; i < 48; i++) {
      const uint16_t g4 = i < 24 ? mkjob(7, 7, i) : mkjob(7, 6, i - 24);
      if (i < 16) { post.job[i * 2] = mkjob(6, 7, 15 - i); post.job[i * 2 + 1] = g4; }
      else post.job[i * 2] = g4;
    }
    cudaFuncSetAttribute(gemm_kernel, cudaFuncAttributeMaxDynamicSharedMemorySize, GEMM_SMEM);
    cudaFuncSetAttribute(chain_kernel, cudaFuncAttributeMaxDynamicSharedMemorySize, CHAIN_SMEM);
  }
  launch(ln_kernel, 256, 256, 0, 1, false, x);
  launch(chain_kernel, 64, 256, CHAIN_SMEM, 8, false, mem0, Wq, Wk, Wv, Wo);
  launch(gemm_kernel, 68, 384, GEMM_SMEM, 2, true, side);
  launch(gemm_kernel, 96, 384, GEMM_SMEM, 2, true, post);
}
```

```cpp
#include <cuda_runtime.h>
#include <cuda_bf16.h>
#include <cuda.h>
#include <stdint.h>

typedef __nv_bfloat16 bf16;
constexpr int S_ = 2048, D_ = 576, HD_ = 4096, F_ = 4608, NSEG = 64;

__device__ bf16 g_xn[S_ * D_];
__device__ bf16 g_h2[S_ * D_];
__device__ bf16 g_q[S_ * HD_];
__device__ bf16 g_k[S_ * HD_];
__device__ bf16 g_v[S_ * HD_];
__device__ bf16 g_o[S_ * HD_];
__device__ bf16 g_km[NSEG * 8 * HD_];
__device__ bf16 g_vm[NSEG * 8 * HD_];
__device__ bf16 g_ut[F_ * D_];
__device__ float g_yb[S_ * D_];
__device__ float g_pk[8 * 512 * D_];
__device__ float g_part[2 * 8 * 8 * 5 * 32 * 4];
__device__ unsigned int g_cnt[192];

#define PT(i)
#define PC(i)
__device__ __forceinline__ uint32_t smem_u32(const void* p) { return (uint32_t)__cvta_generic_to_shared(p); }
__device__ __forceinline__ void mbar_init(uint32_t b, uint32_t c) { asm volatile("mbarrier.init.shared::cta.b64 [%0], %1;" ::"r"(b), "r"(c)); }
__device__ __forceinline__ void mbar_expect(uint32_t b, uint32_t bytes) { asm volatile("mbarrier.arrive.expect_tx.shared::cta.b64 _, [%0], %1;" ::"r"(b), "r"(bytes) : "memory"); }
__device__ __forceinline__ void mbar_wait(uint32_t b, uint32_t parity) {
  uint32_t ok;
  do { asm volatile("{\n.reg .pred p;\nmbarrier.try_wait.parity.shared::cta.b64 p, [%1], %2;\nselp.u32 %0, 1, 0, p;\n}" : "=r"(ok) : "r"(b), "r"(parity) : "memory"); } while (!ok);
}
__device__ __forceinline__ void mbar_wait_cl(uint32_t b, uint32_t parity) {
  uint32_t ok;
  do { asm volatile("{\n.reg .pred p;\nmbarrier.try_wait.parity.shared::cta.b64 p, [%1], %2;\nselp.u32 %0, 1, 0, p;\n}" : "=r"(ok) : "r"(b), "r"(parity) : "memory"); } while (!ok);
}
__device__ __forceinline__ uint32_t mapa(uint32_t a, uint32_t r) { uint32_t o; asm("mapa.shared::cluster.u32 %0, %1, %2;" : "=r"(o) : "r"(a), "r"(r)); return o; }
__device__ __forceinline__ void mbar_arrive_remote(uint32_t remote_b) { asm volatile("mbarrier.arrive.shared::cluster.b64 _, [%0];" ::"r"(remote_b) : "memory"); }
__device__ __forceinline__ uint32_t cluster_rank() { uint32_t r; asm("mov.u32 %0, %%cluster_ctarank;" : "=r"(r)); return r; }
__device__ __forceinline__ void cluster_sync() { asm volatile("barrier.cluster.arrive.release.aligned;\nbarrier.cluster.wait.acquire.aligned;" ::: "memory"); }
__device__ __forceinline__ void tma2d(uint32_t dst, const CUtensorMap* m, int c0, int c1, uint32_t bar) {
  asm volatile("cp.async.bulk.tensor.2d.shared::cluster.global.mbarrier::complete_tx::bytes [%0], [%1, {%3, %4}], [%2];"
               ::"r"(dst), "l"(m), "r"(bar), "r"(c0), "r"(c1) : "memory");
}
__device__ __forceinline__ void tma2d_mc(uint32_t dst, const CUtensorMap* m, int c0, int c1, uint32_t bar, uint16_t mask) {
  asm volatile("cp.async.bulk.tensor.2d.shared::cluster.global.mbarrier::complete_tx::bytes.multicast::cluster [%0], [%1, {%3, %4}], [%2], %5;"
               ::"r"(dst), "l"(m), "r"(bar), "r"(c0), "r"(c1), "h"(mask) : "memory");
}
__device__ __forceinline__ uint32_t pack_bf16(float a, float b) { __nv_bfloat162 t = __floats2bfloat162_rn(a, b); return *(uint32_t*)&t; }
__device__ __forceinline__ float2 unpack_bf16(uint32_t u) { return __bfloat1622float2(*(__nv_bfloat162*)&u); }
__device__ __forceinline__ void mma16816(float (&c)[4], const uint32_t (&a)[4], uint32_t b0, uint32_t b1) {
  asm volatile("mma.sync.aligned.m16n8k16.row.col.f32.bf16.bf16.f32 {%0,%1,%2,%3},{%4,%5,%6,%7},{%8,%9},{%0,%1,%2,%3};"
               : "+f"(c[0]), "+f"(c[1]), "+f"(c[2]), "+f"(c[3]) : "r"(a[0]), "r"(a[1]), "r"(a[2]), "r"(a[3]), "r"(b0), "r"(b1));
}
__device__ __forceinline__ void ldsm4(uint32_t (&r)[4], uint32_t a) { asm volatile("ldmatrix.sync.aligned.m8n8.x4.shared.b16 {%0,%1,%2,%3},[%4];" : "=r"(r[0]), "=r"(r[1]), "=r"(r[2]), "=r"(r[3]) : "r"(a) : "memory"); }
__device__ __forceinline__ void ldsm4t(uint32_t (&r)[4], uint32_t a) { asm volatile("ldmatrix.sync.aligned.m8n8.x4.trans.shared.b16 {%0,%1,%2,%3},[%4];" : "=r"(r[0]), "=r"(r[1]), "=r"(r[2]), "=r"(r[3]) : "r"(a) : "memory"); }
__device__ __forceinline__ uint32_t movm(uint32_t a) { uint32_t o; asm volatile("movmatrix.sync.aligned.m8n8.trans.b16 %0, %1;" : "=r"(o) : "r"(a)); return o; }
__device__ __forceinline__ void cp16(uint32_t dst, const void* src) { asm volatile("cp.async.cg.shared.global [%0], [%1], 16;" ::"r"(dst), "l"(src) : "memory"); }
__device__ __forceinline__ void pdl_wait() { asm volatile("griddepcontrol.wait;" ::: "memory"); }
__device__ __forceinline__ void pdl_launch() { asm volatile("griddepcontrol.launch_dependents;" ::: "memory"); }

__device__ __forceinline__ void wait_cnt(const unsigned int* c, unsigned int target) {
  uint32_t v; int n = 0;
  do { asm volatile("ld.acquire.gpu.global.u32 %0, [%1];" : "=r"(v) : "l"(c) : "memory"); if (v >= target) break; __nanosleep(64); } while (++n < (1 << 22));
}
__global__ void __launch_bounds__(256) ln_kernel(const bf16* __restrict__ x) {
  int row = blockIdx.x * 8 + (threadIdx.x >> 5), lane = threadIdx.x & 31;
  if (blockIdx.x == 0 && threadIdx.x < 192) { g_cnt[threadIdx.x] = 0; if (threadIdx.x == 0) PT(0); }
  for (int i = blockIdx.x * 256 + threadIdx.x; i < 2 * 64 * 640; i += 256 * 256) g_part[i] = 0.f;
  const uint32_t* xr = (const uint32_t*)(x + (size_t)row * D_);
  float v[18]; float s = 0.f;
#pragma unroll
  for (int i = 0; i < 9; i++) { float2 f = unpack_bf16(xr[lane + 32 * i]); v[2 * i] = f.x; v[2 * i + 1] = f.y; s += f.x + f.y; }
#pragma unroll
  for (int pass = 0; pass < 2; pass++) {
#pragma unroll
    for (int o = 16; o; o >>= 1) s += __shfl_xor_sync(~0u, s, o);
    float m = s * (1.f / D_), q = 0.f;
#pragma unroll
    for (int i = 0; i < 18; i++) { v[i] -= m; q += v[i] * v[i]; }
#pragma unroll
    for (int o = 16; o; o >>= 1) q += __shfl_xor_sync(~0u, q, o);
    float r = 1.f / sqrtf(q * (1.f / D_) + 1e-5f);
    uint32_t* dst = (uint32_t*)((pass == 0 ? g_xn : g_h2) + (size_t)row * D_);
    s = 0.f;
#pragma unroll
    for (int i = 0; i < 9; i++) {
      uint32_t p = pack_bf16(v[2 * i] * r, v[2 * i + 1] * r);
      dst[lane + 32 * i] = p;
      float2 f = unpack_bf16(p); v[2 * i] = f.x; v[2 * i + 1] = f.y; s += f.x + f.y;
    }
  }
}

template<int TA> __device__ __forceinline__ void wgmma_n256(float (&d)[128], uint64_t da, uint64_t db, int sc) {
  asm volatile("{\n.reg .pred p;\nsetp.ne.b32 p, %130, 0;\n"
    "wgmma.mma_async.sync.aligned.m64n256k16.f32.bf16.bf16 {%0, %1, %2, %3, %4, %5, %6, %7, %8, %9, %10, %11, %12, %13, %14, %15, %16, %17, %18, %19, %20, %21, %22, %23, %24, %25, %26, %27, %28, %29, %30, %31, %32, %33, %34, %35, %36, %37, %38, %39, %40, %41, %42, %43, %44, %45, %46, %47, %48, %49, %50, %51, %52, %53, %54, %55, %56, %57, %58, %59, %60, %61, %62, %63, %64, %65, %66, %67, %68, %69, %70, %71, %72, %73, %74, %75, %76, %77, %78, %79, %80, %81, %82, %83, %84, %85, %86, %87, %88, %89, %90, %91, %92, %93, %94, %95, %96, %97, %98, %99, %100, %101, %102, %103, %104, %105, %106, %107, %108, %109, %110, %111, %112, %113, %114, %115, %116, %117, %118, %119, %120, %121, %122, %123, %124, %125, %126, %127}, %128, %129, p, 1, 1, %131, 1;\n}\n"
    : "+f"(d[0]), "+f"(d[1]), "+f"(d[2]), "+f"(d[3]), "+f"(d[4]), "+f"(d[5]), "+f"(d[6]), "+f"(d[7]), "+f"(d[8]), "+f"(d[9]), "+f"(d[10]), "+f"(d[11]), "+f"(d[12]), "+f"(d[13]), "+f"(d[14]), "+f"(d[15]), "+f"(d[16]), "+f"(d[17]), "+f"(d[18]), "+f"(d[19]), "+f"(d[20]), "+f"(d[21]), "+f"(d[22]), "+f"(d[23]), "+f"(d[24]), "+f"(d[25]), "+f"(d[26]), "+f"(d[27]), "+f"(d[28]), "+f"(d[29]), "+f"(d[30]), "+f"(d[31]), "+f"(d[32]), "+f"(d[33]), "+f"(d[34]), "+f"(d[35]), "+f"(d[36]), "+f"(d[37]), "+f"(d[38]), "+f"(d[39]), "+f"(d[40]), "+f"(d[41]), "+f"(d[42]), "+f"(d[43]), "+f"(d[44]), "+f"(d[45]), "+f"(d[46]), "+f"(d[47]), "+f"(d[48]), "+f"(d[49]), "+f"(d[50]), "+f"(d[51]), "+f"(d[52]), "+f"(d[53]), "+f"(d[54]), "+f"(d[55]), "+f"(d[56]), "+f"(d[57]), "+f"(d[58]), "+f"(d[59]), "+f"(d[60]), "+f"(d[61]), "+f"(d[62]), "+f"(d[63]), "+f"(d[64]), "+f"(d[65]), "+f"(d[66]), "+f"(d[67]), "+f"(d[68]), "+f"(d[69]), "+f"(d[70]), "+f"(d[71]), "+f"(d[72]), "+f"(d[73]), "+f"(d[74]), "+f"(d[75]), "+f"(d[76]), "+f"(d[77]), "+f"(d[78]), "+f"(d[79]), "+f"(d[80]), "+f"(d[81]), "+f"(d[82]), "+f"(d[83]), "+f"(d[84]), "+f"(d[85]), "+f"(d[86]), "+f"(d[87]), "+f"(d[88]), "+f"(d[89]), "+f"(d[90]), "+f"(d[91]), "+f"(d[92]), "+f"(d[93]), "+f"(d[94]), "+f"(d[95]), "+f"(d[96]), "+f"(d[97]), "+f"(d[98]), "+f"(d[99]), "+f"(d[100]), "+f"(d[101]), "+f"(d[102]), "+f"(d[103]), "+f"(d[104]), "+f"(d[105]), "+f"(d[106]), "+f"(d[107]), "+f"(d[108]), "+f"(d[109]), "+f"(d[110]), "+f"(d[111]), "+f"(d[112]), "+f"(d[113]), "+f"(d[114]), "+f"(d[115]), "+f"(d[116]), "+f"(d[117]), "+f"(d[118]), "+f"(d[119]), "+f"(d[120]), "+f"(d[121]), "+f"(d[122]), "+f"(d[123]), "+f"(d[124]), "+f"(d[125]), "+f"(d[126]), "+f"(d[127])
    : "l"(da), "l"(db), "r"(sc), "n"(TA));
}

template<int TA> __device__ __forceinline__ void wgmma_n192(float (&d)[128], uint64_t da, uint64_t db, int sc) {
  asm volatile("{\n.reg .pred p;\nsetp.ne.b32 p, %98, 0;\n"
    "wgmma.mma_async.sync.aligned.m64n192k16.f32.bf16.bf16 {%0, %1, %2, %3, %4, %5, %6, %7, %8, %9, %10, %11, %12, %13, %14, %15, %16, %17, %18, %19, %20, %21, %22, %23, %24, %25, %26, %27, %28, %29, %30, %31, %32, %33, %34, %35, %36, %37, %38, %39, %40, %41, %42, %43, %44, %45, %46, %47, %48, %49, %50, %51, %52, %53, %54, %55, %56, %57, %58, %59, %60, %61, %62, %63, %64, %65, %66, %67, %68, %69, %70, %71, %72, %73, %74, %75, %76, %77, %78, %79, %80, %81, %82, %83, %84, %85, %86, %87, %88, %89, %90, %91, %92, %93, %94, %95}, %96, %97, p, 1, 1, %99, 1;\n}\n"
    : "+f"(d[0]), "+f"(d[1]), "+f"(d[2]), "+f"(d[3]), "+f"(d[4]), "+f"(d[5]), "+f"(d[6]), "+f"(d[7]), "+f"(d[8]), "+f"(d[9]), "+f"(d[10]), "+f"(d[11]), "+f"(d[12]), "+f"(d[13]), "+f"(d[14]), "+f"(d[15]), "+f"(d[16]), "+f"(d[17]), "+f"(d[18]), "+f"(d[19]), "+f"(d[20]), "+f"(d[21]), "+f"(d[22]), "+f"(d[23]), "+f"(d[24]), "+f"(d[25]), "+f"(d[26]), "+f"(d[27]), "+f"(d[28]), "+f"(d[29]), "+f"(d[30]), "+f"(d[31]), "+f"(d[32]), "+f"(d[33]), "+f"(d[34]), "+f"(d[35]), "+f"(d[36]), "+f"(d[37]), "+f"(d[38]), "+f"(d[39]), "+f"(d[40]), "+f"(d[41]), "+f"(d[42]), "+f"(d[43]), "+f"(d[44]), "+f"(d[45]), "+f"(d[46]), "+f"(d[47]), "+f"(d[48]), "+f"(d[49]), "+f"(d[50]), "+f"(d[51]), "+f"(d[52]), "+f"(d[53]), "+f"(d[54]), "+f"(d[55]), "+f"(d[56]), "+f"(d[57]), "+f"(d[58]), "+f"(d[59]), "+f"(d[60]), "+f"(d[61]), "+f"(d[62]), "+f"(d[63]), "+f"(d[64]), "+f"(d[65]), "+f"(d[66]), "+f"(d[67]), "+f"(d[68]), "+f"(d[69]), "+f"(d[70]), "+f"(d[71]), "+f"(d[72]), "+f"(d[73]), "+f"(d[74]), "+f"(d[75]), "+f"(d[76]), "+f"(d[77]), "+f"(d[78]), "+f"(d[79]), "+f"(d[80]), "+f"(d[81]), "+f"(d[82]), "+f"(d[83]), "+f"(d[84]), "+f"(d[85]), "+f"(d[86]), "+f"(d[87]), "+f"(d[88]), "+f"(d[89]), "+f"(d[90]), "+f"(d[91]), "+f"(d[92]), "+f"(d[93]), "+f"(d[94]), "+f"(d[95])
    : "l"(da), "l"(db), "r"(sc), "n"(TA));
}

struct GemmParams {
  CUtensorMap mA[4];
  CUtensorMap mB[6];
  const bf16* x; const bf16* b1; const bf16* b2; bf16* out;
  int stride, kid;
  int wait_at_end;
  uint16_t job[960];
};
constexpr int NSTAGE = 4, STAGE_BYTES = 49152;
constexpr int GEMM_SMEM = NSTAGE * STAGE_BYTES + 8 * 2048 + 256 + 1024;

__device__ __forceinline__ uint64_t mkdesc(uint32_t addr, uint32_t lbo, uint32_t sbo) {
  return (uint64_t)((addr & 0x3FFFF) >> 4) | ((uint64_t)(lbo >> 4) << 16) | ((uint64_t)(sbo >> 4) << 32) | (1ull << 62);
}
__device__ __forceinline__ void red_release(unsigned int* c) { asm volatile("red.release.gpu.global.add.u32 [%0], 1;" ::"l"(c) : "memory"); }
__device__ __forceinline__ float gelu_tanh(float u) {
  float z = 0.7978845608028654f * (u + 0.044715f * u * u * u);
  float e = __expf(2.f * z);
  float th = 1.f - __fdividef(2.f, e + 1.f);
  return 0.5f * u * (1.f + th);
}
template <int BN, int TA>
__device__ __forceinline__ void gemm_mainloop(float (&d)[128], int kiters, uint32_t sbase, uint32_t fullb, uint32_t emptyb_l, uint32_t emptyb_r,
                                              int wg, int& stage, uint32_t& phase, bool elect) {
  int prev = -1;
  for (int k = 0; k < kiters; k++) {
    mbar_wait(fullb + stage * 8, phase);
    uint32_t a = sbase + stage * STAGE_BYTES + wg * 8192, b = sbase + stage * STAGE_BYTES + 16384;
    asm volatile("wgmma.fence.sync.aligned;" ::: "memory");
#pragma unroll
    for (int kk = 0; kk < 4; kk++) {
      uint64_t da = TA ? mkdesc(a + kk * 2048, 8192, 1024) : mkdesc(a + kk * 32, 16, 1024);
      uint64_t db = mkdesc(b + kk * 2048, 8192, 1024);
      if constexpr (BN == 256) wgmma_n256<TA>(d, da, db, (k | kk) != 0); else wgmma_n192<TA>(d, da, db, (k | kk) != 0);
    }
    asm volatile("wgmma.commit_group.sync.aligned;" ::: "memory");
    asm volatile("wgmma.wait_group.sync.aligned 1;" ::: "memory");
    if (prev >= 0 && elect) { mbar_arrive_remote(emptyb_l + prev * 8); mbar_arrive_remote(emptyb_r + prev * 8); }
    prev = stage;
    if (++stage == NSTAGE) { stage = 0; phase ^= 1; }
  }
  asm volatile("wgmma.wait_group.sync.aligned 0;" ::: "memory");
  if (elect) { mbar_arrive_remote(emptyb_l + prev * 8); mbar_arrive_remote(emptyb_r + prev * 8); }
}
template <int BN, class F>
__device__ __forceinline__ void store_tile(const float (&d)[128], uint32_t stg, bf16* dst, int ld, int lane, F f) {
#pragma unroll
  for (int c = 0; c < BN / 64; c++) {
#pragma unroll
    for (int i = 0; i < 8; i += 2) {
      const int o = c * 32 + i * 4;
      uint32_t r0 = f(d[o], d[o + 1], 0, c * 64 + i * 8), r1 = f(d[o + 2], d[o + 3], 1, c * 64 + i * 8);
      uint32_t r2 = f(d[o + 4], d[o + 5], 0, c * 64 + i * 8 + 8), r3 = f(d[o + 6], d[o + 7], 1, c * 64 + i * 8 + 8);
      int m = lane >> 3, row = (m & 1) * 8 + (lane & 7), ch = (i + (m >> 1)) ^ (row & 7);
      asm volatile("stmatrix.sync.aligned.m8n8.x4.shared.b16 [%0], {%1,%2,%3,%4};" ::"r"(stg + row * 128 + ch * 16), "r"(r0), "r"(r1), "r"(r2), "r"(r3) : "memory");
    }
    __syncwarp();
#pragma unroll
    for (int j = 0; j < 4; j++) {
      int idx = lane + 32 * j, row = idx >> 3, ch = idx & 7;
      uint4 v;
      asm volatile("ld.shared.v4.u32 {%0,%1,%2,%3}, [%4];" : "=r"(v.x), "=r"(v.y), "=r"(v.z), "=r"(v.w) : "r"(stg + row * 128 + ((ch ^ (row & 7)) * 16)));
      *(uint4*)(dst + (size_t)row * ld + c * 64 + ch * 8) = v;
    }
    __syncwarp();
  }
}

__device__ __forceinline__ void attn_unit(int seg, int h, uint8_t* sm, int lane, const unsigned int* segflag) {
  const int g = lane >> 2, t = lane & 3;
  const uint32_t sv = smem_u32(sm);
  const size_t tok0 = (size_t)seg * 32;
  for (int i = 128 + lane; i < 40 * 16; i += 32) {
    int r = i >> 4, c = i & 15;
    cp16(sv + r * 256 + ((c ^ (r & 7)) * 16), g_v + (tok0 + r - 8) * HD_ + h * 128 + c * 8);
  }
  for (int i = lane; i < 8 * 16; i += 32) *(uint4*)(sm + 40 * 256 + i * 16) = make_uint4(0, 0, 0, 0);
  asm volatile("cp.async.commit_group;" ::: "memory");
  float s[2][5][4];
#pragma unroll
  for (int m = 0; m < 2; m++)
#pragma unroll
    for (int n = 0; n < 5; n++) { s[m][n][0] = s[m][n][1] = s[m][n][2] = s[m][n][3] = 0.f; }
#pragma unroll
  for (int j = 0; j < 4; j++) {
    uint4 qa[2][2], kb[5];
#pragma unroll
    for (int m = 0; m < 2; m++)
#pragma unroll
      for (int hh = 0; hh < 2; hh++) qa[m][hh] = *(const uint4*)(g_q + (tok0 + m * 16 + hh * 8 + g) * HD_ + h * 128 + j * 32 + t * 8);
#pragma unroll
    for (int n = 1; n < 5; n++) kb[n] = *(const uint4*)(g_k + (tok0 + (n - 1) * 8 + g) * HD_ + h * 128 + j * 32 + t * 8);
#pragma unroll
    for (int m = 0; m < 2; m++) {
      uint32_t a0[4] = {qa[m][0].x, qa[m][1].x, qa[m][0].y, qa[m][1].y}, a1[4] = {qa[m][0].z, qa[m][1].z, qa[m][0].w, qa[m][1].w};
#pragma unroll
      for (int n = 1; n < 5; n++) { mma16816(s[m][n], a0, kb[n].x, kb[n].y); mma16816(s[m][n], a1, kb[n].z, kb[n].w); }
    }
  }
  if (lane == 0) wait_cnt(segflag, 64);
  __syncwarp();
  for (int i = lane; i < 128; i += 32) {
    int r = i >> 4, c = i & 15;
    cp16(sv + r * 256 + ((c ^ (r & 7)) * 16), g_vm + ((size_t)seg * 8 + r) * HD_ + h * 128 + c * 8);
  }
  asm volatile("cp.async.commit_group;" ::: "memory");
  {
    uint4 km[4], qa[4][2][2];
#pragma unroll
    for (int j = 0; j < 4; j++) {
      km[j] = __ldcg((const uint4*)(g_km + ((size_t)seg * 8 + g) * HD_ + h * 128 + j * 32 + t * 8));
#pragma unroll
      for (int m = 0; m < 2; m++)
#pragma unroll
        for (int hh = 0; hh < 2; hh++) qa[j][m][hh] = *(const uint4*)(g_q + (tok0 + m * 16 + hh * 8 + g) * HD_ + h * 128 + j * 32 + t * 8);
    }
#pragma unroll
    for (int j = 0; j < 4; j++)
#pragma unroll
      for (int m = 0; m < 2; m++) {
        uint32_t a0[4] = {qa[j][m][0].x, qa[j][m][1].x, qa[j][m][0].y, qa[j][m][1].y}, a1[4] = {qa[j][m][0].z, qa[j][m][1].z, qa[j][m][0].w, qa[j][m][1].w};
        mma16816(s[m][0], a0, km[j].x, km[j].y); mma16816(s[m][0], a1, km[j].z, km[j].w);
      }
  }
  const float sc = 0.08838834764831845f * 1.4426950408889634f;
  uint32_t pa[2][3][4];
#pragma unroll
  for (int m = 0; m < 2; m++) {
    float inv[2];
#pragma unroll
    for (int hh = 0; hh < 2; hh++) {
      int qi = 8 + m * 16 + hh * 8 + g;
      float mx = -INFINITY;
#pragma unroll
      for (int n = 0; n < 5; n++)
#pragma unroll
        for (int e = 0; e < 2; e++) { float& z = s[m][n][hh * 2 + e]; z = (n * 8 + t * 2 + e <= qi) ? z * sc : -INFINITY; mx = fmaxf(mx, z); }
      mx = fmaxf(mx, __shfl_xor_sync(~0u, mx, 1)); mx = fmaxf(mx, __shfl_xor_sync(~0u, mx, 2));
      float sum = 0.f;
#pragma unroll
      for (int n = 0; n < 5; n++)
#pragma unroll
        for (int e = 0; e < 2; e++) { float& z = s[m][n][hh * 2 + e]; z = exp2f(z - mx); sum += z; }
      sum += __shfl_xor_sync(~0u, sum, 1); sum += __shfl_xor_sync(~0u, sum, 2);
      inv[hh] = 1.f / sum;
    }
#pragma unroll
    for (int kk = 0; kk < 3; kk++) {
      pa[m][kk][0] = pack_bf16(s[m][2 * kk][0] * inv[0], s[m][2 * kk][1] * inv[0]);
      pa[m][kk][1] = pack_bf16(s[m][2 * kk][2] * inv[1], s[m][2 * kk][3] * inv[1]);
      if (kk < 2) {
        pa[m][kk][2] = pack_bf16(s[m][2 * kk + 1][0] * inv[0], s[m][2 * kk + 1][1] * inv[0]);
        pa[m][kk][3] = pack_bf16(s[m][2 * kk + 1][2] * inv[1], s[m][2 * kk + 1][3] * inv[1]);
      } else { pa[m][kk][2] = 0; pa[m][kk][3] = 0; }
    }
  }
  asm volatile("cp.async.wait_group 0;" ::: "memory");
  __syncwarp();
  uint32_t ov[2][16][2];
#pragma unroll
  for (int np = 0; np < 8; np++) {
    float o[2][2][4] = {};
#pragma unroll
    for (int kk = 0; kk < 3; kk++) {
      uint32_t b[4];
      int mi = lane >> 3, r = kk * 16 + (mi & 1) * 8 + (lane & 7), c = np * 2 + (mi >> 1);
      ldsm4t(b, sv + r * 256 + ((c ^ (r & 7)) * 16));
#pragma unroll
      for (int m = 0; m < 2; m++) { mma16816(o[m][0], pa[m][kk], b[0], b[1]); mma16816(o[m][1], pa[m][kk], b[2], b[3]); }
    }
#pragma unroll
    for (int m = 0; m < 2; m++)
#pragma unroll
      for (int q = 0; q < 2; q++) { ov[m][np * 2 + q][0] = pack_bf16(o[m][q][0], o[m][q][1]); ov[m][np * 2 + q][1] = pack_bf16(o[m][q][2], o[m][q][3]); }
  }
  __syncwarp();
#pragma unroll
  for (int m = 0; m < 2; m++)
#pragma unroll
    for (int n = 0; n < 16; n++)
#pragma unroll
      for (int hh = 0; hh < 2; hh++) {
        int r = m * 16 + hh * 8 + g;
        *(uint32_t*)(sm + r * 256 + ((n ^ (r & 7)) * 16) + t * 4) = ov[m][n][hh];
      }
  __syncwarp();
#pragma unroll
  for (int i = 0; i < 16; i++) {
    int idx = lane + 32 * i, r = idx >> 4, c = idx & 15;
    *(uint4*)(g_o + (tok0 + r) * HD_ + h * 128 + c * 8) = *(const uint4*)(sm + r * 256 + ((c ^ (r & 7)) * 16));
  }
}

__global__ void __launch_bounds__(384, 1) gemm_kernel(const __grid_constant__ GemmParams p) {
  extern __shared__ uint8_t smem_raw[];
  const uint32_t sbase = (smem_u32(smem_raw) + 1023) & ~1023u;
  const uint32_t stg0 = sbase + NSTAGE * STAGE_BYTES, fullb = stg0 + 8 * 2048, emptyb = fullb + 64;
  const uint32_t rank = cluster_rank();
  const int wg = __shfl_sync(~0u, (int)(threadIdx.x >> 7), 0), lane = threadIdx.x & 31;
  const int cl = blockIdx.x >> 1;
  if (threadIdx.x == 0) {
    for (int i = 0; i < NSTAGE; i++) { mbar_init(fullb + i * 8, 1); mbar_init(emptyb + i * 8, 4); }
    asm volatile("fence.mbarrier_init.release.cluster;" ::: "memory");
  }
  cluster_sync();
  if (blockIdx.x == 0 && threadIdx.x == 0) PT(1 + p.kid * 2);
  const uint16_t* jobs = p.job + cl * p.stride;
  if (wg == 0) {
    asm volatile("setmaxnreg.dec.sync.aligned.u32 40;");
    if (threadIdx.x == 0) {
      int stage = 0; uint32_t phase = 1;
      for (int j = 0; j < p.stride; j++) {
        uint32_t job = jobs[j];
        if (job == 0xFFFF) break;
        int type = job >> 12, m = (job >> 6) & 63, n = job & 63;
        int row0 = m * 256 + rank * 128;
        int bn = type < 3 ? 256 : 192;
        if (type == 6) {
          for (int k = 0; k < NSTAGE; k++) {
            mbar_wait_cl(emptyb + stage * 8, phase);
            asm volatile("mbarrier.arrive.shared::cta.b64 _, [%0];" ::"r"(fullb + stage * 8) : "memory");
            if (++stage == NSTAGE) { stage = 0; phase ^= 1; }
          }
          continue;
        }
        int kit = type < 3 ? 9 : (type == 3 ? 32 : (type == 4 ? 72 : (type == 5 ? 64 : 8)));
        int k0 = 0;
        if (type == 7) { k0 = (n / 3) * 8; n = n % 3; type = 5; }
        if (type == 5) wait_cnt(&g_cnt[16 + m], 32);
        const CUtensorMap* ma = &p.mA[type < 3 ? 0 : type - 2];
        const CUtensorMap* mb = &p.mB[type];
        bool ta = (type == 3 || type == 4);
        if (type >= 4) {
          if (type == 4) wait_cnt(&g_cnt[0], 108);
          asm volatile("fence.proxy.async;" ::: "memory");
        }
        for (int k = k0; k < k0 + kit; k++) {
          mbar_wait_cl(emptyb + stage * 8, phase);
          uint32_t fb = fullb + stage * 8, a = sbase + stage * STAGE_BYTES, b = a + 16384;
          mbar_expect(fb, 16384 + bn * 128);
          if (ta) { tma2d(a, ma, row0, k * 64, fb); tma2d(a + 8192, ma, row0 + 64, k * 64, fb); }
          else tma2d(a, ma, k * 64, row0, fb);
          for (int i = 0; i < bn / 64; i++) tma2d_mc(b + i * 8192 + rank * 4096, mb, n * bn + i * 64, k * 64 + rank * 32, fb, (uint16_t)3);
          if (++stage == NSTAGE) { stage = 0; phase ^= 1; }
        }
      }
    }
    __syncwarp();
    pdl_launch();
    cluster_sync();
  } else {
    asm volatile("setmaxnreg.inc.sync.aligned.u32 232;");
    const int cw = wg - 1, warp = __shfl_sync(~0u, (int)(threadIdx.x >> 5) & 3, 0);
    const uint32_t eb_l = mapa(emptyb, rank), eb_r = mapa(emptyb, rank ^ 1);
    const uint32_t stg = stg0 + (cw * 4 + warp) * 2048;
    const bool elect = (threadIdx.x & 127) == 0;
    const int g = lane >> 2, t = lane & 3;
    int stage = 0; uint32_t phase = 0;
    float d[128];
    for (int j = 0; j < p.stride; j++) {
      uint32_t job = jobs[j];
      if (job == 0xFFFF) break;
      int type = job >> 12, m = (job >> 6) & 63, n = job & 63;
      int row0 = m * 256 + rank * 128 + cw * 64 + warp * 16;
      if (type < 3) {
        gemm_mainloop<256, 0>(d, 9, sbase, fullb, eb_l, eb_r, cw, stage, phase, elect);
        bf16* dst = (type == 0 ? g_q : (type == 1 ? g_k : g_v)) + (size_t)row0 * HD_ + n * 256;
        store_tile<256>(d, stg, dst, HD_, lane, [](float a, float b, int, int) { return pack_bf16(a, b); });
        asm volatile("bar.sync %0, 256;" ::"r"(1) : "memory");
        if (threadIdx.x == 128) asm volatile("red.release.gpu.global.add.u32 [%0], 1;" ::"l"(&g_cnt[(type ? 8 : 40) + m]) : "memory");
      } else if (type == 3) {
        gemm_mainloop<192, 1>(d, 32, sbase, fullb, eb_l, eb_r, cw, stage, phase, elect);
        float bb[2] = {__bfloat162float(p.b1[row0 + g]), __bfloat162float(p.b1[row0 + g + 8])};
        store_tile<192>(d, stg, g_ut + (size_t)row0 * D_ + n * 192, D_, lane,
                        [&](float a, float b, int h, int) { return pack_bf16(gelu_tanh(a + bb[h]), gelu_tanh(b + bb[h])); });
        asm volatile("fence.proxy.async;" ::: "memory");
        asm volatile("bar.sync %0, 256;" ::"r"(1) : "memory");
        if (threadIdx.x == 128) red_release(&g_cnt[0]);
      } else if (type == 4) {
        gemm_mainloop<192, 1>(d, 72, sbase, fullb, eb_l, eb_r, cw, stage, phase, elect);
        float bb[2] = {__bfloat162float(p.b2[row0 + g]), __bfloat162float(p.b2[row0 + g + 8])};
#pragma unroll
        for (int i = 0; i < 24; i++)
#pragma unroll
          for (int h = 0; h < 2; h++) {
            size_t off = (size_t)(row0 + g + h * 8) * D_ + n * 192 + i * 8 + t * 2;
            float2 xv = unpack_bf16(*(const uint32_t*)(p.x + off));
            *(float2*)(g_yb + off) = make_float2(d[i * 4 + h * 2] + bb[h] + xv.x, d[i * 4 + h * 2 + 1] + bb[h] + xv.y);
          }
        asm volatile("bar.sync %0, 256;" ::"r"(1) : "memory");
        if (threadIdx.x == 128) red_release(&g_cnt[24 + m]);
      } else if (type == 6) {
        const int st0 = stage;
        for (int k = 0; k < NSTAGE; k++) { mbar_wait(fullb + stage * 8, phase); if (++stage == NSTAGE) { stage = 0; phase ^= 1; } }
        const int seg = m * 8 + (n >> 1), w8 = cw * 4 + warp;
        if (lane == 0) { wait_cnt(&g_cnt[40 + m], 32); wait_cnt(&g_cnt[8 + m], 64); }
        __syncwarp();
        {
          const size_t o = ((size_t)seg * 32 + lane) * HD_ + ((n & 1) * 16 + rank * 8 + w8) * 128;
#pragma unroll
          for (int i = 0; i < 2; i++) {
            asm volatile("prefetch.global.L2 [%0];" ::"l"(g_q + o + i * 64)); asm volatile("prefetch.global.L2 [%0];" ::"l"(g_k + o + i * 64));
            asm volatile("prefetch.global.L2 [%0];" ::"l"(g_v + o + i * 64));
          }
        }
        attn_unit(seg, (n & 1) * 16 + rank * 8 + w8, smem_raw + (sbase - smem_u32(smem_raw)) + w8 * 12288, lane, &g_cnt[96 + seg]);
        asm volatile("fence.proxy.async;" ::: "memory");
        asm volatile("bar.sync %0, 256;" ::"r"(1) : "memory");
        if (elect) for (int k = 0; k < NSTAGE; k++) { mbar_arrive_remote(eb_l + k * 8); mbar_arrive_remote(eb_r + k * 8); }
        if (threadIdx.x == 128) red_release(&g_cnt[16 + m]);
        (void)st0;
#pragma unroll
        for (int i = 0; i < 128; i++) d[i] = 0.f;
      } else if (type == 7) {
        const int nt = n % 3;
        gemm_mainloop<192, 0>(d, 8, sbase, fullb, eb_l, eb_r, cw, stage, phase, elect);
        if (lane == 0) wait_cnt(&g_cnt[24 + m], 6);
        __syncwarp();
        if (p.kid == 2) {
          const int ks = n / 3;
          float* pk = g_pk + ((size_t)ks * 512 + row0 - 1536 + g) * D_ + nt * 192 + t * 2;
#pragma unroll
          for (int i = 0; i < 24; i++)
#pragma unroll
            for (int h = 0; h < 2; h++) *(float2*)(pk + h * 8 * D_ + i * 8) = make_float2(d[i * 4 + h * 2], d[i * 4 + h * 2 + 1]);
          asm volatile("bar.sync %0, 256;" ::"r"(1) : "memory");
          unsigned int* cn = &g_cnt[48 + ((m - 4) * 3 + nt) * 2 + rank];
          if (threadIdx.x == 128) red_release(cn);
          if (lane == 0) wait_cnt(cn, 8);
          __syncwarp();
          const int r0 = m * 256 + rank * 128 + ks * 16;
#pragma unroll
          for (int it = 0; it < 3; it++) {
            int i = threadIdx.x - 128 + it * 256, rr = i / 48, cc = (i - rr * 48) * 4;
            size_t off = (size_t)(r0 + rr) * D_ + nt * 192 + cc;
            float4 y = __ldcg((const float4*)(g_yb + off)), q[8];
#pragma unroll
            for (int k = 0; k < 8; k++) q[k] = __ldcg((const float4*)(g_pk + (size_t)k * 512 * D_ + off - (size_t)1536 * D_));
#pragma unroll
            for (int k = 0; k < 8; k++) { y.x += q[k].x; y.y += q[k].y; y.z += q[k].z; y.w += q[k].w; }
            *(uint2*)(p.out + off) = make_uint2(pack_bf16(y.x, y.y), pack_bf16(y.z, y.w));
          }
          continue;
        }
#pragma unroll
        for (int i = 0; i < 24; i++)
#pragma unroll
          for (int h = 0; h < 2; h++)
            atomicAdd((float2*)(g_yb + (size_t)(row0 + g + h * 8) * D_ + nt * 192 + i * 8 + t * 2), make_float2(d[i * 4 + h * 2], d[i * 4 + h * 2 + 1]));
        __threadfence();
        asm volatile("bar.sync %0, 256;" ::"r"(1) : "memory");
        volatile uint32_t* lastf = (volatile uint32_t*)(smem_raw + (emptyb + 64 - smem_u32(smem_raw)));
        if (threadIdx.x == 128) { *lastf = atomicAdd(&g_cnt[48 + ((m - 4) * 3 + nt) * 2 + rank], 1); __threadfence(); }
        asm volatile("bar.sync %0, 256;" ::"r"(1) : "memory");
        if (*lastf == 7) {
          const int r0 = m * 256 + rank * 128;
#pragma unroll 8
          for (int i = threadIdx.x - 128; i < 128 * 48; i += 256) {
            int rr = i / 48, cc = (i - rr * 48) * 4;
            size_t off = (size_t)(r0 + rr) * D_ + nt * 192 + cc;
            float4 y = __ldcg((const float4*)(g_yb + off));
            *(uint2*)(p.out + off) = make_uint2(pack_bf16(y.x, y.y), pack_bf16(y.z, y.w));
          }
        }
        asm volatile("bar.sync %0, 256;" ::"r"(1) : "memory");
      } else {
        gemm_mainloop<192, 0>(d, 64, sbase, fullb, eb_l, eb_r, cw, stage, phase, elect);
        if (lane == 0) wait_cnt(&g_cnt[24 + m], 6);
        __syncwarp();
        const float* yb = g_yb + (size_t)(row0 + g) * D_ + n * 192 + t * 2;
        store_tile<192>(d, stg, p.out + (size_t)row0 * D_ + n * 192, D_, lane,
                        [&](float a, float b, int h, int c) { float2 y = *(const float2*)(yb + h * 8 * D_ + c); return pack_bf16(a + y.x, b + y.y); });
      }
    }
    if (blockIdx.x == 0 && threadIdx.x == 128) PT(2 + p.kid * 2);
    cluster_sync();
  }
}

constexpr int CH_WV = 0;
constexpr int CH_MEM = CH_WV + 73728;
constexpr int CH_KB = CH_MEM + 9216;
constexpr int CH_VB = CH_KB + 12288;
constexpr int CH_WO = CH_VB + 12288;
constexpr int CH_Q = CH_WO + 81920;
constexpr int CH_R1 = CH_Q + 1024;
constexpr int CH_SC = CH_R1 + 4096;
constexpr int CH_OF = CH_SC + 3584;
constexpr int CH_R2 = CH_OF + 8192;
constexpr int CH_BAR = CH_R2 + 12288;
constexpr int CHAIN_SMEM = CH_BAR + 64 + 1024;
#define POLL_DELAY 480
__device__ __forceinline__ void st_async1(uint32_t a, uint32_t v, uint32_t bar) { asm volatile("st.async.weak.shared::cluster.mbarrier::complete_tx::bytes.b32 [%0], %1, [%2];" ::"r"(a), "r"(v), "r"(bar) : "memory"); }
__device__ __forceinline__ void st_async2(uint32_t a, uint32_t v0, uint32_t v1, uint32_t bar) { asm volatile("st.async.weak.shared::cluster.mbarrier::complete_tx::bytes.v2.b32 [%0], {%1, %2}, [%3];" ::"r"(a), "r"(v0), "r"(v1), "r"(bar) : "memory"); }
__device__ __forceinline__ uint4 lds128(uint32_t a) { uint4 v; asm volatile("ld.shared.v4.u32 {%0,%1,%2,%3}, [%4];" : "=r"(v.x), "=r"(v.y), "=r"(v.z), "=r"(v.w) : "r"(a) : "memory"); return v; }
__device__ __forceinline__ void sts128f(uint32_t a, const float (&c)[4]) { asm volatile("st.shared.v4.f32 [%0], {%1,%2,%3,%4};" ::"r"(a), "f"(c[0]), "f"(c[1]), "f"(c[2]), "f"(c[3]) : "memory"); }
__device__ __forceinline__ void sts32(uint32_t a, uint32_t v) { asm volatile("st.shared.u32 [%0], %1;" ::"r"(a), "r"(v) : "memory"); }
__device__ __forceinline__ void mbar_wait_b(uint32_t b, uint32_t parity) {
  uint32_t ok; int n = 0;
  do { asm volatile("{\n.reg .pred p;\nmbarrier.try_wait.parity.shared::cta.b64 p, [%1], %2;\nselp.u32 %0, 1, 0, p;\n}" : "=r"(ok) : "r"(b), "r"(parity) : "memory"); } while (!ok && ++n < (1 << 20));
}
__device__ __forceinline__ uint32_t mapa_v(uint32_t a, uint32_t r) { uint32_t o; asm volatile("mapa.shared::cluster.u32 %0, %1, %2;" : "=r"(o) : "r"(a), "r"(r)); return o; }
__device__ __forceinline__ uint32_t tid_v() { uint32_t o; asm volatile("mov.u32 %0, %%tid.x;" : "=r"(o)); return o; }
template <int ACC>
__device__ __forceinline__ void wg_rs(float (&d)[4], const uint32_t (&a)[4], uint32_t dlo) {
  uint64_t db = ((uint64_t)16 << 32) | dlo;
  asm volatile("{\n.reg .pred p;\nsetp.ne.b32 p, %9, 0;\nwgmma.mma_async.sync.aligned.m64n8k16.f32.bf16.bf16 {%0,%1,%2,%3}, {%4,%5,%6,%7}, %8, p, 1, 1, 0;\n}"
               : "+f"(d[0]), "+f"(d[1]), "+f"(d[2]), "+f"(d[3]) : "r"(a[0]), "r"(a[1]), "r"(a[2]), "r"(a[3]), "l"(db), "n"(ACC));
}
template <int N>
__device__ __forceinline__ void wg_wait(float (&d)[N][4]) {
  asm volatile("wgmma.commit_group.sync.aligned;\nwgmma.wait_group.sync.aligned 0;" ::: "memory");
#pragma unroll
  for (int i = 0; i < N; i++) asm volatile("" : "+f"(d[i][0]), "+f"(d[i][1]), "+f"(d[i][2]), "+f"(d[i][3]) :: "memory");
}
#define BAR_ALL() asm volatile("bar.sync 0, 256;" ::: "memory")

__global__ void __launch_bounds__(256, 1) chain_kernel(const bf16* __restrict__ mem0, const bf16* __restrict__ Wq, const bf16* __restrict__ Wk,
                                                       const bf16* __restrict__ Wv, const bf16* __restrict__ Wo) {
  extern __shared__ uint8_t smem_raw[];
  const uint32_t sb = (smem_u32(smem_raw) + 1023) & ~1023u;
  const int tid = threadIdx.x, warp = __shfl_sync(~0u, tid >> 5, 0), wgi = __shfl_sync(~0u, tid >> 7, 0), lane = tid & 31, g = lane >> 2, t = lane & 3;
  const uint32_t r = cluster_rank();
  const int c = blockIdx.x >> 3, h = 4 * c + (r >> 1), j0 = h * 128 + (r & 1) * 64;
  const uint32_t bm = sb + CH_BAR, bs = bm + 8, bo = bm + 16;
  pdl_launch();
  if (blockIdx.x == 0 && tid == 0) PT(7);
  if (tid == 0) { mbar_init(bm, 1); mbar_init(bs, 1); mbar_init(bo, 1); asm volatile("fence.mbarrier_init.release.cluster;" ::: "memory"); }
  const int mi = lane >> 3, l7 = lane & 7;
  for (int i = tid; i < 576 * 8; i += 256) {
    int row = i >> 3, ch = i & 7;
    cp16(sb + CH_WV + row * 128 + ((ch ^ (row & 7)) * 16), Wq + (size_t)row * HD_ + j0 + ch * 8);
    cp16(sb + CH_WO + row * 128 + ((ch ^ (row & 7)) * 16), Wk + (size_t)row * HD_ + j0 + ch * 8);
  }
  asm volatile("cp.async.commit_group;\ncp.async.wait_group 0;" ::: "memory");
  BAR_ALL();
  uint32_t w1[36][4];
#pragma unroll
  for (int i = 0; i < 36; i++) {
    int row = i * 16 + (mi >> 1) * 8 + l7, ch = ((warp & 3) * 2 + (mi & 1)) ^ (row & 7);
    ldsm4t(w1[i], sb + (wgi ? CH_WO : CH_WV) + row * 128 + ch * 16);
  }
  BAR_ALL();
  for (int i = tid; i < 512 * 10; i += 256) {
    int row = i / 10, ch = i - row * 10;
    cp16(sb + CH_WV + row * 176 + ch * 16, Wo + (size_t)(c * 512 + row) * D_ + (ch < 8 ? r * 64 + ch * 8 : 512 + (r >> 1) * 16 + (ch - 8) * 8));
  }
  asm volatile("cp.async.commit_group;\ncp.async.wait_group 0;" ::: "memory");
  BAR_ALL();
  const int kperm = 2 * ((mi >> 1) * 2 + (l7 >> 2)) + (l7 & 1) + 8 * ((l7 >> 1) & 1);
  for (int i = 0; i < 16; i++) {
    uint32_t a[4];
    ldsm4t(a, sb + CH_WV + ((wgi * 16 + i) * 16 + kperm) * 176 + ((warp & 3) * 2 + (mi & 1)) * 16);
    asm volatile("st.shared.v4.u32 [%0], {%1,%2,%3,%4};" ::"r"(sb + CH_WO + 8192 + (warp * 16 + i) * 512 + lane * 16), "r"(a[0]), "r"(a[1]), "r"(a[2]), "r"(a[3]) : "memory");
  }
  for (int u = warp; u < 16; u += 8) {
    uint32_t a[4];
    ldsm4t(a, sb + CH_WV + (((r & 1) * 16 + u) * 16 + kperm) * 176 + (8 + (mi & 1)) * 16);
    asm volatile("st.shared.v4.u32 [%0], {%1,%2,%3,%4};" ::"r"(sb + CH_WO + u * 512 + lane * 16), "r"(a[0]), "r"(a[1]), "r"(a[2]), "r"(a[3]) : "memory");
  }
  BAR_ALL();
  for (int i = tid; i < 576 * 8; i += 256) {
    int row = i >> 3, ch = i & 7;
    cp16(sb + CH_WV + row * 128 + ((ch ^ (row & 7)) * 16), Wv + (size_t)row * HD_ + j0 + ch * 8);
  }
  for (int i = tid; i < 8 * 72; i += 256) {
    int row = i / 72, ch = i - row * 72;
    cp16(sb + CH_MEM + ch * 128 + row * 16, mem0 + row * D_ + ch * 8);
  }
  for (int i = tid; i < 4 * 64; i += 256) {
    int b = i >> 6, o = i & 63;
    asm volatile("st.shared.v4.u32 [%0], {%1,%1,%1,%1};" ::"r"(sb + CH_KB + b * 6144 + 40 * 128 + o * 16), "r"(0) : "memory");
  }
  auto prefetch_kv = [&](int s, int tid) {
    if ((s & 7) == 0) { if ((tid & 31) == 0) wait_cnt(&g_cnt[8 + (s >> 3)], 64); __syncwarp(); }
#pragma unroll
    for (int i = 0; i < 2; i++) {
      int u = tid + i * 256, which = u >> 8, row = (u & 255) >> 3, ch = u & 7;
      const bf16* src = (which ? g_v : g_k) + (size_t)(s * 32 + row) * HD_ + j0 + ch * 8;
      cp16(sb + (which ? CH_VB : CH_KB) + (s & 1) * 6144 + (row + 8) * 128 + ((ch ^ (row & 7)) * 16), src);
    }
    asm volatile("cp.async.commit_group;" ::: "memory");
  };
  prefetch_kv(0, tid);
  asm volatile("cp.async.wait_group 0;" ::: "memory");
  asm volatile("fence.proxy.async.shared::cta;" ::: "memory");
  BAR_ALL();
  cluster_sync();
  const uint32_t dsb = ((sb & 0x3FFFF) >> 4) | (8u << 16);
  if (blockIdx.x == 0 && tid == 0) PT(10);
#define CP(i) if (blockIdx.x == 0 && lane == 0 && warp == (((i) == 5 || (i) == 7) ? 4 : 0)) PC(64 + s * 16 + (i))
  for (int s = 0; s < NSEG; s++) {
    const int tid = tid_v(), lane = tid & 31, g = lane >> 2, t = lane & 3, mi = lane >> 3, l7 = lane & 7;
    CP(0);
    const uint32_t par = s & 1, kb = sb + CH_KB + par * 6144, vb = sb + CH_VB + par * 6144;
    if (s > 0) mbar_wait_b(bm, par ^ 1);
    CP(1);
    if (tid == 0 && s < NSEG - 1) { mbar_expect(bs, 2560); mbar_expect(bo, 8192); mbar_expect(bm, 9216); }
    auto phase1 = [&]() {
      float pa[3][4] = {};
#pragma unroll
      for (int i = 0; i < 36; i += 2) {
        uint32_t b[4];
        ldsm4(b, sb + CH_MEM + i * 256 + mi * 128 + l7 * 16);
        mma16816(pa[i % 3], w1[i], b[0], b[1]); mma16816(pa[(i + 1) % 3], w1[i + 1], b[2], b[3]);
      }
      CP(2);
      uint32_t b0 = movm(pack_bf16(pa[0][0] + pa[1][0] + pa[2][0], pa[0][1] + pa[1][1] + pa[2][1]));
      uint32_t b1 = movm(pack_bf16(pa[0][2] + pa[1][2] + pa[2][2], pa[0][3] + pa[1][3] + pa[2][3]));
      uint32_t dst = (wgi ? kb : sb + CH_Q) + g * 128 + t * 4;
      sts32(dst + ((((warp & 3) * 2) ^ g) * 16), b0); sts32(dst + ((((warp & 3) * 2 + 1) ^ g) * 16), b1);
      if (wgi) { uint32_t* gp = (uint32_t*)(g_km + ((size_t)s * 8 + g) * HD_ + j0 + (warp & 3) * 16 + t * 2); gp[0] = b0; gp[4] = b1; }
      asm volatile("cp.async.wait_group 0;" ::: "memory");
    };
    if (wgi == 0) {
      phase1();
      BAR_ALL();
      CP(4);
      if (s + 1 < NSEG) { prefetch_kv(s + 1, tid); asm volatile("bar.sync 6, 224;" ::: "memory"); }
      float va[4][4];
      asm volatile("wgmma.fence.sync.aligned;" ::: "memory");
      const uint32_t dwa = (((sb + CH_WV) & 0x3FFFF) >> 4) | ((8192u >> 4) << 16);
#pragma unroll
      for (int ks = 0; ks < 36; ks++) {
        uint64_t da = ((uint64_t)(0x40000000u | (1024 >> 4)) << 32) | (dwa + ks * 128), db = ((uint64_t)16 << 32) | (dsb + ((CH_MEM + ks * 256) >> 4));
        if (ks < 4)
          asm volatile("{\n.reg .pred p;\nsetp.ne.b32 p, 0, 0;\nwgmma.mma_async.sync.aligned.m64n8k16.f32.bf16.bf16 {%0,%1,%2,%3}, %4, %5, p, 1, 1, 1, 0;\n}"
                       : "=f"(va[ks & 3][0]), "=f"(va[ks & 3][1]), "=f"(va[ks & 3][2]), "=f"(va[ks & 3][3]) : "l"(da), "l"(db));
        else
          asm volatile("{\n.reg .pred p;\nsetp.ne.b32 p, 1, 0;\nwgmma.mma_async.sync.aligned.m64n8k16.f32.bf16.bf16 {%0,%1,%2,%3}, %4, %5, p, 1, 1, 1, 0;\n}"
                       : "+f"(va[ks & 3][0]), "+f"(va[ks & 3][1]), "+f"(va[ks & 3][2]), "+f"(va[ks & 3][3]) : "l"(da), "l"(db));
      }
      wg_wait(va);
      CP(6);
      uint32_t b0 = movm(pack_bf16(va[0][0] + va[1][0] + va[2][0] + va[3][0], va[0][1] + va[1][1] + va[2][1] + va[3][1]));
      uint32_t b1 = movm(pack_bf16(va[0][2] + va[1][2] + va[2][2] + va[3][2], va[0][3] + va[1][3] + va[2][3] + va[3][3]));
      sts32(vb + g * 128 + t * 4 + (((warp * 2) ^ g) * 16), b0); sts32(vb + g * 128 + t * 4 + (((warp * 2 + 1) ^ g) * 16), b1);
      uint32_t* gp = (uint32_t*)(g_vm + ((size_t)s * 8 + g) * HD_ + j0 + warp * 16 + t * 2); gp[0] = b0; gp[4] = b1;
      asm volatile("bar.arrive 7, 256;" ::: "memory");
    } else {
      phase1();
      BAR_ALL();
      if (warp == 7 && lane == 0 && s > 0) { __threadfence(); atomicAdd(&g_cnt[96 + s - 1], 1); }
      if (warp < 7 && s < NSEG - 1) {
        const int mt = warp - 4;
        const uint32_t sc_l = mapa_v(sb + CH_SC + (r & 1) * 1792, r), sc_r = mapa_v(sb + CH_SC + (r & 1) * 1792, r ^ 1), bs_l = mapa_v(bs, r), bs_r = mapa_v(bs, r ^ 1);
        float sa[4][4] = {};
#pragma unroll
        for (int kp = 0; kp < 2; kp++) {
          uint32_t b[4], a0[4], a1[4];
          ldsm4(b, sb + CH_Q + l7 * 128 + (((kp * 4 + mi) ^ l7) * 16));
          int row = mt * 16 + (mi & 1) * 8 + l7;
          ldsm4(a0, kb + row * 128 + (((kp * 4 + (mi >> 1)) ^ l7) * 16));
          ldsm4(a1, kb + row * 128 + (((kp * 4 + 2 + (mi >> 1)) ^ l7) * 16));
          mma16816(sa[2 * kp], a0, b[0], b[1]); mma16816(sa[2 * kp + 1], a1, b[2], b[3]);
        }
        asm volatile("bar.arrive 6, 224;" :: "f"(sa[0][0]), "f"(sa[1][0]), "f"(sa[2][0]), "f"(sa[3][0]) : "memory");
#pragma unroll
        for (int e = 0; e < 4; e++) {
          uint32_t off = ((2 * t + (e & 1)) * 56 + mt * 16 + (e >> 1) * 8 + g) * 4, v = __float_as_uint((sa[0][e] + sa[1][e]) + (sa[2][e] + sa[3][e]));
          if (mt < 2 || e < 2) { st_async1(sc_r + off, v, bs_r); st_async1(sc_l + off, v, bs_l); }
        }
        CP(5);
      }
      if (s < NSEG - 1) {
        prefetch_kv(s + 1, tid);
        const int w3 = warp & 3;
        uint32_t vt[3][4];
#pragma unroll
        for (int kk = 1; kk < 3; kk++) { int row = kk * 16 + (mi >> 1) * 8 + l7; ldsm4t(vt[kk], vb + row * 128 + (((w3 * 2 + (mi & 1)) ^ l7) * 16)); }
        mbar_wait_b(bs, par);
        CP(7);
        float z[10]; float mx = -INFINITY;
        const float scl = 0.08838834764831845f * 1.4426950408889634f;
#pragma unroll
        for (int i = 0; i < 5; i++) {
          float2 u0, u1; uint32_t a = sb + CH_SC + (g * 56 + i * 8 + 2 * t) * 4;
          asm volatile("ld.shared.v2.f32 {%0,%1}, [%2];" : "=f"(u0.x), "=f"(u0.y) : "r"(a) : "memory");
          asm volatile("ld.shared.v2.f32 {%0,%1}, [%2];" : "=f"(u1.x), "=f"(u1.y) : "r"(a + 1792) : "memory");
          z[2 * i] = (u0.x + u1.x) * scl; z[2 * i + 1] = (u0.y + u1.y) * scl;
        }
        mx = fmaxf(fmaxf(fmaxf(z[0], z[1]), fmaxf(z[2], z[3])), fmaxf(fmaxf(fmaxf(z[4], z[5]), fmaxf(z[6], z[7])), fmaxf(z[8], z[9])));
        mx = fmaxf(mx, __shfl_xor_sync(~0u, mx, 1)); mx = fmaxf(mx, __shfl_xor_sync(~0u, mx, 2));
        uint32_t pb[5];
#pragma unroll
        for (int i = 0; i < 5; i++) pb[i] = pack_bf16(exp2f(z[2 * i] - mx), exp2f(z[2 * i + 1] - mx));
        const uint32_t ones[4] = {0x3F803F80u, 0x3F803F80u, 0x3F803F80u, 0x3F803F80u};
        float o0[4] = {}, o1[4] = {}, o2[4] = {}, s0[4] = {}, s1[4] = {}, s2[4] = {};
        mma16816(s0, ones, pb[0], pb[1]);
        mma16816(o1, vt[1], pb[2], pb[3]); mma16816(s1, ones, pb[2], pb[3]);
        mma16816(o2, vt[2], pb[4], 0u); mma16816(s2, ones, pb[4], 0u);
        asm volatile("bar.sync 7, 256;" ::: "memory");
        ldsm4t(vt[0], vb + ((mi >> 1) * 8 + l7) * 128 + (((w3 * 2 + (mi & 1)) ^ l7) * 16));
        mma16816(o0, vt[0], pb[0], pb[1]);
        const float i0 = __fdividef(1.f, s0[0] + s1[0] + s2[0]), i1 = __fdividef(1.f, s0[1] + s1[1] + s2[1]);
        uint32_t f0 = movm(pack_bf16((o0[0] + o1[0] + o2[0]) * i0, (o0[1] + o1[1] + o2[1]) * i1));
        uint32_t f1 = movm(pack_bf16((o0[2] + o1[2] + o2[2]) * i0, (o0[3] + o1[3] + o2[3]) * i1));
        const int ks = r * 4 + w3;
        const uint32_t off = CH_OF + ks * 256 + (t >> 1) * 128 + g * 16 + (t & 1) * 8;
        const uint32_t cl0 = mapa_v(sb, 0), clstep = mapa_v(sb, 1) - cl0;
#pragma unroll
        for (int d = 0; d < 8; d++) st_async2(cl0 + d * clstep + off, f0, f1, cl0 + d * clstep + CH_BAR + 16);
      } else asm volatile("bar.sync 7, 256;" ::: "memory");
    }
    if (s == NSEG - 1) break;
    CP(8);
    uint32_t wo[16][4];
#pragma unroll
    for (int i = 0; i < 16; i++) { uint4 v = lds128(sb + CH_WO + 8192 + (warp * 16 + i) * 512 + lane * 16); wo[i][0] = v.x; wo[i][1] = v.y; wo[i][2] = v.z; wo[i][3] = v.w; }
    mbar_wait_b(bo, par);
    CP(9);
    const uint32_t tag = ((s >> 1) + 1) & 1;
    float* pbase = g_part + (size_t)par * 8 * 5120 + lane * 4;
    auto put = [&](int slot, const float (&a)[4]) {
      asm volatile("st.relaxed.gpu.global.v4.b32 [%0], {%1,%2,%3,%4};" ::"l"(pbase + c * 5120 + slot * 128), "r"((__float_as_uint(a[0]) & ~1u) | tag),
                   "r"((__float_as_uint(a[1]) & ~1u) | tag), "r"((__float_as_uint(a[2]) & ~1u) | tag), "r"((__float_as_uint(a[3]) & ~1u) | tag) : "memory");
    };
    {
      float acc[4][4];
      asm volatile("wgmma.fence.sync.aligned;" ::: "memory");
      const uint32_t dof = dsb + ((CH_OF >> 4) + wgi * 256);
#pragma unroll
      for (int i = 0; i < 16; i++) { if (i < 4) wg_rs<0>(acc[i & 3], wo[i], dof + i * 16); else wg_rs<1>(acc[i & 3], wo[i], dof + i * 16); }
      wg_wait(acc);
#pragma unroll
      for (int e = 0; e < 4; e++) acc[0][e] = (acc[0][e] + acc[1][e]) + (acc[2][e] + acc[3][e]);
      CP(10);
      const int w3 = warp & 3;
      if (wgi) {
        sts128f(sb + CH_R2 + w3 * 512 + lane * 16, acc[0]);
        asm volatile("bar.arrive %0, 64;" ::"r"(1 + w3) : "memory");
        if (w3 < 2) {
          float ex[2][4] = {};
#pragma unroll
          for (int i = 0; i < 8; i += 2) {
            uint32_t b[4]; ldsm4(b, sb + CH_OF + ((r & 1) * 16 + w3 * 8 + i) * 256 + mi * 128 + l7 * 16);
            uint4 v0 = lds128(sb + CH_WO + (w3 * 8 + i) * 512 + lane * 16), v1 = lds128(sb + CH_WO + (w3 * 8 + i + 1) * 512 + lane * 16);
            uint32_t a0[4] = {v0.x, v0.y, v0.z, v0.w}, a1[4] = {v1.x, v1.y, v1.z, v1.w};
            mma16816(ex[0], a0, b[0], b[1]); mma16816(ex[1], a1, b[2], b[3]);
          }
#pragma unroll
          for (int e = 0; e < 4; e++) ex[0][e] += ex[1][e];
          if (w3 == 1) { sts128f(sb + CH_R2 + 4 * 512 + lane * 16, ex[0]); asm volatile("bar.arrive 5, 64;" ::: "memory"); }
          else {
            asm volatile("bar.sync 5, 64;" ::: "memory");
            uint4 v = lds128(sb + CH_R2 + 4 * 512 + lane * 16);
            ex[0][0] += __uint_as_float(v.x); ex[0][1] += __uint_as_float(v.y); ex[0][2] += __uint_as_float(v.z); ex[0][3] += __uint_as_float(v.w);
            put(32 + r, ex[0]);
          }
        }
      } else {
        asm volatile("bar.sync %0, 64;" ::"r"(1 + w3) : "memory");
        uint4 v = lds128(sb + CH_R2 + w3 * 512 + lane * 16);
        acc[0][0] += __uint_as_float(v.x); acc[0][1] += __uint_as_float(v.y); acc[0][2] += __uint_as_float(v.z); acc[0][3] += __uint_as_float(v.w);
        put(r * 4 + w3, acc[0]);
      }
    }
    CP(11);
    if (warp < 4 || warp == 6) { long long t0 = clock64(); while (clock64() - t0 < POLL_DELAY) {} }
    if (warp < 4) {
      const float* pb = pbase + (r * 4 + warp) * 128;
      uint4 v[8]; int n = 0; uint32_t need = 0xFF;
#pragma unroll
      for (int i = 0; i < 8; i++) v[i] = make_uint4(0, 0, 0, 0);
      do {
#pragma unroll
        for (int i = 0; i < 8; i++)
          asm volatile("{\n.reg .pred p;\nsetp.ne.b32 p, %5, 0;\n@p ld.relaxed.gpu.global.v4.b32 {%0,%1,%2,%3}, [%4];\n}" : "+r"(v[i].x), "+r"(v[i].y), "+r"(v[i].z), "+r"(v[i].w) : "l"(pb + i * 5120), "r"(need & (1u << i)) : "memory");
#pragma unroll
        for (int i = 0; i < 8; i++) {
          bool ok = ((v[i].x & v[i].y & v[i].z & v[i].w & 1u) == tag) && (((v[i].x | v[i].y | v[i].z | v[i].w) & 1u) == tag);
          if (__all_sync(~0u, ok)) need &= ~(1u << i);
        }
      } while (need && ++n < (1 << 18));
      float m[4] = {};
#pragma unroll
      for (int i = 0; i < 8; i++) { m[0] += __uint_as_float(v[i].x); m[1] += __uint_as_float(v[i].y); m[2] += __uint_as_float(v[i].z); m[3] += __uint_as_float(v[i].w); }
      __syncwarp();
      CP(12);
      uint32_t b0 = movm(pack_bf16(m[0], m[1])), b1 = movm(pack_bf16(m[2], m[3]));
      const uint32_t off = CH_MEM + (r * 4 + warp) * 256 + g * 16 + t * 4;
      const uint32_t cl0 = mapa_v(sb, 0), clstep = mapa_v(sb, 1) - cl0;
#pragma unroll
      for (int d = 0; d < 8; d++) { st_async1(cl0 + d * clstep + off, b0, cl0 + d * clstep + CH_BAR); st_async1(cl0 + d * clstep + off + 128, b1, cl0 + d * clstep + CH_BAR); }
    } else if (warp == 6) {
      const float* pb = pbase - lane * 4 + (32 + (r & ~1u)) * 128 + lane * 4 + (r & 1) * 2;
      uint2 v[16]; int n = 0; uint32_t need = 0xFF;
#pragma unroll
      for (int i = 0; i < 16; i++) v[i] = make_uint2(0, 0);
      do {
#pragma unroll
        for (int i = 0; i < 16; i++)
          asm volatile("{\n.reg .pred p;\nsetp.ne.b32 p, %3, 0;\n@p ld.relaxed.gpu.global.v2.b32 {%0,%1}, [%2];\n}" : "+r"(v[i].x), "+r"(v[i].y) : "l"(pb + (i >> 1) * 5120 + (i & 1) * 128), "r"(need & (1u << (i >> 1))) : "memory");
#pragma unroll
        for (int i = 0; i < 16; i += 2) {
          bool ok = ((v[i].x & v[i].y & v[i + 1].x & v[i + 1].y & 1u) == tag) && (((v[i].x | v[i].y | v[i + 1].x | v[i + 1].y) & 1u) == tag);
          if (__all_sync(~0u, ok)) need &= ~(1u << (i >> 1));
        }
      } while (need && ++n < (1 << 18));
      float m0 = 0.f, m1 = 0.f;
#pragma unroll
      for (int i = 0; i < 16; i++) { m0 += __uint_as_float(v[i].x); m1 += __uint_as_float(v[i].y); }
      __syncwarp();
      uint32_t b0 = movm(pack_bf16(m0, m1));
      const uint32_t off = CH_MEM + (32 + (r >> 1)) * 256 + (r & 1) * 128 + g * 16 + t * 4;
      const uint32_t cl0 = mapa_v(sb, 0), clstep = mapa_v(sb, 1) - cl0;
#pragma unroll
      for (int d = 0; d < 8; d++) st_async1(cl0 + d * clstep + off, b0, cl0 + d * clstep + CH_BAR);
    }
  }
  BAR_ALL();
  if (tid == 0) { __threadfence(); atomicAdd(&g_cnt[96 + NSEG - 1], 1); }
  if (blockIdx.x == 0 && tid == 0) PT(8);
  cluster_sync();
}
typedef CUresult (*EncodeFn)(CUtensorMap*, CUtensorMapDataType, cuuint32_t, void*, const cuuint64_t*, const cuuint64_t*, const cuuint32_t*, const cuuint32_t*,
                             CUtensorMapInterleave, CUtensorMapSwizzle, CUtensorMapL2promotion, CUtensorMapFloatOOBfill);
static EncodeFn g_enc;
static void mkmap(CUtensorMap* m, const void* ptr, int rows, int cols, int boxc, int boxr) {
  cuuint64_t dims[2] = {(cuuint64_t)cols, (cuuint64_t)rows}, strides[1] = {(cuuint64_t)cols * 2};
  cuuint32_t box[2] = {(cuuint32_t)boxc, (cuuint32_t)boxr}, es[2] = {1, 1};
  g_enc(m, CU_TENSOR_MAP_DATA_TYPE_BFLOAT16, 2, (void*)ptr, dims, strides, box, es, CU_TENSOR_MAP_INTERLEAVE_NONE, CU_TENSOR_MAP_SWIZZLE_128B,
        CU_TENSOR_MAP_L2_PROMOTION_L2_256B, CU_TENSOR_MAP_FLOAT_OOB_FILL_NONE);
}
#define URG 45.0
#define CHDT 3.7
constexpr int NATT = 112;
constexpr double CH_T0 = 24.0, CH_DT = CHDT;
static inline uint16_t mkjob(int type, int m, int n) { return (uint16_t)(type << 12 | m << 6 | n); }
static void schedule_side(GemmParams& p, const uint16_t* base, int nb, int ncl) {
  static const double cost[8] = {7.6, 7.6, 7.6, 19.5, 56.0, 33.0, 12.5, 7.0};
  double t[66]; int cnt[66] = {};
  for (int c = 0; c < 66; c++) t[c] = 9.0;
  p.stride = 960 / ncl;
  for (int i = 0; i < 960; i++) p.job[i] = 0xFFFF;
  double g2_end = 0, q_end[8] = {}, g3_end[8] = {}, at_end[8] = {}; int qn[8] = {}, g3n[8] = {}, atn[8] = {};
  int bi = 0, ai = 0, gi = 0;
  while (bi < nb || ai < NATT || gi < 60) {
    int b = -1;
    for (int c = 0; c < ncl; c++) if (cnt[c] < p.stride && (b < 0 || t[c] < t[b] || (t[c] == t[b] && cnt[c] < cnt[b]))) b = c;
    const double inf = 1e30;
    int am = ai >> 4, gm = gi < 12 ? gi / 3 : 4 + (gi - 12) / 24;
    double ra = ai < NATT && qn[am] == 16 ? (q_end[am] > CH_T0 + CH_DT * (am * 8 + ((ai & 15) >> 1) + 2) ? q_end[am] : CH_T0 + CH_DT * (am * 8 + ((ai & 15) >> 1) + 2)) : inf;
    double rg = gi < 60 && atn[gm] == 16 && g3n[gm] == 3 ? (at_end[gm] > g3_end[gm] - 30 ? at_end[gm] : g3_end[gm] - 30) : inf;
    bool urgent = bi < nb && (base[bi] >> 12) >= 1 && (base[bi] >> 12) <= 2 && CH_T0 + CH_DT * 8 * ((base[bi] >> 6) & 63) - t[b] < URG;
    uint16_t job; double start = t[b];
    if (urgent) job = base[bi++];
    else if (rg <= t[b] || (bi >= nb && rg < inf && (rg <= ra || (gi < 60 && ai >= NATT)))) { job = gi < 12 ? mkjob(5, gm, gi % 3) : mkjob(7, gm, (gi - 12) % 24); gi++; if (rg > start) start = rg; }
    else if (ai < NATT && (ra <= t[b] || bi >= nb)) { job = mkjob(6, am, ai & 15); ai++; if (ra > start) start = ra; }
    else job = base[bi++];
    int ty = job >> 12, m = (job >> 6) & 63;
    if (ty == 4 && start < g2_end) start = g2_end;
    t[b] = start + cost[ty];
    if (ty == 3 && t[b] > g2_end) g2_end = t[b];
    if (ty == 0) { qn[m]++; if (t[b] > q_end[m]) q_end[m] = t[b]; }
    if (ty == 4) { g3n[m]++; if (t[b] > g3_end[m]) g3_end[m] = t[b]; }
    if (ty == 6) { atn[m]++; if (t[b] > at_end[m]) at_end[m] = t[b]; }
    p.job[b * p.stride + cnt[b]++] = job;
  }
}
template <class... A>
static void launch(void (*k)(A...), int grid, int block, int smem, int cluster, bool pdl, A... a) {
  cudaLaunchConfig_t c = {};
  c.gridDim = grid; c.blockDim = block; c.dynamicSmemBytes = smem; c.stream = cudaStreamPerThread;
  cudaLaunchAttribute at[2]; int n = 0;
  if (cluster > 1) { at[n].id = cudaLaunchAttributeClusterDimension; at[n].val.clusterDim.x = cluster; at[n].val.clusterDim.y = 1; at[n].val.clusterDim.z = 1; n++; }
  if (pdl) { at[n].id = cudaLaunchAttributeProgrammaticStreamSerialization; at[n].val.programmaticStreamSerializationAllowed = 1; n++; }
  c.attrs = at; c.numAttrs = n;
  cudaLaunchKernelEx(&c, k, a...);
}

extern "C" void kernel_launch(void* const* d_in, const int* in_sizes, int n_in, void* d_out, int out_size) {
  const bf16 *x = (const bf16*)d_in[0], *mem0 = (const bf16*)d_in[1], *Wq = (const bf16*)d_in[2], *Wk = (const bf16*)d_in[3], *Wv = (const bf16*)d_in[4],
             *Wo = (const bf16*)d_in[5], *w1 = (const bf16*)d_in[8], *b1 = (const bf16*)d_in[9], *w2 = (const bf16*)d_in[10], *b2 = (const bf16*)d_in[11];
  static bool init = false;
  static GemmParams side, post;
  if (!init) {
    init = true;
    cudaDriverEntryPointQueryResult qr;
    cudaGetDriverEntryPoint("cuTensorMapEncodeTiled", (void**)&g_enc, cudaEnableDefault, &qr);
    void *xn, *h2, *o, *ut;
    cudaGetSymbolAddress(&xn, g_xn); cudaGetSymbolAddress(&h2, g_h2); cudaGetSymbolAddress(&o, g_o); cudaGetSymbolAddress(&ut, g_ut);
    GemmParams b = {};
    mkmap(&b.mA[0], xn, S_, D_, 64, 128); mkmap(&b.mA[1], w1, S_, F_, 64, 64); mkmap(&b.mA[2], w2, F_, S_, 64, 64); mkmap(&b.mA[3], o, S_, HD_, 64, 128);
    mkmap(&b.mB[0], Wq, D_, HD_, 64, 32); mkmap(&b.mB[1], Wk, D_, HD_, 64, 32); mkmap(&b.mB[2], Wv, D_, HD_, 64, 32);
    mkmap(&b.mB[3], h2, S_, D_, 64, 32); mkmap(&b.mB[4], ut, F_, D_, 64, 32); mkmap(&b.mB[5], Wo, HD_, D_, 64, 32);
    b.x = x; b.b1 = b1; b.b2 = b2; b.out = (bf16*)d_out;
    side = b; post = b; side.kid = 1; post.kid = 2;
    static uint16_t jl[1024]; int n = 0;
    auto kv = [&](int m) { for (int j = 0; j < 16; j++) { jl[n++] = mkjob(1, m, j); jl[n++] = mkjob(2, m, j); } };
    auto qq = [&](int m) { for (int j = 0; j < 16; j++) jl[n++] = mkjob(0, m, j); };
    kv(0); kv(1);
    for (int m = 0; m < 18; m++) for (int j = 0; j < 3; j++) jl[n++] = mkjob(3, m, j);
    kv(2); qq(0); kv(3); qq(1);
    for (int m = 0; m < 8; m++) for (int j = 0; j < 3; j++) jl[n++] = mkjob(4, m, j);
    for (int m = 4; m < 8; m++) { kv(m); qq(m - 2); }
    qq(6); qq(7);
    schedule_side(side, jl, n, 34);
    side.wait_at_end = 0;
    post.stride = 2;
    for (int i = 0; i < 960; i++) post.job[i] = 0xFFFF;
    for (int i = 0; i < 48; i++) {
      const uint16_t g4 = i < 24 ? mkjob(7, 7, i) : mkjob(7, 6, i - 24);
      if (i < 16) { post.job[i * 2] = mkjob(6, 7, 15 - i); post.job[i * 2 + 1] = g4; }
      else post.job[i * 2] = g4;
    }
    cudaFuncSetAttribute(gemm_kernel, cudaFuncAttributeMaxDynamicSharedMemorySize, GEMM_SMEM);
    cudaFuncSetAttribute(chain_kernel, cudaFuncAttributeMaxDynamicSharedMemorySize, CHAIN_SMEM);
  }
  launch(ln_kernel, 256, 256, 0, 1, false, x);
  launch(chain_kernel, 64, 256, CHAIN_SMEM, 8, false, mem0, Wq, Wk, Wv, Wo);
  launch(gemm_kernel, 68, 384, GEMM_SMEM, 2, true, side);
  launch(gemm_kernel, 96, 384, GEMM_SMEM, 2, true, post);
}
```
